```python
import torch

def _softmax(x, axis=-1):
    return torch.softmax(x, dim=axis)
def _gelu(x):
    return torch.nn.functional.gelu(x, approximate="tanh")
def _silu(x):
    return torch.nn.functional.silu(x)
def _sigmoid(x):
    return torch.sigmoid(x)
def _layernorm(x, axis=-1, eps=1e-5):
    m = x.mean(dim=axis, keepdim=True)
    v = x.var(dim=axis, keepdim=True, unbiased=False)
    return (x - m) / torch.sqrt(v + eps)
def _scatter_add(tgt, idx, src, axis=0):
    return tgt.clone().index_add_(axis, idx, src)
def _segment_sum(src, seg, n):
    out = torch.zeros((n,) + src.shape[1:], dtype=src.dtype)
    return out.index_add_(0, seg, src)
def _pad(x, pw):
    flat = tuple(v for pair in reversed(pw) for v in pair)
    return torch.nn.functional.pad(x, flat)

kernel_name = 'sequential_preLN__compressed_kv_cla__moe_arch_mod__prompt'

def setup_inputs():

    _w = (lambda a: (lambda t: t.to(torch.bfloat16) if t.is_floating_point() else t)(torch.as_tensor(a)))
    def _A_setup():
        B, H, Sq, Sk, D, M = 1, 32, 2048, 2048, 128, 1024
        Dc = 4 * D
        return {
            "x": _w((lambda *s: torch.randn(*s, dtype=torch.bfloat16) * 0.1)(B, Sq, M)),
            "c_kv": _w((lambda *s: torch.randn(*s, dtype=torch.bfloat16) * 1.6)(B, Sk, Dc)),
            "w_q": _w((lambda *s: torch.randn(*s, dtype=torch.bfloat16) * 0.8)(M, H, D) * (M ** -0.5)),
            "w_uk": _w((lambda *s: torch.randn(*s, dtype=torch.bfloat16) * 0.8)(Dc, H, D) * (Dc ** -0.5)),
            "w_uv": _w((lambda *s: torch.randn(*s, dtype=torch.bfloat16) * 1.6)(Dc, H, D) * (Dc ** -0.5)),
            "w_o": _w((lambda *s: torch.randn(*s, dtype=torch.bfloat16) * 1.6)(H, D, M) * ((H * D) ** -0.5)),
        }
    _A_in = _A_setup()

    def _B_setup():
        B, S, D, F, C = 1, 2048, 1024, 3584, 2
        return {
            "x": _w((lambda *s: torch.randn(*s, dtype=torch.bfloat16) * 0.1)(B, S, D)),
            "w_r": _w((lambda *s: torch.randn(*s, dtype=torch.bfloat16) * 0.2)(D)),
            "w_gate": _w((lambda *s: torch.randn(*s, dtype=torch.bfloat16) * 0.2)(D, F)),
            "w_up": _w((lambda *s: torch.randn(*s, dtype=torch.bfloat16) * 0.2)(D, F)),
            "w_down": _w((lambda *s: torch.randn(*s, dtype=torch.bfloat16) * 0.2)(F, D)),
        }
    _B_in = _B_setup()

    return {
        "A_x": _A_in["x"],
        "A_c_kv": _A_in["c_kv"],
        "A_w_q": _A_in["w_q"],
        "A_w_uk": _A_in["w_uk"],
        "A_w_uv": _A_in["w_uv"],
        "A_w_o": _A_in["w_o"],
        "B_x": _B_in["x"],
        "B_w_r": _B_in["w_r"],
        "B_w_gate": _B_in["w_gate"],
        "B_w_up": _B_in["w_up"],
        "B_w_down": _B_in["w_down"],
    }

def reference(A_x, A_c_kv, A_w_q, A_w_uk, A_w_uv, A_w_o, B_x, B_w_r, B_w_gate, B_w_up, B_w_down):
    def _A_ref(x, c_kv, w_q, w_uk, w_uv, w_o):
        B, Sq, M = x.shape[0], x.shape[1], x.shape[2]
        Sk = c_kv.shape[1]
        H, D = w_q.shape[1], w_q.shape[2]
        q = torch.einsum("bqm,mhd->bhqd", x, w_q)
        k = torch.einsum("bkc,chd->bhkd", c_kv, w_uk)
        v = torch.einsum("bkc,chd->bhkd", c_kv, w_uv)
        scores = torch.einsum("bhqd,bhkd->bhqk", q, k) * (D ** -0.5)
        off = Sk - Sq
        qi = torch.arange(Sq)[:, None]
        kj = torch.arange(Sk)[None, :]
        cmask = kj <= (qi + off)
        scores = torch.where(cmask[None, None], scores, -1e9)
        p = _softmax(scores, axis=-1)
        ctx = torch.einsum("bhqk,bhkd->bhqd", p, v)
        return torch.einsum("bhqd,hdm->bqm", ctx, w_o)

    def _B_ref(x, w_r, w_gate, w_up, w_down):
        B, S, D = x.shape
        C = 2
        r = x @ w_r
        idx = torch.argsort(-r, axis=-1)[:, :C]
        idx_e = (lambda x, n, axis: torch.repeat_interleave(x, n, dim=axis))(idx.reshape(B, C, 1), D, axis=2)
        x_sel = (lambda x, i, axis: torch.take_along_dim(x, i, dim=axis))(x, idx_e, axis=1)
        g = _silu(x_sel @ w_gate)
        u = x_sel @ w_up
        y = (g * u) @ w_down
        r_sel = _sigmoid((lambda x, i, axis: torch.take_along_dim(x, i, dim=axis))(r, idx, axis=1))
        y = y * r_sel.reshape(B, C, 1)
        b_off = (torch.arange(B) * S).reshape(B, 1)
        flat_idx = (idx + b_off).reshape(B * C)
        zero = (x * 0.0).reshape(B * S, D)
        upd = _scatter_add(zero, flat_idx, y.reshape(B * C, D), axis=0)
        return x + upd.reshape(B, S, D)

    x = A_x
    h = x + _A_ref(_layernorm(x, axis=-1), A_c_kv, A_w_q, A_w_uk, A_w_uv, A_w_o)
    h2 = h + _B_ref(_layernorm(h, axis=-1), B_w_r, B_w_gate, B_w_up, B_w_down)
    return h2
```

```cpp
#include <cuda_runtime.h>
#include <cuda_bf16.h>
#include <cuda.h>
#include <stdint.h>
#include <type_traits>

#pragma nv_diag_suppress 549
namespace {

constexpr int SEQ = 2048, DM = 1024, NH = 32, HD = 128, DC = 512, NQ = NH * HD, FF = 3584;

__device__ __align__(1024) __nv_bfloat16 g_xn[SEQ * DM];
__device__ __align__(1024) __nv_bfloat16 g_qkv[3 * SEQ * NQ];
constexpr int XR_PS = 0;
constexpr int XR_KEY = 128;
constexpr int XR_CAND = 136;
constexpr int XR_Y = 648;
constexpr int XR_SIZE = 1104;
__device__ __align__(1024) uint4 g_xr[128 * XR_SIZE];
constexpr int C_LN = 0, C_QKV = 16, C_CTX = 32, C_NUM = 64;
__device__ unsigned g_cnt[C_NUM];

#define TL(k, i, cond) do {} while (0)
#define TC(w, g, i) do {} while (0)
#define TCF(w, g) do {} while (0)
#define TS(i) do {} while (0)
#undef TCLK
#define TCLK 0

__device__ __forceinline__ uint32_t s2u(const void* p) { return (uint32_t)__cvta_generic_to_shared(p); }
__device__ __forceinline__ void mbar_init(uint32_t b, uint32_t c) { asm volatile("mbarrier.init.shared::cta.b64 [%0], %1;" ::"r"(b), "r"(c) : "memory"); }
__device__ __forceinline__ void mbar_expect(uint32_t b, uint32_t bytes) { asm volatile("mbarrier.arrive.expect_tx.shared::cta.b64 _, [%0], %1;" ::"r"(b), "r"(bytes) : "memory"); }
__device__ __forceinline__ void mbar_arrive(uint32_t b) { asm volatile("mbarrier.arrive.shared::cta.b64 _, [%0];" ::"r"(b) : "memory"); }
__device__ __forceinline__ void mbar_arrive_cta(uint32_t b, uint32_t cta) {
  asm volatile("{\n.reg .b32 r;\nmapa.shared::cluster.u32 r, %0, %1;\nmbarrier.arrive.shared::cluster.b64 _, [r];\n}" ::"r"(b), "r"(cta) : "memory");
}
__device__ __forceinline__ bool mbar_test(uint32_t b, uint32_t ph) {
  uint32_t ok;
  asm volatile("{\n.reg .pred p;\nmbarrier.test_wait.parity.shared::cta.b64 p, [%1], %2;\nselp.u32 %0, 1, 0, p;\n}" : "=r"(ok) : "r"(b), "r"(ph) : "memory");
  return ok;
}
__device__ __forceinline__ void mbar_wait(uint32_t b, uint32_t ph) {
  asm volatile(
      "{\n.reg .pred p;\n.reg .u32 n;\nmov.u32 n, 0;\n"
      "LW:\nmbarrier.try_wait.parity.shared::cta.b64 p, [%0], %1, 20000;\n@p bra LD;\n"
      "add.u32 n, n, 1;\nsetp.lt.u32 p, n, 0x40000;\n@p bra LW;\ntrap;\nLD:\n}" ::"r"(b), "r"(ph) : "memory");
}
__device__ __forceinline__ void mbar_wait_c(uint32_t b, uint32_t ph) {
  asm volatile(
      "{\n.reg .pred p;\n.reg .u32 n;\nmov.u32 n, 0;\n"
      "LW:\nmbarrier.try_wait.parity.shared::cta.b64 p, [%0], %1;\n@p bra LD;\n"
      "add.u32 n, n, 1;\nsetp.lt.u32 p, n, 0x100000;\n@p bra LW;\ntrap;\nLD:\n}" ::"r"(b), "r"(ph) : "memory");
}
__device__ __forceinline__ bool mbar_try(uint32_t b, uint32_t ph) {
  uint32_t ok;
  asm volatile("{\n.reg .pred p;\nmbarrier.try_wait.parity.shared::cta.b64 p, [%1], %2;\nselp.u32 %0, 1, 0, p;\n}" : "=r"(ok) : "r"(b), "r"(ph) : "memory");
  return ok;
}
#define UNLIKELY(c) __builtin_expect(!!(c), 0)
__device__ __forceinline__ void mbar_wait_f(uint32_t b, uint32_t ph) { if (UNLIKELY(!mbar_try(b, ph))) mbar_wait_c(b, ph); }
__device__ __forceinline__ uint32_t pinned(uint32_t v) { uint32_t r; asm volatile("mov.b32 %0, %1;" : "=r"(r) : "r"(v)); return r; }
template <bool SLEEP = false>
__device__ __forceinline__ void spin_until_ge(const unsigned* p, unsigned target) {
  asm volatile(
      "{\n.reg .pred p, q;\n.reg .u32 n, v;\nmov.u32 n, 0;\nsetp.ne.u32 q, %2, 0;\n"
      "LW:\nld.acquire.gpu.global.u32 v, [%0];\nsetp.ge.u32 p, v, %1;\n@p bra LD;\n@q nanosleep.u32 200;\n"
      "add.u32 n, n, 1;\nsetp.lt.u32 p, n, 0x400000;\n@p bra LW;\ntrap;\nLD:\n}" ::"l"(p), "r"(target), "n"((int)SLEEP) : "memory");
}
__device__ __forceinline__ uint4 poll_chunk(const uint4* p) {
  uint4 v;
  asm volatile(
      "{\n.reg .pred p;\n.reg .u32 n, m;\nmov.u32 n, 0;\n"
      "LW:\nld.relaxed.gpu.global.v4.u32 {%0,%1,%2,%3}, [%4];\nmax.u32 m, %0, %1;\nmax.u32 m, m, %2;\nmax.u32 m, m, %3;\n"
      "setp.ne.u32 p, m, 0xFFFFFFFF;\n@p bra LD;\n"
      "add.u32 n, n, 1;\nsetp.lt.u32 p, n, 0x400000;\n@p bra LW;\ntrap;\nLD:\n}"
      : "=r"(v.x), "=r"(v.y), "=r"(v.z), "=r"(v.w) : "l"(p) : "memory");
  return v;
}
template <int N>
__device__ __forceinline__ void poll_chunks(uint4 (&v)[N], const uint4* p, int stride) {
#pragma unroll 1
  for (int n = 0; n < 0x400000; n++) {
    uint32_t m = 0;
#pragma unroll
    for (int i = 0; i < N; i++) {
      asm volatile("ld.relaxed.gpu.global.v4.u32 {%0,%1,%2,%3}, [%4];" : "=r"(v[i].x), "=r"(v[i].y), "=r"(v[i].z), "=r"(v[i].w) : "l"(p + i * stride) : "memory");
    }
#pragma unroll
    for (int i = 0; i < N; i++) m = max(max(m, max(v[i].x, v[i].y)), max(v[i].z, v[i].w));
    if (m != 0xFFFFFFFFu) break;
  }
}
__device__ __forceinline__ void fence_async_all() { asm volatile("fence.proxy.async;" ::: "memory"); }
__device__ __forceinline__ void bar_sync(int id, int n) { asm volatile("bar.sync %0, %1;" ::"r"(id), "r"(n) : "memory"); }
__device__ __forceinline__ void bar_arrive(int id, int n) { asm volatile("bar.arrive %0, %1;" ::"r"(id), "r"(n) : "memory"); }
__device__ __forceinline__ void cluster_arrive() { asm volatile("barrier.cluster.arrive.relaxed.aligned;" ::: "memory"); }
__device__ __forceinline__ void cluster_wait() { asm volatile("barrier.cluster.wait.acquire.aligned;" ::: "memory"); }
__device__ __forceinline__ void fence_gpu() { asm volatile("fence.acq_rel.gpu;" ::: "memory"); }
__device__ __forceinline__ void red_add(unsigned* p, unsigned v) { asm volatile("red.relaxed.gpu.global.add.u32 [%0], %1;" ::"l"(p), "r"(v) : "memory"); }
__device__ __forceinline__ void prefetch_tm(const CUtensorMap* m) { asm volatile("prefetch.tensormap [%0];" ::"l"(m) : "memory"); }

__device__ __forceinline__ void tma_ld2(uint32_t dst, const CUtensorMap* m, uint32_t bar, int c0, int c1) {
  asm volatile("cp.async.bulk.tensor.2d.shared::cta.global.mbarrier::complete_tx::bytes [%0], [%1, {%3,%4}], [%2];" ::"r"(dst), "l"(m), "r"(bar), "r"(c0), "r"(c1) : "memory");
}
__device__ __forceinline__ void tma_ld3(uint32_t dst, const CUtensorMap* m, uint32_t bar, int c0, int c1, int c2) {
  asm volatile("cp.async.bulk.tensor.3d.shared::cta.global.mbarrier::complete_tx::bytes [%0], [%1, {%3,%4,%5}], [%2];" ::"r"(dst), "l"(m), "r"(bar), "r"(c0), "r"(c1), "r"(c2) : "memory");
}
__device__ __forceinline__ void tma_ld3_mc(uint32_t dst, const CUtensorMap* m, uint32_t bar, int c0, int c1, int c2, uint16_t mask) {
  asm volatile("cp.async.bulk.tensor.3d.shared::cluster.global.mbarrier::complete_tx::bytes.multicast::cluster [%0], [%1, {%3,%4,%5}], [%2], %6;" ::"r"(dst), "l"(m), "r"(bar), "r"(c0), "r"(c1), "r"(c2), "h"(mask) : "memory");
}
__device__ __forceinline__ void l2_prefetch(const void* p, uint32_t bytes) { asm volatile("cp.async.bulk.prefetch.L2.global [%0], %1;" ::"l"(p), "r"(bytes) : "memory"); }

__device__ __forceinline__ void wg_fence() { asm volatile("wgmma.fence.sync.aligned;" ::: "memory"); }
__device__ __forceinline__ void wg_commit() { asm volatile("wgmma.commit_group.sync.aligned;" ::: "memory"); }
template <int N> __device__ __forceinline__ void wg_wait() { asm volatile("wgmma.wait_group.sync.aligned %0;" ::"n"(N) : "memory"); }
template <int N> __device__ __forceinline__ void reg_alloc() { asm volatile("setmaxnreg.inc.sync.aligned.u32 %0;" ::"n"(N)); }
template <int N> __device__ __forceinline__ void reg_dealloc() { asm volatile("setmaxnreg.dec.sync.aligned.u32 %0;" ::"n"(N)); }
template <int N> __device__ __forceinline__ void fence_regs(float* d) {
#pragma unroll
  for (int i = 0; i < N; i++) asm volatile("" : "+f"(d[i])::"memory");
}
template <int N> __device__ __forceinline__ void fence_regs(uint32_t* d) {
#pragma unroll
  for (int i = 0; i < N; i++) asm volatile("" : "+r"(d[i])::"memory");
}

__device__ __forceinline__ uint64_t mk_desc(uint32_t addr, uint32_t lbo, uint32_t sbo, uint32_t swz) {
  uint32_t lo = ((addr & 0x3FFFF) >> 4) | ((lbo >> 4) << 16);
  uint32_t hi = (sbo >> 4) | (swz << 30);
  return ((uint64_t)hi << 32) | lo;
}
__device__ __forceinline__ uint64_t desc_add(uint64_t d, uint32_t bytes) {
  uint32_t lo = (uint32_t)d + (bytes >> 4);
  return (d & 0xFFFFFFFF00000000ull) | lo;
}

#define R8(b) "+f"(d[b + 0]), "+f"(d[b + 1]), "+f"(d[b + 2]), "+f"(d[b + 3]), "+f"(d[b + 4]), "+f"(d[b + 5]), "+f"(d[b + 6]), "+f"(d[b + 7])
#define REGS32 "%0,%1,%2,%3,%4,%5,%6,%7,%8,%9,%10,%11,%12,%13,%14,%15,%16,%17,%18,%19,%20,%21,%22,%23,%24,%25,%26,%27,%28,%29,%30,%31"
#define REGS64 REGS32 ",%32,%33,%34,%35,%36,%37,%38,%39,%40,%41,%42,%43,%44,%45,%46,%47,%48,%49,%50,%51,%52,%53,%54,%55,%56,%57,%58,%59,%60,%61,%62,%63"
#define REGS128 REGS64 ",%64,%65,%66,%67,%68,%69,%70,%71,%72,%73,%74,%75,%76,%77,%78,%79,%80,%81,%82,%83,%84,%85,%86,%87,%88,%89,%90,%91,%92,%93,%94,%95," \
               "%96,%97,%98,%99,%100,%101,%102,%103,%104,%105,%106,%107,%108,%109,%110,%111,%112,%113,%114,%115,%116,%117,%118,%119,%120,%121,%122,%123,%124,%125,%126,%127"

template <int TB>
__device__ __forceinline__ void mma_n256_ss(float (&d)[128], uint64_t a, uint64_t b, int acc) {
  asm volatile("{\n.reg .pred p;\nsetp.ne.b32 p, %130, 0;\n"
               "wgmma.mma_async.sync.aligned.m64n256k16.f32.bf16.bf16 {" REGS128 "}, %128, %129, p, 1, 1, 0, %131;\n}\n"
               : R8(0), R8(8), R8(16), R8(24), R8(32), R8(40), R8(48), R8(56), R8(64), R8(72), R8(80), R8(88), R8(96), R8(104), R8(112), R8(120)
               : "l"(a), "l"(b), "r"(acc), "n"(TB));
}
template <int TB>
__device__ __forceinline__ void mma_n128_ss(float* d, uint64_t a, uint64_t b, int acc) {
  asm volatile("{\n.reg .pred p;\nsetp.ne.b32 p, %66, 0;\n"
               "wgmma.mma_async.sync.aligned.m64n128k16.f32.bf16.bf16 {" REGS64 "}, %64, %65, p, 1, 1, 0, %67;\n}\n"
               : R8(0), R8(8), R8(16), R8(24), R8(32), R8(40), R8(48), R8(56)
               : "l"(a), "l"(b), "r"(acc), "n"(TB));
}
template <int TB>
__device__ __forceinline__ void mma_n128_rs(float* d, const uint32_t* a, uint64_t b, int acc) {
  asm volatile("{\n.reg .pred p;\nsetp.ne.b32 p, %69, 0;\n"
               "wgmma.mma_async.sync.aligned.m64n128k16.f32.bf16.bf16 {" REGS64 "}, {%64,%65,%66,%67}, %68, p, 1, 1, %70;\n}\n"
               : R8(0), R8(8), R8(16), R8(24), R8(32), R8(40), R8(48), R8(56)
               : "r"(a[0]), "r"(a[1]), "r"(a[2]), "r"(a[3]), "l"(b), "r"(acc), "n"(TB));
}
__device__ __forceinline__ void mma_n64_rs(float* d, const uint32_t* a, uint64_t b, int acc) {
  asm volatile("{\n.reg .pred p;\nsetp.ne.b32 p, %37, 0;\n"
               "wgmma.mma_async.sync.aligned.m64n64k16.f32.bf16.bf16 {" REGS32 "}, {%32,%33,%34,%35}, %36, p, 1, 1, 0;\n}\n"
               : R8(0), R8(8), R8(16), R8(24)
               : "r"(a[0]), "r"(a[1]), "r"(a[2]), "r"(a[3]), "l"(b), "r"(acc));
}
#define W8(b) "=f"(d[b + 0]), "=f"(d[b + 1]), "=f"(d[b + 2]), "=f"(d[b + 3]), "=f"(d[b + 4]), "=f"(d[b + 5]), "=f"(d[b + 6]), "=f"(d[b + 7])
__device__ __forceinline__ void mma_n128_rs0(float* d, const uint32_t* a, uint64_t b) {
  asm volatile("wgmma.mma_async.sync.aligned.m64n128k16.f32.bf16.bf16 {" REGS64 "}, {%64,%65,%66,%67}, %68, 0, 1, 1, 0;\n"
               : W8(0), W8(8), W8(16), W8(24), W8(32), W8(40), W8(48), W8(56)
               : "r"(a[0]), "r"(a[1]), "r"(a[2]), "r"(a[3]), "l"(b));
}
__device__ __forceinline__ void mma_n64_rs0(float* d, const uint32_t* a, uint64_t b) {
  asm volatile("wgmma.mma_async.sync.aligned.m64n64k16.f32.bf16.bf16 {" REGS32 "}, {%32,%33,%34,%35}, %36, 0, 1, 1, 0;\n"
               : W8(0), W8(8), W8(16), W8(24)
               : "r"(a[0]), "r"(a[1]), "r"(a[2]), "r"(a[3]), "l"(b));
}
__device__ __forceinline__ uint32_t pack_bf16(float lo, float hi) {
  uint32_t r;
  asm("cvt.rn.bf16x2.f32 %0, %1, %2;" : "=r"(r) : "f"(hi), "f"(lo));
  return r;
}
__device__ __forceinline__ float bf_lo(uint32_t v) { return __uint_as_float(v << 16); }
__device__ __forceinline__ float bf_hi(uint32_t v) { return __uint_as_float(v & 0xFFFF0000u); }
__device__ __forceinline__ float bf_round(float v) { return bf_lo(pack_bf16(v, v)); }
__device__ __forceinline__ void stsm4(uint32_t addr, uint32_t r0, uint32_t r1, uint32_t r2, uint32_t r3) {
  asm volatile("stmatrix.sync.aligned.m8n8.x4.shared.b16 [%0], {%1,%2,%3,%4};" ::"r"(addr), "r"(r0), "r"(r1), "r"(r2), "r"(r3) : "memory");
}
__device__ __forceinline__ uint4 lds128(uint32_t addr) {
  uint4 v;
  asm volatile("ld.shared.v4.u32 {%0,%1,%2,%3}, [%4];" : "=r"(v.x), "=r"(v.y), "=r"(v.z), "=r"(v.w) : "r"(addr));
  return v;
}
__device__ __forceinline__ float ex2(float x) {
  float y;
  asm("ex2.approx.ftz.f32 %0, %1;" : "=f"(y) : "f"(x));
  return y;
}
__device__ __forceinline__ void pin_order(float v, uint32_t dummy) {
  asm volatile("{\n.reg .pred p;\nsetp.eq.b32 p, %0, 0xFFFFFFFF;\n@p st.shared.b32 [%1], %0;\n}" ::"r"(__float_as_uint(v)), "r"(dummy) : "memory");
}
__device__ __forceinline__ void sched_fence(uint32_t dummy) {
  asm volatile("{\n.reg .pred p;\n.reg .u32 c;\nsetp.eq.b32 p, %0, 0xFFFFFFFF;\nmov.u32 c, %%clock;\n@p st.shared.b32 [%0], c;\n}" ::"r"(dummy) : "memory");
}
__device__ __forceinline__ void stage_store_128(uint32_t base, int lane, const uint32_t* pk) {
  const int row = (lane & 7) + ((lane >> 3) & 1) * 8;
  const uint32_t rb = base + row * 128;
  const int hi = lane >> 4;
#pragma unroll
  for (int j = 0; j < 8; j++) {
    const int chunk = 2 * j + hi;
    const uint32_t a = rb + (j >> 2) * 8192 + (((chunk & 7) ^ (lane & 7)) << 4);
    stsm4(a, pk[4 * j + 0], pk[4 * j + 1], pk[4 * j + 2], pk[4 * j + 3]);
  }
}
__device__ __forceinline__ void ln_round(float mean, float var, float& m_bf, float& inv_s) {
  const uint32_t mv = pack_bf16(mean, var);
  m_bf = bf_lo(mv);
  float sq, rc;
  asm("sqrt.approx.f32 %0, %1;" : "=f"(sq) : "f"(bf_round(bf_hi(mv) + 1e-5f)));
  asm("rcp.approx.ftz.f32 %0, %1;" : "=f"(rc) : "f"(bf_round(sq)));
  inv_s = rc;
}
__device__ __forceinline__ uint32_t hadd2_bf(uint32_t a, uint32_t b) {
  uint32_t r;
  asm("add.rn.bf16x2 %0, %1, %2;" : "=r"(r) : "r"(a), "r"(b));
  return r;
}
__device__ __forceinline__ uint32_t ln_apply(uint32_t h, uint32_t nm2, float inv_s) {
  const uint32_t d = hadd2_bf(h, nm2);
  return pack_bf16(bf_lo(d) * inv_s, bf_hi(d) * inv_s);
}
__device__ __forceinline__ void ldsm4(uint32_t* r, uint32_t addr) {
  asm volatile("ldmatrix.sync.aligned.m8n8.x4.shared.b16 {%0,%1,%2,%3}, [%4];" : "=r"(r[0]), "=r"(r[1]), "=r"(r[2]), "=r"(r[3]) : "r"(addr) : "memory");
}
__device__ __forceinline__ void mma16816(float* d, uint32_t a0, uint32_t a1, uint32_t a2, uint32_t a3, uint32_t b0, uint32_t b1) {
  asm volatile("mma.sync.aligned.m16n8k16.row.col.f32.bf16.bf16.f32 {%0,%1,%2,%3}, {%4,%5,%6,%7}, {%8,%9}, {%0,%1,%2,%3};"
               : "+f"(d[0]), "+f"(d[1]), "+f"(d[2]), "+f"(d[3]) : "r"(a0), "r"(a1), "r"(a2), "r"(a3), "r"(b0), "r"(b1));
}

template <class F>
__device__ __forceinline__ void unroll8(F f) {
  f(std::integral_constant<int, 0>{}); f(std::integral_constant<int, 1>{}); f(std::integral_constant<int, 2>{}); f(std::integral_constant<int, 3>{});
  f(std::integral_constant<int, 4>{}); f(std::integral_constant<int, 5>{}); f(std::integral_constant<int, 6>{}); f(std::integral_constant<int, 7>{});
}

constexpr float AT_C = 0.08838834764831845f * 1.4426950408889634f;
#define AT_LO 0x1p-40f
#define AT_HI 0x1p40f
#define SH_K 4
#define AT_R1 48
#define AT_R2 48
template <int I0, int I1>
__device__ __forceinline__ void at_exp(float* S) {
#pragma unroll
  for (int i = I0; i < I1; i++) asm volatile("ex2.approx.ftz.f32 %0, %0;" : "+f"(S[i]));
}
#define HSUM 1
template <int I0, int I1>
__device__ __forceinline__ void at_fin(const float* S, uint32_t* P, float& l0, float& l1) {
#pragma unroll
  for (int i = I0; i < I1; i += 4) {
    if (!HSUM) { l0 += S[i] + S[i + 1]; l1 += S[i + 2] + S[i + 3]; }
    P[i / 2] = pack_bf16(S[i], S[i + 1]); P[i / 2 + 1] = pack_bf16(S[i + 2], S[i + 3]);
  }
}
__device__ __forceinline__ void at_sum(const uint32_t* P, bool half, float& l0, float& l1) {
  uint32_t u[4];
#pragma unroll
  for (int r = 0; r < 4; r++) {
    const uint32_t* q = P + (r >> 1) * 16 + (r & 1);
    u[r] = hadd2_bf(hadd2_bf(hadd2_bf(q[0], q[2]), hadd2_bf(q[4], q[6])), hadd2_bf(hadd2_bf(q[8], q[10]), hadd2_bf(q[12], q[14])));
  }
  u[0] = hadd2_bf(u[0], half ? 0u : u[2]);
  u[1] = hadd2_bf(u[1], half ? 0u : u[3]);
  l0 += bf_lo(u[0]) + bf_hi(u[0]);
  l1 += bf_lo(u[1]) + bf_hi(u[1]);
}
__device__ __forceinline__ void at_mask(float* S, int r, int lane) {
  const int d = r + (lane >> 2) - (lane & 3) * 2;
#pragma unroll
  for (int j = 0; j < 8; j++) {
    float dummy0 = 0.f, dummy1 = 0.f;
    float& lo0 = j < 7 ? S[4 * (j < 7 ? j + 1 : j) + 2] : dummy0;
    float& lo1 = j < 7 ? S[4 * (j < 7 ? j + 1 : j) + 3] : dummy1;
    asm("{\n.reg .pred p, q;\nsetp.lt.s32 p, %4, %5;\nsetp.le.s32 q, %4, %5;\n"
        "@p add.f32 %0, %0, 0fFF800000;\n@q add.f32 %1, %1, 0fFF800000;\n@p add.f32 %2, %2, 0fFF800000;\n@q add.f32 %3, %3, 0fFF800000;\n}"
        : "+f"(S[4 * j]), "+f"(S[4 * j + 1]), "+f"(lo0), "+f"(lo1) : "r"(d), "r"(8 * j));
  }
}
__device__ __forceinline__ uint32_t ldg32(const __nv_bfloat16* p) { return __ldcg(reinterpret_cast<const uint32_t*>(p)); }
__device__ __forceinline__ uint32_t ldg16x2(const __nv_bfloat16* p, int stride) {
  return (uint32_t)__ldcg(reinterpret_cast<const unsigned short*>(p)) | ((uint32_t)__ldcg(reinterpret_cast<const unsigned short*>(p + stride)) << 16);
}
__device__ __forceinline__ void slow_tile(float* O, uint32_t* Q, float& l0, float& l1, const __nv_bfloat16* wq, int row0, int head, int lane) {
  const int r = lane >> 2, q = lane & 3;
#pragma unroll
  for (int i = 0; i < 64; i++) O[i] = 0.f;
  {
    const __nv_bfloat16* xa = g_xn + (size_t)(row0 + r) * DM + 2 * q;
    const __nv_bfloat16* wb = wq + (size_t)(2 * q) * NQ + head * HD + (r >> 1) * 8 + (r & 1);
#pragma unroll 1
    for (int k = 0; k < DM; k += 16) {
      const uint32_t a0 = ldg32(xa + k), a1 = ldg32(xa + k + 8 * DM), a2 = ldg32(xa + k + 8), a3 = ldg32(xa + k + 8 * DM + 8);
#pragma unroll
      for (int j = 0; j < 16; j++) {
        const __nv_bfloat16* wp = wb + (size_t)k * NQ + (j >> 2) * 32 + (j & 3) * 2;
        mma16816(O + 4 * j, a0, a1, a2, a3, ldg16x2(wp, NQ), ldg16x2(wp + 8 * NQ, NQ));
      }
    }
  }
#pragma unroll
  for (int i = 0; i < 32; i++) Q[i] = pack_bf16(O[2 * i], O[2 * i + 1]);
#pragma unroll
  for (int i = 0; i < 64; i++) O[i] = 0.f;
  float m0 = -INFINITY, m1 = -INFINITY;
  l0 = l1 = 0.f;
#pragma unroll 1
  for (int kv = 0; kv <= row0; kv += 16) {
    float s[8] = {0.f, 0.f, 0.f, 0.f, 0.f, 0.f, 0.f, 0.f};
    const __nv_bfloat16* kp = g_qkv + (size_t)(SEQ + kv + r) * NQ + head * HD + 2 * q;
#pragma unroll
    for (int k = 0; k < 8; k++) {
      mma16816(s, Q[4 * k], Q[4 * k + 1], Q[4 * k + 2], Q[4 * k + 3], ldg32(kp + 16 * k), ldg32(kp + 16 * k + 8));
      mma16816(s + 4, Q[4 * k], Q[4 * k + 1], Q[4 * k + 2], Q[4 * k + 3], ldg32(kp + 8 * NQ + 16 * k), ldg32(kp + 8 * NQ + 16 * k + 8));
    }
#pragma unroll
    for (int i = 0; i < 8; i++)
      if (kv + (i >> 2) * 8 + 2 * q + (i & 1) > row0 + r + (i & 2) * 4) s[i] = -INFINITY;
    float a = fmaxf(fmaxf(fmaxf(s[0], s[1]), fmaxf(s[4], s[5])), m0), b = fmaxf(fmaxf(fmaxf(s[2], s[3]), fmaxf(s[6], s[7])), m1);
    a = fmaxf(a, __shfl_xor_sync(~0u, a, 1)); b = fmaxf(b, __shfl_xor_sync(~0u, b, 1));
    a = fmaxf(a, __shfl_xor_sync(~0u, a, 2)); b = fmaxf(b, __shfl_xor_sync(~0u, b, 2));
    const float c0 = ex2(m0 - a), c1 = ex2(m1 - b);
    m0 = a; m1 = b;
#pragma unroll
    for (int i = 0; i < 8; i++) s[i] = ex2(s[i] - ((i & 2) ? b : a));
    l0 = l0 * c0 + (s[0] + s[1]) + (s[4] + s[5]);
    l1 = l1 * c1 + (s[2] + s[3]) + (s[6] + s[7]);
    const uint32_t p0 = pack_bf16(s[0], s[1]), p1 = pack_bf16(s[2], s[3]), p2 = pack_bf16(s[4], s[5]), p3 = pack_bf16(s[6], s[7]);
    const __nv_bfloat16* vp = g_qkv + (size_t)(2 * SEQ + kv + 2 * q) * NQ + head * HD + r;
#pragma unroll
    for (int j = 0; j < 16; j++) {
      O[4 * j] *= c0; O[4 * j + 1] *= c0; O[4 * j + 2] *= c1; O[4 * j + 3] *= c1;
      mma16816(O + 4 * j, p0, p1, p2, p3, ldg16x2(vp + 8 * j, NQ), ldg16x2(vp + 8 * NQ + 8 * j, NQ));
    }
  }
}

constexpr int P1_STAGE = 49152;
constexpr int SLOT = 32768;
constexpr int OFF_LN = 6 * SLOT, OFF_STG = 6 * SLOT, OFF_R3 = 0;
constexpr int OFF_BAR = 229376;
constexpr int OFF_MISC = OFF_BAR + 8 * 56;
constexpr int SMEM_BYTES = OFF_MISC + 2080;
constexpr int OFF_RSTAT = OFF_MISC + 1056;
enum : int {
  B_FULL1 = 0, B_KF = 4, B_VF = 6, B_FULL3 = 8, B_XF = 14, B_LN = 15, B_DEP = 16, B_OUT2 = 22, B_PF = 23, B_SET = 24, B_SET2 = 25, B_QP = 26,
  B_WR = 29, B_WF = 30, B_LND = 31,
  B_XE = 32, B_PUB = 33, B_OUT = 39,
  B_EMPTY1 = 40, B_KE = 44, B_VE = 46, B_EMPTY3 = 48, B_WE = 54, B_NUM = 56
};
constexpr int PRE = 3;
#define LN_PF 4
#define LN_LD 9
constexpr int LN_PFN = 2;
constexpr int SL_SCR = 67 % 6;
constexpr int PF_KB = 52, PF_CLK = 500;
constexpr int SET_KB = 46;
#define ST_G 1
#define ST_NS 0
#define WMODE 2
#define W_G0 22
#define W_PF 2
#define KVPF 1
#define XPF_KB 50
struct Params {
  CUtensorMap xn, ckv, wq, wk, wv, kv, ctx_ld, ctx_st, wo, x, wd, wg, wu, out;
};

__global__ void __cluster_dims__(2, 1, 1) __launch_bounds__(384, 1)
fused_kernel(const __grid_constant__ Params p, const __nv_bfloat16* __restrict__ x, const __nv_bfloat16* __restrict__ wq,
             const __nv_bfloat16* __restrict__ w_r, const __nv_bfloat16* __restrict__ wgate, const __nv_bfloat16* __restrict__ wup,
             __nv_bfloat16* __restrict__ out) {
  extern __shared__ __align__(1024) uint8_t sp[];
  const uint32_t sb = s2u(sp);
  const uint32_t bar = sb + OFF_BAR;
  auto B = [&](int i) { return bar + 8 * i; };
  const int tid = threadIdx.x, warp = __shfl_sync(~0u, tid >> 5, 0), wg = warp >> 2, lane = tid & 31;
  const int cta = blockIdx.x, rank = cta & 1, cl = cta >> 1;
  const int mp = cl < 4 ? 1 : (cl < 36 ? (cl & 7) : (0x3207654 >> (4 * ((cl - 36) % 7))) & 7);
  const int gq = cl < 4 ? 4 + cl : (cl < 36 ? (cl - 4) >> 3 : 4 + (cl - 36) / 7);
  const int mt = 2 * mp + rank;
  const int ti = (gq & 3) * 2 + rank, hh = mp * 2 + (gq >> 2);
  const int rid = mt * 8 + gq;
  const int fid = mt * 7 + gq;
  const bool ffn = gq < 7;
  uint4* const xr = g_xr + rid * XR_SIZE;
  TL(0, 0, tid == 128);
  if (tid == 32) TS(0);
  if (tid == 0) {
#pragma unroll 1
    for (int kb = 0; kb < PRE; kb++) {
      mbar_init(B(B_FULL1 + kb), 1);
      asm volatile("fence.mbarrier_init.release.cluster;" ::: "memory");
      mbar_expect(B(B_FULL1 + kb), P1_STAGE);
      tma_ld2(sb + kb * P1_STAGE, &p.ckv, B(B_FULL1 + kb), kb * 64, mt * 128);
      tma_ld3(sb + kb * P1_STAGE + 16384 + rank * 16384, &p.wk, B(B_FULL1 + kb), 0, kb * 64, gq * 4 + rank * 2);
      tma_ld3(sb + kb * P1_STAGE + 32768 - rank * 16384, &p.wk, B(B_FULL1 + kb), 0, kb * 64, gq * 4 + 2 - rank * 2);
    }
  }
  if (lane == 0) {
#pragma unroll 1
    for (int i = warp < PRE ? warp + 12 : warp; i < B_NUM; i += 12) {
      mbar_init(B(i), i >= B_EMPTY1 ? 16 : (i >= B_XE ? 8 : (i > B_WR ? 3 : (i == B_WR ? 2 : 1))));
    }
    asm volatile("fence.mbarrier_init.release.cluster;" ::: "memory");
  }
  __syncwarp();
  cluster_arrive();
  if (tid == 32) {
    if (mt >= 2 * PRE) asm volatile("cp.async.bulk.prefetch.tensor.3d.L2.global [%0, {%1,%2,%3}];" ::"l"(&p.wk), "r"(0), "r"((mt >> 1) * 64), "r"(gq * 4 + (mt & 1) * 2) : "memory");
    if (gq >= PRE) asm volatile("cp.async.bulk.prefetch.tensor.2d.L2.global [%0, {%1,%2}];" ::"l"(&p.ckv), "r"(gq * 64), "r"(mt * 128) : "memory");
  } else if (tid == 64) {
    prefetch_tm(&p.wv); prefetch_tm(&p.wq); prefetch_tm(&p.xn);
  }
  __syncwarp();
  cluster_wait();
  if (wg == 0) {
    reg_dealloc<40>();
    if (warp == 0) {
      if (lane == 0) {
        int st = 0; uint32_t ph = 1;
#pragma unroll 1
        for (int t = 0; t < 6; t++) {
          const CUtensorMap* ma = t >= 4 ? &p.xn : &p.ckv;
          const CUtensorMap* mb = t >= 4 ? &p.wq : ((t & 1) ? &p.wv : &p.wk);
          const int nk = t >= 4 ? 16 : 8;
          const int row = (t < 4 ? mt : (t == 4 ? 15 - ti : ti)) * 128;
          const int col = t < 4 ? (gq + (t >> 1) * 8) * 4 + rank * 2 : (hh + rank * 16) * 2;
          if (t >= 4) mbar_wait(B(B_DEP + t - 4), 0);
#pragma unroll 1
          for (int kb = 0; kb < nk; kb++) {
            const uint32_t d = sb + st * P1_STAGE, fb = B(B_FULL1 + st);
            if (t > 0 || kb >= PRE) {
              mbar_wait(B(B_EMPTY1 + st), ph);
              mbar_expect(fb, P1_STAGE);
              tma_ld2(d, ma, fb, kb * 64, row);
              tma_ld3_mc(d + 16384 + rank * 16384, mb, fb, 0, kb * 64, col, 3);
            }
            if (t < 3 && t * 8 + kb >= LN_PF && t * 8 + kb < LN_PF + LN_PFN) l2_prefetch(x + (size_t)cta * 16 * DM + (t * 8 + kb - LN_PF) * (16 * DM / LN_PFN), 32768 / LN_PFN);
            if (t < 3 && t * 8 + kb == LN_LD) {
              mbar_expect(B(B_LN), 32768);
              asm volatile("cp.async.bulk.shared::cluster.global.mbarrier::complete_tx::bytes [%0], [%1], %2, [%3];" ::"r"(sb + OFF_LN),
                           "l"(x + (size_t)cta * 16 * DM), "r"(32768), "r"(B(B_LN)) : "memory");
            }
            if (t < 3 ? kb == 0 : (t == 3 && !(kb & 1)))
              asm volatile("cp.async.bulk.prefetch.tensor.3d.L2.global [%0, {%1,%2,%3}];" ::"l"(t == 3 ? &p.wq : ((t & 1) ? &p.wk : &p.wv)), "r"(0),
                           "r"((t == 3 ? kb * 2 + (gq & 3) : mp) * 64), "r"(t == 3 ? (hh + rank * 16) * 2 : (gq + ((t + 1) >> 1) * 8) * 4 + rank * 2) : "memory");
            if (++st == 4) { st = 0; ph ^= 1; }
          }
        }
        prefetch_tm(&p.kv); prefetch_tm(&p.ctx_ld); prefetch_tm(&p.wo); prefetch_tm(&p.wg); prefetch_tm(&p.wu);
        auto load_kv = [&](int g, int isv) {
          const int h2 = g >= 17, sx = g - 17 * h2, n1 = h2 ? ti + 1 : 16 - ti;
          const int row = (1 + isv) * SEQ + (sx < n1 ? sx : 16 - sx) * 128, col = (hh + 16 * h2) * 2;
          const uint32_t d = sb + (isv ? 2 + 2 * (g & 1) : (g & 1)) * SLOT, fb = B(B_KF + 2 * isv + (g & 1));
          if (g < 2) mbar_wait(B(B_EMPTY1 + (isv ? 1 + 2 * g : g)), 1);
          else mbar_wait(B(B_KE + 2 * isv + (g & 1)), ((g >> 1) & 1) ^ 1);
          mbar_expect(fb, SLOT);
          if (sx != (h2 ? (ti & 6) + 1 : 15 - (ti & 6))) {
            tma_ld3_mc(d + rank * 16384, &p.kv, fb, 0, row, col + rank, 3);
          } else {
            tma_ld3(d, &p.kv, fb, 0, row, col);
            tma_ld3(d + 16384, &p.kv, fb, 0, row, col + 1);
          }
          if (g + KVPF < 34) {
            const int g2 = g + KVPF, h3 = g2 >= 17, s3 = g2 - 17 * h3, n3 = h3 ? ti + 1 : 16 - ti;
            const int row3 = (1 + isv) * SEQ + (s3 < n3 ? s3 : 16 - s3) * 128, col3 = (hh + 16 * h3) * 2;
            asm volatile("cp.async.bulk.prefetch.tensor.3d.L2.global [%0, {%1,%2,%3}];" ::"l"(&p.kv), "r"(0), "r"(row3), "r"(col3 + rank) : "memory");
            if (s3 == (h3 ? (ti & 6) + 1 : 15 - (ti & 6)))
              asm volatile("cp.async.bulk.prefetch.tensor.3d.L2.global [%0, {%1,%2,%3}];" ::"l"(&p.kv), "r"(0), "r"(row3), "r"(col3 + 1 - rank) : "memory");
          }
        };
        int nw = ffn && WMODE ? 0 : 12;
        auto load_w = [&]() {
          const int c = nw < 8 ? (nw >> 2) + (nw & 2) : nw >> 1;
          if (!(nw & 3)) mbar_expect(B(B_WF), 32768);
          tma_ld2(sb + (c < 4 ? 3 + (c & 2) : 6) * SLOT + (c & 1) * 16384 + (nw & 1) * 8192, (nw & 1) ? &p.wg : &p.wu, B(B_WF), fid * 32, c * 128);
          nw++;
        };
#pragma unroll 1
        for (int g = 0; g < 34; g++) {
          if (g == 0 || g == 17 - KVPF) mbar_wait(B(B_DEP + 2 + (g > 0)), 0);
          load_kv(g, 0);
          if (WMODE == 3 && g >= W_G0 - W_PF && g < W_G0 - W_PF + 12) {
            const int n = g - W_G0 + W_PF, c = n < 8 ? (n >> 2) + (n & 2) : n >> 1;
            l2_prefetch(((n & 1) ? wgate : wup) + (size_t)(c * 128 + cta) * FF, FF * 2);
          }
          if (g > 0) load_kv(g - 1, 1);
          if (WMODE == 1) { if (nw < 12 && mbar_test(B(B_QP + (nw >> 2)), 0)) { load_w(); load_w(); } }
          else if (g >= W_G0 && nw < 12 && mbar_test(B(B_QP + (nw >> 2)), 0)) load_w();
        }
        load_kv(33, 1);
#pragma unroll 1
        while (nw < 12) { mbar_wait(B(B_QP + (nw >> 2)), 0); load_w(); }
        prefetch_tm(&p.wd); prefetch_tm(&p.x); prefetch_tm(&p.out);
        st = 0; ph = 1;
#pragma unroll 1
        for (int kb = 0; kb < 64; kb++) {
          if ((kb & 31) == 0) mbar_wait(B(B_DEP + 4 + (kb >> 5)), 0);
          if (kb < 6) mbar_wait(B(B_KE + ((0xB3A210 >> (4 * kb)) & 15)), 0);
          else mbar_wait(B(B_EMPTY3 + st), ph);
          const uint32_t d = sb + OFF_R3 + st * SLOT, fb = B(B_FULL3 + st);
          mbar_expect(fb, SLOT);
          tma_ld2(d, &p.ctx_ld, fb, kb * 64, mt * 128);
          tma_ld3_mc(d + 16384 + rank * 8192, &p.wo, fb, 0, kb * 64, gq * 2 + rank, 3);
          if (++st == 6) { st = 0; ph ^= 1; }
          if (kb == PF_KB) mbar_arrive(B(B_PF));
          if (kb == SET_KB) mbar_arrive(B(B_SET));
          if (kb == 58) l2_prefetch(xr, XR_CAND * 16);
          if ((kb >> 1) == XPF_KB / 2)
            asm volatile("cp.async.bulk.prefetch.tensor.3d.L2.global [%0, {%1,%2,%3}];" ::"l"(&p.x), "r"(0), "r"(mt * 128 + (kb & 1) * 64), "r"(gq * 2) : "memory");
        }
        mbar_wait(B(B_XE), 0);
        mbar_expect(B(B_XF), 32768);
        tma_ld3(sb + OFF_STG, &p.x, B(B_XF), 0, mt * 128, gq * 2);
        tma_ld3(sb + OFF_STG + 16384, &p.x, B(B_XF), 0, mt * 128 + 64, gq * 2);
        if (ffn) {
#pragma unroll 1
          for (int j = 0; j < 3; j++) {
            mbar_wait(B(B_EMPTY3 + st), ph);
            const uint32_t d = sb + OFF_R3 + st * SLOT, fb = B(B_FULL3 + st);
            mbar_expect(fb, SLOT);
            if (j == 0) {
              for (int h = 0; h < 2; h++) {
                tma_ld2(d + h * 16384, &p.wu, fb, fid * 32, (6 + h) * 128);
                tma_ld2(d + h * 16384 + 8192, &p.wg, fb, fid * 32, (6 + h) * 128);
              }
            } else {
              tma_ld3(d, &p.wd, fb, 0, fid * 32, 8 * (j - 1));
            }
            if (++st == 6) { st = 0; ph ^= 1; }
          }
        }
      }
    } else {
      if (warp >= 2) {
#pragma unroll 1
        for (int i = tid - 64; i < XR_CAND; i += 64) xr[i] = make_uint4(~0u, ~0u, ~0u, ~0u);
        if (warp == 2) { __syncwarp(); if (lane == 0) mbar_arrive(B(B_WR)); }
      }
      if (warp == 3) {
        float ws = 0.f;
#pragma unroll
        for (int j = 0; j < 4; j++) {
          const uint4 q = __ldg(reinterpret_cast<const uint4*>(w_r) + j * 32 + lane);
          ws += bf_lo(q.x) + bf_hi(q.x) + bf_lo(q.y) + bf_hi(q.y) + bf_lo(q.z) + bf_hi(q.z) + bf_lo(q.w) + bf_hi(q.w);
        }
#pragma unroll
        for (int o = 16; o; o >>= 1) ws += __shfl_xor_sync(~0u, ws, o);
        uint2* tab = reinterpret_cast<uint2*>(sp + OFF_MISC + 512);
        tab[lane] = make_uint2(0x3F803F80u, 0x3F803F80u);
        tab[32 + lane] = __ldg(reinterpret_cast<const uint2*>(w_r + gq * 128) + lane);
        if (lane == 0) *reinterpret_cast<float*>(sp + OFF_MISC + 1024) = ws;
        __syncwarp();
        if (lane == 0) mbar_arrive(B(B_WR));
      }
      mbar_wait(B(B_LN), 0);
#pragma unroll 1
      for (int r = warp - 1; r < 16; r += 3) {
        uint4 v[4];
        float a0 = 0.f, a1 = 0.f, b0 = 0.f, b1 = 0.f;
#pragma unroll
        for (int j = 0; j < 4; j++) {
          v[j] = lds128(sb + OFF_LN + r * 2048 + lane * 16 + j * 512);
          const uint32_t u[4] = {v[j].x, v[j].y, v[j].z, v[j].w};
#pragma unroll
          for (int i = 0; i < 4; i++) { const float a = bf_lo(u[i]), b = bf_hi(u[i]); a0 += a; a1 += b; b0 = fmaf(a, a, b0); b1 = fmaf(b, b, b1); }
        }
        a0 += a1; b0 += b1;
#pragma unroll
        for (int o = 16; o; o >>= 1) { a0 += __shfl_xor_sync(~0u, a0, o); b0 += __shfl_xor_sync(~0u, b0, o); }
        const float mean = a0 * (1.f / DM);
        float mb, inv;
        ln_round(mean, fmaxf(fmaf(b0, 1.f / DM, -mean * mean), 0.f), mb, inv);
        inv *= AT_C;
        const uint32_t nm2 = pack_bf16(-mb, -mb);
        uint4* dst = reinterpret_cast<uint4*>(g_xn + (size_t)(cta * 16 + r) * DM) + lane;
#pragma unroll
        for (int j = 0; j < 4; j++)
          dst[j * 32] = make_uint4(ln_apply(v[j].x, nm2, inv), ln_apply(v[j].y, nm2, inv), ln_apply(v[j].z, nm2, inv), ln_apply(v[j].w, nm2, inv));
      }
      __syncwarp();
      if (lane == 0) {
        mbar_arrive(B(B_LND));
        fence_gpu();
        red_add(&g_cnt[C_LN + (cta >> 3)], 1);
      }
      TL(3, warp, lane == 0);
      if (warp == 3) {
        if (lane == 0) {
#pragma unroll 1
          for (int i = 0; i < 6; i++) {
            const int c = i < 2 ? C_LN + (i ? ti : 15 - ti) : (i < 4 ? C_QKV + (i - 2) * 8 + mp : C_CTX + (i - 4) * 16 + mt);
            spin_until_ge<true>(&g_cnt[c], i < 2 ? 24 : 16);
            fence_async_all();
            mbar_arrive(B(B_DEP + i));
            TL(3, 4 + i, true);
          }
        }
      } else if (warp == 1 && lane == 0) {
        mbar_wait(B(B_WR), 0);
#pragma unroll 1
        for (int i = 0; i < 6; i++) {
          const int c = i < 2 ? C_QKV + gq + i * 8 : C_CTX + (i >> 2) * 16 + ((i == 3 || i == 4) ? ti : 15 - ti);
          mbar_wait(B(B_PUB + i), 0);
          if (i >= 2 && i < 5) {
#pragma unroll 1
            for (int n = 0; n < 8 / ST_G; n++) {
              const int h = n / (4 / ST_G), a = n % (4 / ST_G) * ST_G;
              asm volatile("cp.async.bulk.tensor.3d.global.shared::cta.bulk_group [%0, {%2,%3,%4}], [%1];" ::"l"(&p.ctx_st),
                           "r"(sb + (i == 4 ? 6 * SLOT + h * 16384 : (3 + 2 * h) * SLOT + (i - 2) * 16384) + a * 4096),
                           "r"(0), "r"((i == 2 ? 15 - ti : ti) * 128 + h * 64), "r"((hh + (i >> 2) * 16) * 4 + a) : "memory");
              asm volatile("cp.async.bulk.commit_group;\ncp.async.bulk.wait_group.read 0;" ::: "memory");
              if (ST_NS) __nanosleep(ST_NS);
            }
            mbar_arrive(B(B_QP + i - 2));
            asm volatile("cp.async.bulk.wait_group 0;" ::: "memory");
          }
          fence_gpu();
          red_add(&g_cnt[c], 1);
          TS(1 + i);
        }
      }
      if (warp == 2) {
        mbar_wait(B(B_SET), 0);
#pragma unroll 1
        for (int i = XR_CAND + lane; i < XR_SIZE; i += 32) xr[i] = make_uint4(~0u, ~0u, ~0u, ~0u);
        __syncwarp();
        if (lane == 0) { fence_gpu(); mbar_arrive(B(B_SET2)); }
        __syncwarp();
        mbar_wait(B(B_PF), 0);
        uint32_t t0;
        asm volatile("mov.u32 %0, %%clock;" : "=r"(t0));
        constexpr int NF = 8;
#pragma unroll 1
        for (int i = 0; i < NF; i++) {
          const char* a = (const char*)(((i & 2) ? wgate : wup) + (size_t)((6 + (i >> 2)) * 128 + cta) * FF) + min((i & 1) * 32 + lane, 55) * 128;
          asm volatile("prefetch.global.L2 [%0];" ::"l"(a));
#pragma unroll 1
          for (int n = 0; n < 64; n++) {
            __nanosleep(100);
            uint32_t t;
            asm volatile("mov.u32 %0, %%clock;" : "=r"(t));
            if (t - t0 >= (uint32_t)(i + 1) * PF_CLK) break;
          }
        }
      }
      __syncwarp();
      mbar_wait(B(B_OUT), 0);
      if (tid == 64) TS(7);
#pragma unroll 1
      for (int i = warp - 1; i < 64; i += 3) {
        const int row = 2 * i + (lane >> 4);
        const uint2 rs = *reinterpret_cast<const uint2*>(sp + OFF_RSTAT + row * 8);
        uint4* q = reinterpret_cast<uint4*>(sp + OFF_STG + (row >> 6) * 16384 + ((lane & 15) >> 3) * 8192 + (row & 63) * 128 + ((lane & 7) << 4));
        const uint4 v = *q;
        const float inv = __uint_as_float(rs.y);
        *q = make_uint4(hadd2_bf(v.x, ln_apply(v.x, rs.x, inv)), hadd2_bf(v.y, ln_apply(v.y, rs.x, inv)),
                        hadd2_bf(v.z, ln_apply(v.z, rs.x, inv)), hadd2_bf(v.w, ln_apply(v.w, rs.x, inv)));
      }
      asm volatile("fence.proxy.async.shared::cta;" ::: "memory");
      bar_sync(4, 96);
      if (warp == 1) {
        mbar_wait(B(B_OUT2), 0);
        const uint32_t* keys = reinterpret_cast<const uint32_t*>(sp + OFF_MISC);
        const int t0 = 0x7FFF - (keys[16] & 0x7FFF) - mt * 128, t1 = 0x7FFF - (keys[17] & 0x7FFF) - mt * 128;
        const int grp = lane >> 1;
        if (grp != (t0 >> 3) && grp != (t1 >> 3))
          asm volatile("cp.async.bulk.tensor.2d.global.shared::cta.bulk_group [%0, {%2,%3}], [%1];" ::"l"(&p.out),
                       "r"(sb + OFF_STG + (grp >> 3) * 16384 + (lane & 1) * 8192 + (grp & 7) * 1024), "r"(gq * 128 + (lane & 1) * 64), "r"(mt * 128 + grp * 8) : "memory");
        asm volatile("cp.async.bulk.commit_group;" ::: "memory");
#pragma unroll 1
        for (int k = 0; k < 8; k++) {
          const int tt = k < 4 ? t0 : t1, row = (tt & ~7) + (k & 3) * 2 + (lane >> 4);
          if (tt >= 0 && tt < 128 && row != t0 && row != t1)
            *reinterpret_cast<uint4*>(out + (size_t)(mt * 128 + row) * DM + gq * 128 + (lane & 15) * 8) =
                lds128(sb + OFF_STG + (row >> 6) * 16384 + ((lane & 15) >> 3) * 8192 + (row & 63) * 128 + (((lane & 7) ^ (row & 7)) << 4));
        }
        asm volatile("cp.async.bulk.wait_group.read 0;" ::: "memory");
      }
      TL(2, 25, tid == 32);
      if (tid == 32) TS(8);
    }
    __syncwarp();
    cluster_arrive();
    cluster_wait();
  } else {
    reg_alloc<232>();
    const int w = wg - 1, cw = warp - 4, ct = tid - 128;
    const uint32_t stg = sb + OFF_STG + w * 16384 + (cw & 3) * 2048;
    auto publish = [&](int i) { __syncwarp(); if (lane == 0) mbar_arrive(B(B_PUB + i)); };
    auto release2 = [&](uint32_t b) { if (lane < 2) mbar_arrive_cta(b, lane); };
    float R[128];
    float O[64], acc[64];
    uint32_t pk[64];
    uint32_t* const Q = pk;
    uint32_t P[32];
    auto packed = [&](int i) {
      const float* v = R + 16 * (i >> 1) + 2 * (i & 1);
      return make_uint4(pack_bf16(v[0], v[1]), pack_bf16(v[4], v[5]), pack_bf16(v[8], v[9]), pack_bf16(v[12], v[13]));
    };
    const uint32_t q_st = sb + (cw & 3) * 1024 + (lane >> 2) * 64 + (((lane & 3) ^ (lane >> 3)) << 4);
    const uint32_t q_ld = sb + (cw & 3) * 1024 + (lane & 15) * 64 + (((lane >> 4) ^ ((lane >> 1) & 3)) << 4);
    auto park = [&](uint32_t off, int i, uint4 v) {
      asm volatile("st.shared.v4.u32 [%0], {%1,%2,%3,%4};" ::"r"(q_st + off + (i >> 1) * 4096 + (i & 1) * 512), "r"(v.x), "r"(v.y), "r"(v.z), "r"(v.w) : "memory");
    };
    auto load_q = [&](uint32_t off, int k) { ldsm4(Q + 4 * k, ((q_ld + off) ^ ((k & 1) << 5)) + (k >> 1) * 4096); };
    {
      TL(0, 1, tid == 128);
      __nv_bfloat16* pdst = g_qkv;
      auto put = [&](int i) { __stcs(reinterpret_cast<uint4*>(pdst + (i & 1) * 8 * NQ + (i >> 1) * 32), make_uint4(pk[4 * i], pk[4 * i + 1], pk[4 * i + 2], pk[4 * i + 3])); };
      const uint64_t da0 = mk_desc(sb + w * 8192, 16, 1024, 1);
      const uint64_t db0 = mk_desc(sb + 16384, 8192, 1024, 1);
      int st = 0; uint32_t ph = 0;
      auto issue = [&](int accum) {
        mbar_wait_c(B(B_FULL1 + st), ph);
        const uint64_t da = desc_add(da0, st * P1_STAGE), db = desc_add(db0, st * P1_STAGE);
        wg_fence();
#pragma unroll
        for (int k = 0; k < 4; k++) mma_n256_ss<1>(R, desc_add(da, k * 32), desc_add(db, k * 2048), k == 0 ? accum : 1);
        wg_commit();
      };
#pragma unroll 1
      for (int t = 0; t < 6; t++) {
        const int nk = t >= 4 ? 16 : 8;
        const bool tr = t > 0 && t < 5;
        issue(0);
        TL(0, 2 + 2 * t + 16 * w, (tid & 127) == 0);
        if (tr) { put(0); put(1); }
        int prev = st;
        if (++st == 4) { st = 0; ph ^= 1; }
#pragma unroll 1
        for (int kb = 1; kb < nk; kb++) {
          if (kb == nk - 1 && w == 1) bar_sync(5, 256);
          issue(1);
          if (kb == nk - 1 && w == 0) bar_arrive(5, 256);
          if (tr) {
#pragma unroll
            for (int i = 1; i < 8; i++) if (kb == i) { put(2 * i); put(2 * i + 1); }
            if (kb == 7 && !(t & 1)) publish((t >> 1) - 1);
          } else if (t == 5 && kb == 2) {
            mbar_wait_c(B(B_LND), 0);
#pragma unroll
            for (int i = 0; i < 8; i++) park(6 * SLOT + w * 16384, i, make_uint4(pk[4 * i], pk[4 * i + 1], pk[4 * i + 2], pk[4 * i + 3]));
            __syncwarp();
#pragma unroll
            for (int k = 0; k < 8; k++) load_q(6 * SLOT + w * 16384, k);
            __syncwarp();
#pragma unroll
            for (int i = 0; i < 8; i++) park(6 * SLOT + w * 16384, i, make_uint4(pk[32 + 4 * i], pk[33 + 4 * i], pk[34 + 4 * i], pk[35 + 4 * i]));
          }
          wg_wait<1>();
          release2(B(B_EMPTY1 + prev));
          prev = st;
          if (++st == 4) { st = 0; ph ^= 1; }
        }
        if (t == 5 && w == 1) bar_arrive(6, 256);
        pdst = g_qkv + (size_t)(((t & 1) + 1) * SEQ + mt * 128 + cw * 16 + (lane >> 2)) * NQ + (gq + (t >> 1) * 8) * 256 + (lane & 3) * 8;
        wg_wait<0>();
        fence_regs<128>(R);
        release2(B(B_EMPTY1 + prev));
        TL(0, 3 + 2 * t + 16 * w, (tid & 127) == 0);
        if (t == 5) break;
#pragma unroll
        for (int i = 0; i < 16; i++) { const uint4 v = packed(i); pk[4 * i] = v.x; pk[4 * i + 1] = v.y; pk[4 * i + 2] = v.z; pk[4 * i + 3] = v.w; }
      }
    }
    auto issue3 = [&](int st, uint32_t ph, int accum) {
      mbar_wait_c(B(B_FULL3 + st), ph);
      const uint64_t da = mk_desc(sb + OFF_R3 + w * 8192 + st * SLOT, 16, 1024, 1), db = mk_desc(sb + OFF_R3 + 16384 + st * SLOT, 8192, 1024, 1);
      wg_fence();
#pragma unroll
      for (int k = 0; k < 4; k++) mma_n128_ss<1>(acc, desc_add(da, k * 32), desc_add(db, k * 2048), k == 0 ? accum : 1);
      wg_commit();
    };
    uint32_t wf[128];
    auto grab = [&](int c, uint32_t off) {
      const int wr_ = cw * 16 + (lane & 7) + (lane >> 4) * 8;
      const uint32_t wl = sb + off + wr_ * 64 + ((((lane >> 3) & 1) ^ ((wr_ >> 1) & 3)) << 4);
#pragma unroll
      for (int m = 0; m < 8; m++)
        asm volatile("ldmatrix.sync.aligned.m8n8.x4.trans.shared.b16 {%0,%1,%2,%3}, [%4];"
                     : "=r"(wf[16 * c + 4 * m]), "=r"(wf[16 * c + 4 * m + 1]), "=r"(wf[16 * c + 4 * m + 2]), "=r"(wf[16 * c + 4 * m + 3])
                     : "r"((wl + (m >> 1) * 8192) ^ ((m & 1) << 5)) : "memory");
    };
    uint4 ob[8];
    {
      const int wrow = cw * 16;
      const uint64_t dk0 = mk_desc(sb, 16, 1024, 1);
      const uint64_t dv0 = mk_desc(sb + 2 * SLOT, 16384, 1024, 1);
      const uint32_t pin = sb + OFF_MISC + 1028;
      float l0 = 0.f, l1 = 0.f;
      float inv[2] = {0.f, 0.f};
      int g = 0, t = 0;
      uint32_t fail = 0;
      auto piece = [&](int tt) { return (uint32_t)(tt == 3 ? 6 * SLOT + w * 16384 : (3 + 2 * w) * SLOT + (tt - 1) * 16384); };
      uint32_t par = 0;
      auto issue_s = [&](float* S, auto between) {
        const uint64_t dk = desc_add(dk0, par * 16);
        mma_n128_rs0(S, Q, dk);
#pragma unroll
        for (int k = 1; k < 8; k++) {
          if (k == SH_K) between();
          mma_n128_rs<0>(S, Q + 4 * k, desc_add(dk, (k >> 2) * 16384 + (k & 3) * 32), 1);
        }
        wg_commit();
      };
      auto issue_pv = [&](bool half, int accum) {
        const uint64_t dv = desc_add(dv0, ((g - 1) & 1) * 2 * SLOT);
        wg_fence();
#pragma unroll
        for (int k = 0; k < 4; k++) mma_n128_rs<1>(O, P + 4 * k, desc_add(dv, k * 2048), k == 0 ? accum : 1);
        wg_commit();
        if (UNLIKELY(half)) {
          wg_fence();
          wg_commit();
        } else {
          wg_fence();
#pragma unroll
          for (int k = 4; k < 8; k++) mma_n128_rs<1>(O, P + 4 * k, desc_add(dv, k * 2048), 1);
          wg_commit();
        }
        bar_arrive(2 - w, 256);
        wg_wait<2>();
        fence_regs<32>(Q);
      };
      uint32_t rel;
      asm("mapa.shared::cluster.u32 %0, %1, %2;" : "=r"(rel) : "r"(B(B_KE + 1)), "r"(lane & 1));
      auto release_k = [&]() {
        if (lane < 2) asm volatile("mbarrier.arrive.shared::cluster.b64 _, [%0];" ::"r"(rel) : "memory");
        rel ^= 8;
      };
      auto pv_done = [&]() {
        sched_fence(q_st);
        wg_wait<0>();
        fence_regs<64>(O); fence_regs<32>(P);
        if (lane < 2) asm volatile("mbarrier.arrive.shared::cluster.b64 _, [%0+16];" ::"r"(rel) : "memory");
      };
      auto row_inv = [&]() {
        l0 += __shfl_xor_sync(~0u, l0, 1); l1 += __shfl_xor_sync(~0u, l1, 1);
        l0 += __shfl_xor_sync(~0u, l0, 2); l1 += __shfl_xor_sync(~0u, l1, 2);
        const bool ok = __all_sync(~0u, l0 >= AT_LO && l0 <= AT_HI && l1 >= AT_LO && l1 <= AT_HI) != 0;
        asm("rcp.approx.ftz.f32 %0, %1;" : "=f"(inv[0]) : "f"(l0));
        asm("rcp.approx.ftz.f32 %0, %1;" : "=f"(inv[1]) : "f"(l1));
        l0 = l1 = 0.f;
        return ok;
      };
      auto scaled = [&](int i) {
        const float* o = O + 16 * (i >> 1) + 2 * (i & 1);
        const float c = inv[i & 1];
        return make_uint4(pack_bf16(o[0] * c, o[1] * c), pack_bf16(o[4] * c, o[5] * c), pack_bf16(o[8] * c, o[9] * c), pack_bf16(o[12] * c, o[13] * c));
      };
      auto hand_over = [&](int tt) { asm volatile("fence.proxy.async.shared::cta;" ::: "memory"); publish(2 + tt); };
      {
        if (w == 0) { bar_arrive(7, 256); bar_sync(6, 256); } else { bar_arrive(1, 256); bar_sync(7, 256); }
#pragma unroll
        for (int i = 0; i < 8; i++) park(piece(1), i, packed(i));
        mbar_wait_c(B(B_KF), 0);
        bar_sync(1 + w, 256);
        float S[64];
        wg_fence();
        issue_s(S, []() {});
        bar_arrive(2 - w, 256);
        TL(1, 0, tid == 128);
#pragma unroll
        for (int i = 0; i < 8; i++) park(piece(2), i, packed(8 + i));
        wg_wait<0>();
        fence_regs<64>(S);
        release2(B(B_KE));
        TL(1, 1, tid == 128);
        at_exp<0, 16>(S);
        sched_fence(q_st);
        at_exp<16, 32>(S); at_fin<0, 16>(S, P, l0, l1);
        sched_fence(q_st);
        at_exp<32, 48>(S); at_fin<16, 32>(S, P, l0, l1);
        mbar_wait_f(B(B_KF + 1), 0);
        sched_fence(q_st);
        at_exp<48, 64>(S); at_fin<32, 64>(S, P, l0, l1);
        TL(1, 2, tid == 128);
      }
      const uint64_t m_first = 1ull | (1ull << (16 - ti)) | (1ull << 17) | (1ull << (18 + ti));
      const uint64_t m_diag = (3ull << (15 - ti)) | (3ull << (17 + ti));
      const uint64_t m_last = m_first >> 1;
      enum { F_FIRST = 1, F_DIAG = 2, F_LAST = 4, F_PFIRST = 8, F_PHALF = 16, F_FLUSH = 32, F_PUB = 64, F_STOP = 128 };
      auto kind = [&](int gn) {
        const uint32_t a = (uint32_t)((m_first << 2) >> gn), d = (uint32_t)((m_diag << 1) >> gn);
        return ((a >> 2) & 1) * F_FIRST | ((d >> 1) & 1) * F_DIAG | ((uint32_t)(m_last >> gn) & 1) * F_LAST | ((a >> 1) & 1) * (gn > 1 ? F_PFIRST | F_FLUSH : F_PFIRST) |
               (w == 0 ? (d & 1) * F_PHALF | ((d >> 1) & 1) * F_STOP : 0) | (gn > 2 ? (a & 1) * F_PUB : 0) | (gn == 34 ? F_STOP : 0);
      };
      const uint32_t kinds = pinned(kind(lane + 3));
      uint32_t f = F_PFIRST, fn;
      int tp = 0;
      bool vok;
      auto shadow1 = [&]() {
        vok = mbar_try(B(B_VF + ((g - 1) & 1)), ((g - 1) >> 1) & 1);
        at_sum(P, f & F_PHALF, l0, l1);
        fn = __shfl_sync(~0u, kinds, max(g - 2, 0));
      };
      auto shadow2 = [&]() {
        if (UNLIKELY(!vok || (f & (F_PUB | F_FLUSH | F_FIRST)))) {
          if (f & F_PUB) { if (!((fail >> tp) & 1)) hand_over(tp); tp++; }
          if (f & F_FLUSH) {
#pragma unroll
            for (int i = 0; i < 8; i++) park(piece(t), i, scaled(i));
          }
          if (f & F_FIRST) { if (!row_inv()) fail |= 1u << t; t++; }
          if (!vok) mbar_wait_c(B(B_VF + ((g - 1) & 1)), ((g - 1) >> 1) & 1);
        }
      };
      auto exp_q = [&](float* S, auto kc, auto nc) {
        constexpr int k = decltype(kc)::value, n = decltype(nc)::value;
        asm volatile("{\n.reg .pred p;\nsetp.ne.b32 p, %5, 0;\n@p ldmatrix.sync.aligned.m8n8.x4.shared.b16 {%0,%1,%2,%3}, [%4];\n}"
                     : "+r"(Q[4 * k]), "+r"(Q[4 * k + 1]), "+r"(Q[4 * k + 2]), "+r"(Q[4 * k + 3])
                     : "r"(((q_ld + piece(t + 1)) ^ ((k & 1) << 5)) + (k >> 1) * 4096), "r"(f & F_LAST) : "memory");
        at_exp<n * k, n * k + n>(S);
      };
      g = 1; par = SLOT / 16;
#pragma unroll 1
      for (;;) {
        {
          TC(w, g, 6);
          bar_sync(1 + w, 256);
          fence_regs<32>(Q);
          float S[64];
          wg_fence();
          issue_s(S, [&]() { sched_fence(q_st); TCF(w, g); shadow1(); sched_fence(q_st); });
          TC(w, g, 7);
          shadow2();
          fence_regs<64>(O); fence_regs<32>(P);
          issue_pv(f & F_PHALF, ~f & F_PFIRST);
          fence_regs<64>(S);
          TC(w, g, 0);
          release_k();
          at_exp<0, 8>(S);
          if (UNLIKELY(f & (F_DIAG | F_LAST))) {
            at_mask(S + 32, (f & F_DIAG) ? wrow - 64 : 64, lane);
            unroll8([&](auto kc) { exp_q(S + 8, kc, std::integral_constant<int, AT_R1 / 8 - 1>{}); });
          } else {
            at_exp<8, AT_R1>(S);
          }
          TC(w, g, 1);
          if (AT_R1 != AT_R2) {
            sched_fence(q_st);
            wg_wait<1>();
            fence_regs<16>(P);
            at_exp<AT_R1, AT_R2>(S); at_fin<0, AT_R1>(S, P, l0, l1);
          }
          TC(w, g, 2);
          pv_done();
          g = pinned(g + 1); par = pinned(par ^ (SLOT / 16)); f = fn;
          const bool kok = mbar_try(B(B_KF + (g & 1)), g < 34 ? (g >> 1) & 1 : 0);
          at_exp<AT_R2, 64>(S); at_fin<AT_R1 != AT_R2 ? AT_R1 : 0, 64>(S, P, l0, l1);
          TC(w, g, 5);
          if (!TCLK) TL(1, 1 + g, tid == 128);
          if (kok && !(f & F_STOP)) continue;
          if (g == 34) break;
          mbar_wait_c(B(B_KF + (g & 1)), (g >> 1) & 1);
        }
#pragma unroll 1
        while (f & F_STOP) {
          TC(w, g, 6);
          TCF(w, g);
          shadow1();
          shadow2();
          bar_sync(1, 256);
          fence_regs<64>(O); fence_regs<32>(Q); fence_regs<32>(P);
          float S[32];
          const uint64_t dk = desc_add(dk0, par * 16);
          wg_fence();
          mma_n64_rs0(S, Q, dk);
#pragma unroll
          for (int k = 1; k < 8; k++) mma_n64_rs(S, Q + 4 * k, desc_add(dk, (k >> 2) * 16384 + (k & 3) * 32), 1);
          wg_commit();
          TC(w, g, 7);
          issue_pv(f & F_PHALF, ~f & F_PFIRST);
          fence_regs<32>(S);
          TC(w, g, 0);
          release_k();
          at_mask(S, wrow, lane);
          unroll8([&](auto kc) { exp_q(S, kc, std::integral_constant<int, 4>{}); });
          pv_done();
          g++; par ^= SLOT / 16; f = fn;
          at_fin<0, 32>(S, P, l0, l1);
          if (!TCLK) TL(1, 1 + g, tid == 128);
          mbar_wait_c(B(B_KF + (g & 1)), (g >> 1) & 1);
        }
      }
      at_sum(P, false, l0, l1);
      if (!row_inv()) fail |= 8;
      if (__builtin_expect(fail != 0, 0)) {
#pragma unroll 1
        for (int tt = 0; tt < 4; tt++) {
          if (tt < 3 && !((fail >> tt) & 1)) continue;
          slow_tile(O, Q, l0, l1, wq, (((tt + 1) & 2) ? ti : 15 - ti) * 128 + wrow, hh + (tt & 2) * 8, lane);
          row_inv();
          if (tt < 3) {
#pragma unroll
            for (int i = 0; i < 8; i++) park(piece(tt + 1), i, scaled(i));
            hand_over(tt);
          }
        }
#pragma unroll
        for (int i = 0; i < 32; i++) P[i] = 0;
      }
      mbar_wait_c(B(B_VF + 1), 0);
      bar_sync(1 + w, 256);
      fence_regs<64>(O); fence_regs<32>(P);
      wg_fence();
#pragma unroll
      for (int k = 0; k < 8; k++) mma_n128_rs<1>(O, P + 4 * k, desc_add(dv0, 2 * SLOT + k * 2048), 1);
      wg_commit();
      if (w == 0) bar_arrive(2, 256);
      issue3(0, 0, 0);
      if (ffn && WMODE) mbar_wait_c(B(B_WF), 0); else mbar_wait_c(B(B_QP + 2), 0);
      grab(0, 3 * SLOT);
      pin_order(__uint_as_float(wf[28] & wf[24]), pin);
      __syncwarp();
      release2(B(B_WE));
      wg_wait<1>();
      fence_regs<64>(O); fence_regs<32>(P);
      release2(B(B_VE + 1));
      grab(2, 5 * SLOT);
#pragma unroll
      for (int i = 0; i < 8; i++) ob[i] = scaled(i);
      pin_order(__uint_as_float(wf[60] & wf[56]), pin);
      __syncwarp();
      release2(B(B_WE + 1));
      sched_fence(q_st);
      grab(4, 6 * SLOT);
      TL(1, 36, tid == 128);
    }
    {
      int st = 1, prev = 0; uint32_t ph = 0;
      __nv_bfloat16* dst = g_qkv + (size_t)((15 - ti) * 128 + cw * 16 + (lane >> 2)) * NQ + (hh + 16) * 128 + (lane & 3) * 8;
      auto kblock = [&](auto between) {
        issue3(st, ph, 1);
        between();
        wg_wait<1>();
        release2(B(B_EMPTY3 + prev));
        prev = st;
        if (++st == 6) { st = 0; ph ^= 1; }
      };
#pragma unroll 1
      for (int kb = 1; kb < 9; kb++)
        kblock([&]() {
#pragma unroll
          for (int i = 0; i < 8; i++) if (kb == i + 1) *reinterpret_cast<uint4*>(dst + (i & 1) * 8 * NQ + (i >> 1) * 32) = ob[i];
        });
      publish(5);
      if (lane == 0) mbar_arrive(B(B_XE));
      TL(2, 2, tid == 128);
#pragma unroll 1
      for (int kb = 9; kb < 64; kb++) {
        kblock([]() {});
        if ((kb & 7) == 0) TL(2, 1 + (kb >> 3), tid == 128);
      }
    }
    const int r0 = lane >> 2;
    uint32_t hp[32], tb[16];
    mbar_wait_c(B(B_XF), 0);
    mbar_wait_c(B(B_WR), 0);
    mbar_wait_c(B(B_SET2), 0);
#pragma unroll
    for (int j = 0; j < 16; j++) {
      const uint32_t q = stg + r0 * 128 + (lane & 3) * 4 + (j >> 3) * 8192 + (((j & 7) ^ r0) << 4);
      asm volatile("ld.shared.u32 %0, [%1];" : "=r"(hp[2 * j]) : "r"(q) : "memory");
      asm volatile("ld.shared.u32 %0, [%1];" : "=r"(hp[2 * j + 1]) : "r"(q + 1024) : "memory");
      asm volatile("ld.shared.u32 %0, [%1];" : "=r"(tb[j]) : "r"(sb + OFF_MISC + 512 + (r0 & 1) * 256 + (lane & 3) * 4 + j * 16) : "memory");
    }
    wg_wait<0>();
    fence_regs<64>(acc);
    TL(2, 10, tid == 128);
    {
      float d[4] = {0.f, 0.f, 0.f, 0.f}, qa[4] = {0.f, 0.f, 0.f, 0.f}, qb[4] = {0.f, 0.f, 0.f, 0.f};
#pragma unroll
      for (int j = 0; j < 16; j++) {
        hp[2 * j] = hadd2_bf(hp[2 * j], pack_bf16(acc[4 * j], acc[4 * j + 1]));
        hp[2 * j + 1] = hadd2_bf(hp[2 * j + 1], pack_bf16(acc[4 * j + 2], acc[4 * j + 3]));
        if (j & 1) {
          mma16816(d, hp[2 * j - 2], hp[2 * j - 1], hp[2 * j], hp[2 * j + 1], tb[j - 1], tb[j]);
          mma16816(qa, hp[2 * j - 2], hp[2 * j - 1], hp[2 * j], hp[2 * j + 1], hp[2 * j - 2], hp[2 * j]);
          mma16816(qb, hp[2 * j - 2], hp[2 * j - 1], hp[2 * j], hp[2 * j + 1], hp[2 * j - 1], hp[2 * j + 1]);
        }
      }
      const float s2a = __shfl_sync(~0u, (r0 & 1) ? qa[1] : qa[0], r0 * 4 + (r0 >> 1));
      const float s2b = __shfl_sync(~0u, (r0 & 1) ? qb[3] : qb[2], r0 * 4 + (r0 >> 1));
      if ((lane & 3) == 0) {
        __stcg(reinterpret_cast<float4*>(xr + XR_PS + cw * 16 + r0), make_float4(d[0], s2a, d[1], 0.f));
        __stcg(reinterpret_cast<float4*>(xr + XR_PS + cw * 16 + r0 + 8), make_float4(d[2], s2b, d[3], 0.f));
      }
    }
    __syncwarp();
    stage_store_128(stg, lane, hp);
    TL(2, 11, tid == 128);
    __syncwarp();
    uint32_t* keys = reinterpret_cast<uint32_t*>(sp + OFF_MISC);
    {
      uint4 ps[4];
      poll_chunks(ps, g_xr + (mt * 8 + (ct & 1) * 4) * XR_SIZE + XR_PS + (ct >> 1), XR_SIZE);
      TL(2, 12, tid == 128);
      auto F = [](uint32_t u) { return __uint_as_float(u); };
      float s1 = (F(ps[0].x) + F(ps[1].x)) + (F(ps[2].x) + F(ps[3].x)), s2 = (F(ps[0].y) + F(ps[1].y)) + (F(ps[2].y) + F(ps[3].y));
      float s3 = (F(ps[0].z) + F(ps[1].z)) + (F(ps[2].z) + F(ps[3].z));
      s1 += __shfl_xor_sync(~0u, s1, 1); s2 += __shfl_xor_sync(~0u, s2, 1); s3 += __shfl_xor_sync(~0u, s3, 1);
      const float mean = s1 * (1.f / DM);
      float mb, inv;
      ln_round(mean, fmaxf(fmaf(s2, 1.f / DM, -mean * mean), 0.f), mb, inv);
      uint32_t u = pack_bf16((s3 - mb * *reinterpret_cast<const float*>(sp + OFF_MISC + 1024)) * inv, 0.f);
      if (u == 0x8000u) u = 0;
      u = (u & 0x8000u) ? (~u & 0xFFFFu) : (u | 0x8000u);
      const uint32_t key = (u << 16) | (0x7FFFu - (mt * 128 + (ct >> 1)));
      const uint32_t nm2 = pack_bf16(-mb, -mb);
      if (!(ct & 1)) *reinterpret_cast<uint2*>(sp + OFF_RSTAT + (ct >> 1) * 8) = make_uint2(nm2, __float_as_uint(inv));
      const uint32_t c1 = __reduce_max_sync(~0u, key);
      const uint32_t c2 = __reduce_max_sync(~0u, key == c1 ? 0u : key);
      if (lane == 0) __stcg(reinterpret_cast<uint2*>(xr + XR_KEY) + cw, make_uint2(c1, c2));
      const int row = (0x7FFF - (((lane >> 4) ? c2 : c1) & 0x7FFF)) & 15;
      const uint32_t rn = __shfl_sync(~0u, nm2, row * 2);
      const float ri = __shfl_sync(~0u, inv, row * 2);
      const uint4 v = lds128(stg + ((lane & 15) >> 3) * 8192 + row * 128 + (((lane & 7) ^ (row & 7)) << 4));
      __stcg(xr + XR_CAND + cw * 64 + 32 + lane, make_uint4(ln_apply(v.x, rn, ri), ln_apply(v.y, rn, ri), ln_apply(v.z, rn, ri), ln_apply(v.w, rn, ri)));
      __stcg(xr + XR_CAND + cw * 64 + lane, v);
    }
    publish(6);
    TL(2, 13, tid == 128);
    uint32_t wd[16][4];
    if (cw == 0) {
        uint4 kv[2];
        poll_chunks(kv, g_xr + ((lane >> 1) * 8 + gq) * XR_SIZE + XR_KEY + (lane & 1) * 2, 1);
        const uint32_t a1 = max(kv[0].x, kv[0].z), a2 = max(min(kv[0].x, kv[0].z), max(kv[0].y, kv[0].w));
        const uint32_t b1 = max(kv[1].x, kv[1].z), b2 = max(min(kv[1].x, kv[1].z), max(kv[1].y, kv[1].w));
        const uint32_t k1 = max(a1, b1), k2 = max(min(a1, b1), max(a2, b2));
        const uint32_t m1 = __reduce_max_sync(~0u, k1);
        const uint32_t m2 = __reduce_max_sync(~0u, k1 == m1 ? k2 : k1);
        if (lane == 0) {
          keys[16] = m1; keys[17] = m2;
          mbar_arrive(B(B_OUT2));
        }
    }
    bar_sync(3, 256);
    cluster_arrive();
    const uint32_t top1 = keys[16], top2 = keys[17];
    TL(2, 14, tid == 128);
    const int t0 = 0x7FFF - (top1 & 0x7FFF), t1 = 0x7FFF - (top2 & 0x7FFF);
    auto cand = [&](int second, int chunk) {
      const int tk = second ? t1 : t0;
      return g_xr + ((tk >> 7) * 8 + (chunk >> 4)) * XR_SIZE + XR_CAND + ((tk >> 4) & 7) * 64 + ((second && (t0 >> 4) == (t1 >> 4)) ? 16 : 0) + (chunk & 15);
    };
    if (rid == 127 && ct < C_NUM) g_cnt[ct] = 0;
    if (ffn) {
      const int c8 = ct & 127;
      *reinterpret_cast<uint4*>(sp + SL_SCR * SLOT + w * 2064 + c8 * 16) = poll_chunk(cand(w, c8) + 32);
      mbar_wait_c(B(B_FULL3 + 64 % 6), (64 / 6) & 1);
      grab(6, OFF_R3 + (64 % 6) * SLOT);
      bar_sync(3, 256);
      TL(2, 15, tid == 128);
      float d[4][4];
#pragma unroll
      for (int m = 0; m < 4; m++) d[m][0] = d[m][1] = d[m][2] = d[m][3] = 0.f;
#pragma unroll
      for (int s = 0; s < 8; s++) {
        const uint8_t* bp = sp + SL_SCR * SLOT + (r0 & 1) * 2064 + (s * 128 + cw * 16 + (lane & 3) * 2) * 2;
        const uint32_t b0 = *reinterpret_cast<const uint32_t*>(bp), b1 = *reinterpret_cast<const uint32_t*>(bp + 16);
#pragma unroll
        for (int m = 0; m < 4; m++) mma16816(d[m], wf[16 * s + 4 * m], wf[16 * s + 4 * m + 1], wf[16 * s + 4 * m + 2], wf[16 * s + 4 * m + 3], b0, b1);
      }
      float* red = reinterpret_cast<float*>(sp + SL_SCR * SLOT + 8192);
      if ((lane & 3) == 0) {
#pragma unroll
        for (int m = 0; m < 4; m++) {
          *reinterpret_cast<float2*>(red + cw * 128 + (m * 16 + r0) * 2) = make_float2(d[m][0], d[m][1]);
          *reinterpret_cast<float2*>(red + cw * 128 + (m * 16 + 8 + r0) * 2) = make_float2(d[m][2], d[m][3]);
        }
      }
      const int wds = w ? 66 % 6 : 65 % 6;
      mbar_wait_c(B(B_FULL3 + wds), w ? (66 / 6) & 1 : (65 / 6) & 1);
#pragma unroll
      for (int i = 0; i < 16; i++) {
        const int k = (i & 1) * 16 + (lane & 7) + (lane >> 4) * 8;
        asm volatile("ldmatrix.sync.aligned.m8n8.x4.trans.shared.b16 {%0,%1,%2,%3}, [%4];"
                     : "=r"(wd[i][0]), "=r"(wd[i][1]), "=r"(wd[i][2]), "=r"(wd[i][3])
                     : "r"(sb + OFF_R3 + wds * SLOT + (2 * (cw & 3) + (i >> 3)) * 4096 + k * 128 + (((2 * ((i >> 1) & 3) + ((lane >> 3) & 1)) ^ (lane & 7)) << 4)) : "memory");
      }
      bar_sync(3, 256);
      TL(2, 16, tid == 128);
      if (ct < 64) {
        float u = 0.f, gg = 0.f;
#pragma unroll
        for (int i = 0; i < 8; i++) { u += red[i * 128 + ct]; gg += red[i * 128 + 64 + ct]; }
        u = bf_round(u); gg = bf_round(gg);
        const float sg = bf_round(__fdividef(gg, 1.f + __expf(-gg)));
        reinterpret_cast<__nv_bfloat16*>(sp + OFF_MISC + 128)[(ct & 1) * 40 + (ct >> 1)] = __float2bfloat16_rn(sg * u);
      }
      bar_sync(3, 256);
      TL(2, 17, tid == 128);
      const uint32_t* ap = reinterpret_cast<const uint32_t*>(sp + OFF_MISC + 128 + (r0 & 1) * 80 + (lane & 3) * 4);
      const uint32_t a0 = ap[0], a1 = ap[4], a2 = ap[8], a3 = ap[12];
      float2* yp = reinterpret_cast<float2*>(sp + SL_SCR * SLOT + 16384) + cw * 128 + r0;
#pragma unroll
      for (int i = 0; i < 8; i++) {
        float y[4] = {0.f, 0.f, 0.f, 0.f};
        mma16816(y, wd[2 * i][0], wd[2 * i][1], wd[2 * i][2], wd[2 * i][3], a0, a1);
        mma16816(y, wd[2 * i + 1][0], wd[2 * i + 1][1], wd[2 * i + 1][2], wd[2 * i + 1][3], a2, a3);
        if ((lane & 3) == 0) { yp[i * 16] = make_float2(y[0], y[1]); yp[i * 16 + 8] = make_float2(y[2], y[3]); }
      }
      __syncwarp();
      uint4* yd = g_xr + (cw * 16 + (lane >> 2)) * XR_SIZE + XR_Y + fid * 4 + (lane & 3);
      __stcg(yd, lds128(sb + SL_SCR * SLOT + 16384 + cw * 1024 + lane * 16));
      __stcg(yd + 8 * XR_SIZE, lds128(sb + SL_SCR * SLOT + 16384 + cw * 1024 + 512 + lane * 16));
    }
    TL(2, 18, tid == 128);
    TL(2, 38, tid == 352);
    {
      float* red2 = reinterpret_cast<float*>(sp + SL_SCR * SLOT + 12288);
      uint4 hv, hx;
      float rs;
      if (cw == 7) {
        hv = poll_chunk(cand(lane & 1, rid));
        hx = poll_chunk(cand(lane & 1, rid) + 32);
        uint32_t u = ((lane & 1) ? top2 : top1) >> 16;
        u = (u & 0x8000u) ? (u & 0x7FFFu) : (~u & 0xFFFFu);
        rs = bf_round(__fdividef(1.f, 1.f + __expf(-__uint_as_float(u << 16))));
        TL(2, 37, lane == 0 && rs > -1.f);
      } else {
        uint4 z[2];
        poll_chunks(z, xr + XR_Y + ct * 2, 1);
        __syncwarp();
        TL(2, 30 + cw, lane == 0);
        float v[8] = {__uint_as_float(z[0].x), __uint_as_float(z[0].y), __uint_as_float(z[0].z), __uint_as_float(z[0].w),
                      __uint_as_float(z[1].x), __uint_as_float(z[1].y), __uint_as_float(z[1].z), __uint_as_float(z[1].w)};
#pragma unroll
        for (int i = 0; i < 4; i++) { const bool up = lane & 8; v[i] = (up ? v[i + 4] : v[i]) + __shfl_xor_sync(~0u, up ? v[i] : v[i + 4], 8); }
#pragma unroll
        for (int i = 0; i < 2; i++) { const bool up = lane & 4; v[i] = (up ? v[i + 2] : v[i]) + __shfl_xor_sync(~0u, up ? v[i] : v[i + 2], 4); }
        { const bool up = lane & 2; v[0] = (up ? v[1] : v[0]) + __shfl_xor_sync(~0u, up ? v[0] : v[1], 2); }
        v[0] += __shfl_xor_sync(~0u, v[0], 16);
        if (lane < 16) red2[cw * 16 + (lane & 1) * 8 + (lane >> 1)] = v[0];
      }
      bar_sync(3, 256);
      TL(2, 19, tid == 128);
      if (cw == 7) {
        float y = 0.f;
#pragma unroll
        for (int i = 0; i < 7; i++) y += red2[i * 16 + (lane & 15)];
        const uint32_t hw[4] = {hv.x, hv.y, hv.z, hv.w}, hm[4] = {hx.x, hx.y, hx.z, hx.w};
        uint32_t o[4];
#pragma unroll
        for (int e = 0; e < 4; e++) {
          const uint32_t yb = pack_bf16(__shfl_sync(~0u, y, 4 * e + (lane & 1)), __shfl_sync(~0u, y, 4 * e + 2 + (lane & 1)));
          o[e] = hadd2_bf(hw[e], hadd2_bf(hm[e], pack_bf16(bf_lo(yb) * rs, bf_hi(yb) * rs)));
        }
        if (lane < 2) reinterpret_cast<uint4*>(out + (size_t)(lane ? t1 : t0) * DM)[rid] = make_uint4(o[0], o[1], o[2], o[3]);
        TL(2, 21, lane == 0);
      }
    }
    TL(2, 20, tid == 128);
    __syncwarp();
    cluster_wait();
  }
}

typedef CUresult (*EncodeFn)(CUtensorMap*, CUtensorMapDataType, cuuint32_t, void*, const cuuint64_t*, const cuuint64_t*, const cuuint32_t*,
                             const cuuint32_t*, CUtensorMapInterleave, CUtensorMapSwizzle, CUtensorMapL2promotion, CUtensorMapFloatOOBfill);
EncodeFn g_enc = nullptr;

void map2(CUtensorMap* m, const void* ptr, uint64_t rows, uint64_t cols, uint32_t bc, uint32_t br) {
  const CUtensorMapSwizzle sw = bc == 64 ? CU_TENSOR_MAP_SWIZZLE_128B : CU_TENSOR_MAP_SWIZZLE_64B;
  cuuint64_t gd[2] = {cols, rows}, gs[1] = {cols * 2};
  cuuint32_t bd[2] = {bc, br}, es[2] = {1, 1};
  g_enc(m, CU_TENSOR_MAP_DATA_TYPE_BFLOAT16, 2, (void*)ptr, gd, gs, bd, es, CU_TENSOR_MAP_INTERLEAVE_NONE, sw,
        CU_TENSOR_MAP_L2_PROMOTION_L2_128B, CU_TENSOR_MAP_FLOAT_OOB_FILL_NONE);
}
void map3(CUtensorMap* m, const void* ptr, uint64_t rows, uint64_t cols, uint32_t br, uint32_t bch, uint32_t bc = 64) {
  cuuint64_t gd[3] = {bc, rows, cols / bc}, gs[2] = {cols * 2, bc * 2};
  cuuint32_t bd[3] = {bc, br, bch}, es[3] = {1, 1, 1};
  g_enc(m, CU_TENSOR_MAP_DATA_TYPE_BFLOAT16, 3, (void*)ptr, gd, gs, bd, es, CU_TENSOR_MAP_INTERLEAVE_NONE, bc == 64 ? CU_TENSOR_MAP_SWIZZLE_128B : CU_TENSOR_MAP_SWIZZLE_64B,
        CU_TENSOR_MAP_L2_PROMOTION_L2_128B, CU_TENSOR_MAP_FLOAT_OOB_FILL_NONE);
}

}

extern "C" void kernel_launch(void* const* d_in, const int* in_sizes, int n_in, void* d_out, int out_size) {
  const __nv_bfloat16* x = (const __nv_bfloat16*)d_in[0];
  const __nv_bfloat16* ckv = (const __nv_bfloat16*)d_in[1];
  const __nv_bfloat16* wq = (const __nv_bfloat16*)d_in[2];
  const __nv_bfloat16* wk = (const __nv_bfloat16*)d_in[3];
  const __nv_bfloat16* wv = (const __nv_bfloat16*)d_in[4];
  const __nv_bfloat16* wo = (const __nv_bfloat16*)d_in[5];
  const __nv_bfloat16* w_r = (const __nv_bfloat16*)d_in[7];
  const __nv_bfloat16* wgate = (const __nv_bfloat16*)d_in[8];
  const __nv_bfloat16* wup = (const __nv_bfloat16*)d_in[9];
  const __nv_bfloat16* wdown = (const __nv_bfloat16*)d_in[10];
  __nv_bfloat16* out = (__nv_bfloat16*)d_out;

  if (!g_enc) {
    void* fn = nullptr;
    cudaDriverEntryPointQueryResult qr;
    cudaGetDriverEntryPoint("cuTensorMapEncodeTiled", &fn, cudaEnableDefault, &qr);
    g_enc = (EncodeFn)fn;
    cudaFuncSetAttribute(fused_kernel, cudaFuncAttributeMaxDynamicSharedMemorySize, SMEM_BYTES);
  }
  void *xn, *qkv;
  cudaGetSymbolAddress(&xn, g_xn);
  cudaGetSymbolAddress(&qkv, g_qkv);

  Params p;
  map2(&p.xn, xn, SEQ, DM, 64, 128);
  map2(&p.ckv, ckv, SEQ, DC, 64, 128);
  map3(&p.wq, wq, DM, NQ, 64, 2);
  map3(&p.wk, wk, DC, NQ, 64, 2);
  map3(&p.wv, wv, DC, NQ, 64, 2);
  map3(&p.kv, qkv, 3 * SEQ, NQ, 128, 1);
  map2(&p.ctx_ld, qkv, SEQ, NQ, 64, 128);
  map3(&p.ctx_st, qkv, SEQ, NQ, 64, ST_G, 32);
  map3(&p.wo, wo, NQ, DM, 64, 1);
  map3(&p.x, x, SEQ, DM, 64, 2);
  map3(&p.wd, wdown, FF, DM, 32, 8);
  map2(&p.out, out, SEQ, DM, 64, 8);
  map2(&p.wg, wgate, DM, FF, 32, 128);
  map2(&p.wu, wup, DM, FF, 32, 128);
  fused_kernel<<<128, 384, SMEM_BYTES, cudaStreamPerThread>>>(p, x, wq, w_r, wgate, wup, out);
}
```

```cpp
#include <cuda_runtime.h>
#include <cuda_bf16.h>
#include <cuda.h>
#include <stdint.h>
#include <type_traits>

#pragma nv_diag_suppress 549
namespace {

constexpr int SEQ = 2048, DM = 1024, NH = 32, HD = 128, DC = 512, NQ = NH * HD, FF = 3584;

__device__ __align__(1024) __nv_bfloat16 g_xn[SEQ * DM];
__device__ __align__(1024) __nv_bfloat16 g_qkv[3 * SEQ * NQ];
constexpr int XR_PS = 0;
constexpr int XR_KEY = 128;
constexpr int XR_FLAG = 132;
constexpr int XR_CAND = 136;
constexpr int XR_Y = 648;
constexpr int XR_SIZE = 1104;
__device__ __align__(1024) uint4 g_xr[128 * XR_SIZE];
constexpr int C_LN = 0, C_QKV = 16, C_CTX = 32, C_NUM = 64;
__device__ unsigned g_cnt[C_NUM];

#define TL(k, i, cond) do {} while (0)
#define TL_BYTES 0
#define TL_INIT() do {} while (0)
#define TL_DUMP() do {} while (0)
#define TC(w, g, i) do {} while (0)
#define TCF(w, g) do {} while (0)
#define TS(i) do {} while (0)
#undef TCLK
#define TCLK 0

__device__ __forceinline__ uint32_t s2u(const void* p) { return (uint32_t)__cvta_generic_to_shared(p); }
__device__ __forceinline__ void mbar_init(uint32_t b, uint32_t c) { asm volatile("mbarrier.init.shared::cta.b64 [%0], %1;" ::"r"(b), "r"(c) : "memory"); }
__device__ __forceinline__ void mbar_expect(uint32_t b, uint32_t bytes) { asm volatile("mbarrier.arrive.expect_tx.shared::cta.b64 _, [%0], %1;" ::"r"(b), "r"(bytes) : "memory"); }
__device__ __forceinline__ void mbar_arrive(uint32_t b) { asm volatile("mbarrier.arrive.shared::cta.b64 _, [%0];" ::"r"(b) : "memory"); }
__device__ __forceinline__ void mbar_arrive_cta(uint32_t b, uint32_t cta) {
  asm volatile("{\n.reg .b32 r;\nmapa.shared::cluster.u32 r, %0, %1;\nmbarrier.arrive.shared::cluster.b64 _, [r];\n}" ::"r"(b), "r"(cta) : "memory");
}
__device__ __forceinline__ bool mbar_test(uint32_t b, uint32_t ph) {
  uint32_t ok;
  asm volatile("{\n.reg .pred p;\nmbarrier.test_wait.parity.shared::cta.b64 p, [%1], %2;\nselp.u32 %0, 1, 0, p;\n}" : "=r"(ok) : "r"(b), "r"(ph) : "memory");
  return ok;
}
__device__ __forceinline__ void mbar_wait(uint32_t b, uint32_t ph) {
  asm volatile(
      "{\n.reg .pred p;\n.reg .u32 n;\nmov.u32 n, 0;\n"
      "LW:\nmbarrier.try_wait.parity.shared::cta.b64 p, [%0], %1, 20000;\n@p bra LD;\n"
      "add.u32 n, n, 1;\nsetp.lt.u32 p, n, 0x40000;\n@p bra LW;\ntrap;\nLD:\n}" ::"r"(b), "r"(ph) : "memory");
}
__device__ __forceinline__ void mbar_wait_c(uint32_t b, uint32_t ph) {
  asm volatile(
      "{\n.reg .pred p;\n.reg .u32 n;\nmov.u32 n, 0;\n"
      "LW:\nmbarrier.try_wait.parity.shared::cta.b64 p, [%0], %1;\n@p bra LD;\n"
      "add.u32 n, n, 1;\nsetp.lt.u32 p, n, 0x100000;\n@p bra LW;\ntrap;\nLD:\n}" ::"r"(b), "r"(ph) : "memory");
}
__device__ __forceinline__ bool mbar_try(uint32_t b, uint32_t ph) {
  uint32_t ok;
  asm volatile("{\n.reg .pred p;\nmbarrier.try_wait.parity.shared::cta.b64 p, [%1], %2;\nselp.u32 %0, 1, 0, p;\n}" : "=r"(ok) : "r"(b), "r"(ph) : "memory");
  return ok;
}
#define UNLIKELY(c) __builtin_expect(!!(c), 0)
__device__ __forceinline__ void mbar_wait_f(uint32_t b, uint32_t ph) { if (UNLIKELY(!mbar_try(b, ph))) mbar_wait_c(b, ph); }
__device__ __forceinline__ uint32_t pinned(uint32_t v) { uint32_t r; asm volatile("mov.b32 %0, %1;" : "=r"(r) : "r"(v)); return r; }
__device__ __forceinline__ int lane_id() { int r; asm volatile("mov.u32 %0, %%laneid;" : "=r"(r)); return r; }
template <bool SLEEP = false>
__device__ __forceinline__ void spin_until_ge(const unsigned* p, unsigned target) {
  asm volatile(
      "{\n.reg .pred p, q;\n.reg .u32 n, v;\nmov.u32 n, 0;\nsetp.ne.u32 q, %2, 0;\n"
      "LW:\nld.acquire.gpu.global.u32 v, [%0];\nsetp.ge.u32 p, v, %1;\n@p bra LD;\n@q nanosleep.u32 200;\n"
      "add.u32 n, n, 1;\nsetp.lt.u32 p, n, 0x400000;\n@p bra LW;\ntrap;\nLD:\n}" ::"l"(p), "r"(target), "n"((int)SLEEP) : "memory");
}
template <int N>
__device__ __forceinline__ void poll_chunks(uint4 (&v)[N], const uint4* p, int stride) {
#pragma unroll 1
  for (int n = 0; n < 0x400000; n++) {
    uint32_t m = 0;
#pragma unroll
    for (int i = 0; i < N; i++) {
      asm volatile("ld.relaxed.gpu.global.v4.u32 {%0,%1,%2,%3}, [%4];" : "=r"(v[i].x), "=r"(v[i].y), "=r"(v[i].z), "=r"(v[i].w) : "l"(p + i * stride) : "memory");
    }
#pragma unroll
    for (int i = 0; i < N; i++) m = max(max(m, max(v[i].x, v[i].y)), max(v[i].z, v[i].w));
    if (__all_sync(~0u, m != 0xFFFFFFFFu)) break;
  }
}
__device__ __forceinline__ void fence_async_all() { asm volatile("fence.proxy.async;" ::: "memory"); }
__device__ __forceinline__ void bar_sync(int id, int n) { asm volatile("bar.sync %0, %1;" ::"r"(id), "r"(n) : "memory"); }
__device__ __forceinline__ void bar_arrive(int id, int n) { asm volatile("bar.arrive %0, %1;" ::"r"(id), "r"(n) : "memory"); }
__device__ __forceinline__ void cluster_arrive() { asm volatile("barrier.cluster.arrive.relaxed.aligned;" ::: "memory"); }
__device__ __forceinline__ void cluster_wait() { asm volatile("barrier.cluster.wait.acquire.aligned;" ::: "memory"); }
__device__ __forceinline__ void fence_gpu() { asm volatile("fence.acq_rel.gpu;" ::: "memory"); }
__device__ __forceinline__ void red_add(unsigned* p, unsigned v) { asm volatile("red.relaxed.gpu.global.add.u32 [%0], %1;" ::"l"(p), "r"(v) : "memory"); }
__device__ __forceinline__ void prefetch_tm(const CUtensorMap* m) { asm volatile("prefetch.tensormap [%0];" ::"l"(m) : "memory"); }

__device__ __forceinline__ void tma_ld2(uint32_t dst, const CUtensorMap* m, uint32_t bar, int c0, int c1) {
  asm volatile("cp.async.bulk.tensor.2d.shared::cta.global.mbarrier::complete_tx::bytes [%0], [%1, {%3,%4}], [%2];" ::"r"(dst), "l"(m), "r"(bar), "r"(c0), "r"(c1) : "memory");
}
__device__ __forceinline__ void tma_ld3(uint32_t dst, const CUtensorMap* m, uint32_t bar, int c0, int c1, int c2) {
  asm volatile("cp.async.bulk.tensor.3d.shared::cta.global.mbarrier::complete_tx::bytes [%0], [%1, {%3,%4,%5}], [%2];" ::"r"(dst), "l"(m), "r"(bar), "r"(c0), "r"(c1), "r"(c2) : "memory");
}
__device__ __forceinline__ void tma_ld3_mc(uint32_t dst, const CUtensorMap* m, uint32_t bar, int c0, int c1, int c2, uint16_t mask) {
  asm volatile("cp.async.bulk.tensor.3d.shared::cluster.global.mbarrier::complete_tx::bytes.multicast::cluster [%0], [%1, {%3,%4,%5}], [%2], %6;" ::"r"(dst), "l"(m), "r"(bar), "r"(c0), "r"(c1), "r"(c2), "h"(mask) : "memory");
}
__device__ __forceinline__ void l2_prefetch(const void* p, uint32_t bytes) { asm volatile("cp.async.bulk.prefetch.L2.global [%0], %1;" ::"l"(p), "r"(bytes) : "memory"); }

__device__ __forceinline__ void wg_fence() { asm volatile("wgmma.fence.sync.aligned;" ::: "memory"); }
__device__ __forceinline__ void wg_commit() { asm volatile("wgmma.commit_group.sync.aligned;" ::: "memory"); }
template <int N> __device__ __forceinline__ void wg_wait() { asm volatile("wgmma.wait_group.sync.aligned %0;" ::"n"(N) : "memory"); }
template <int N> __device__ __forceinline__ void reg_alloc() { asm volatile("setmaxnreg.inc.sync.aligned.u32 %0;" ::"n"(N)); }
template <int N> __device__ __forceinline__ void reg_dealloc() { asm volatile("setmaxnreg.dec.sync.aligned.u32 %0;" ::"n"(N)); }
template <int N> __device__ __forceinline__ void fence_regs(float* d) {
#pragma unroll
  for (int i = 0; i < N; i++) asm volatile("" : "+f"(d[i])::"memory");
}
template <int N> __device__ __forceinline__ void fence_regs(uint32_t* d) {
#pragma unroll
  for (int i = 0; i < N; i++) asm volatile("" : "+r"(d[i])::"memory");
}

__device__ __forceinline__ uint64_t mk_desc(uint32_t addr, uint32_t lbo, uint32_t sbo, uint32_t swz) {
  uint32_t lo = ((addr & 0x3FFFF) >> 4) | ((lbo >> 4) << 16);
  uint32_t hi = (sbo >> 4) | (swz << 30);
  return ((uint64_t)hi << 32) | lo;
}
__device__ __forceinline__ uint64_t desc_add(uint64_t d, uint32_t bytes) {
  uint32_t lo = (uint32_t)d + (bytes >> 4);
  return (d & 0xFFFFFFFF00000000ull) | lo;
}

#define R8(b) "+f"(d[b + 0]), "+f"(d[b + 1]), "+f"(d[b + 2]), "+f"(d[b + 3]), "+f"(d[b + 4]), "+f"(d[b + 5]), "+f"(d[b + 6]), "+f"(d[b + 7])
#define REGS32 "%0,%1,%2,%3,%4,%5,%6,%7,%8,%9,%10,%11,%12,%13,%14,%15,%16,%17,%18,%19,%20,%21,%22,%23,%24,%25,%26,%27,%28,%29,%30,%31"
#define REGS64 REGS32 ",%32,%33,%34,%35,%36,%37,%38,%39,%40,%41,%42,%43,%44,%45,%46,%47,%48,%49,%50,%51,%52,%53,%54,%55,%56,%57,%58,%59,%60,%61,%62,%63"
#define REGS128 REGS64 ",%64,%65,%66,%67,%68,%69,%70,%71,%72,%73,%74,%75,%76,%77,%78,%79,%80,%81,%82,%83,%84,%85,%86,%87,%88,%89,%90,%91,%92,%93,%94,%95," \
               "%96,%97,%98,%99,%100,%101,%102,%103,%104,%105,%106,%107,%108,%109,%110,%111,%112,%113,%114,%115,%116,%117,%118,%119,%120,%121,%122,%123,%124,%125,%126,%127"

template <int TB>
__device__ __forceinline__ void mma_n256_ss(float (&d)[128], uint64_t a, uint64_t b, int acc) {
  asm volatile("{\n.reg .pred p;\nsetp.ne.b32 p, %130, 0;\n"
               "wgmma.mma_async.sync.aligned.m64n256k16.f32.bf16.bf16 {" REGS128 "}, %128, %129, p, 1, 1, 0, %131;\n}\n"
               : R8(0), R8(8), R8(16), R8(24), R8(32), R8(40), R8(48), R8(56), R8(64), R8(72), R8(80), R8(88), R8(96), R8(104), R8(112), R8(120)
               : "l"(a), "l"(b), "r"(acc), "n"(TB));
}
template <int TB>
__device__ __forceinline__ void mma_n128_ss(float* d, uint64_t a, uint64_t b, int acc) {
  asm volatile("{\n.reg .pred p;\nsetp.ne.b32 p, %66, 0;\n"
               "wgmma.mma_async.sync.aligned.m64n128k16.f32.bf16.bf16 {" REGS64 "}, %64, %65, p, 1, 1, 0, %67;\n}\n"
               : R8(0), R8(8), R8(16), R8(24), R8(32), R8(40), R8(48), R8(56)
               : "l"(a), "l"(b), "r"(acc), "n"(TB));
}
template <int TB>
__device__ __forceinline__ void mma_n128_rs(float* d, const uint32_t* a, uint64_t b, int acc) {
  asm volatile("{\n.reg .pred p;\nsetp.ne.b32 p, %69, 0;\n"
               "wgmma.mma_async.sync.aligned.m64n128k16.f32.bf16.bf16 {" REGS64 "}, {%64,%65,%66,%67}, %68, p, 1, 1, %70;\n}\n"
               : R8(0), R8(8), R8(16), R8(24), R8(32), R8(40), R8(48), R8(56)
               : "r"(a[0]), "r"(a[1]), "r"(a[2]), "r"(a[3]), "l"(b), "r"(acc), "n"(TB));
}
__device__ __forceinline__ void mma_n64_rs(float* d, const uint32_t* a, uint64_t b, int acc) {
  asm volatile("{\n.reg .pred p;\nsetp.ne.b32 p, %37, 0;\n"
               "wgmma.mma_async.sync.aligned.m64n64k16.f32.bf16.bf16 {" REGS32 "}, {%32,%33,%34,%35}, %36, p, 1, 1, 0;\n}\n"
               : R8(0), R8(8), R8(16), R8(24)
               : "r"(a[0]), "r"(a[1]), "r"(a[2]), "r"(a[3]), "l"(b), "r"(acc));
}
#define W8(b) "=f"(d[b + 0]), "=f"(d[b + 1]), "=f"(d[b + 2]), "=f"(d[b + 3]), "=f"(d[b + 4]), "=f"(d[b + 5]), "=f"(d[b + 6]), "=f"(d[b + 7])
__device__ __forceinline__ void mma_n128_rs0(float* d, const uint32_t* a, uint64_t b) {
  asm volatile("wgmma.mma_async.sync.aligned.m64n128k16.f32.bf16.bf16 {" REGS64 "}, {%64,%65,%66,%67}, %68, 0, 1, 1, 0;\n"
               : W8(0), W8(8), W8(16), W8(24), W8(32), W8(40), W8(48), W8(56)
               : "r"(a[0]), "r"(a[1]), "r"(a[2]), "r"(a[3]), "l"(b));
}
__device__ __forceinline__ void mma_n64_rs0(float* d, const uint32_t* a, uint64_t b) {
  asm volatile("wgmma.mma_async.sync.aligned.m64n64k16.f32.bf16.bf16 {" REGS32 "}, {%32,%33,%34,%35}, %36, 0, 1, 1, 0;\n"
               : W8(0), W8(8), W8(16), W8(24)
               : "r"(a[0]), "r"(a[1]), "r"(a[2]), "r"(a[3]), "l"(b));
}
__device__ __forceinline__ uint32_t pack_bf16(float lo, float hi) {
  uint32_t r;
  asm("cvt.rn.bf16x2.f32 %0, %1, %2;" : "=r"(r) : "f"(hi), "f"(lo));
  return r;
}
__device__ __forceinline__ float bf_lo(uint32_t v) { return __uint_as_float(v << 16); }
__device__ __forceinline__ float bf_hi(uint32_t v) { return __uint_as_float(v & 0xFFFF0000u); }
__device__ __forceinline__ float bf_round(float v) { return bf_lo(pack_bf16(v, v)); }
__device__ __forceinline__ void stsm4(uint32_t addr, uint32_t r0, uint32_t r1, uint32_t r2, uint32_t r3) {
  asm volatile("stmatrix.sync.aligned.m8n8.x4.shared.b16 [%0], {%1,%2,%3,%4};" ::"r"(addr), "r"(r0), "r"(r1), "r"(r2), "r"(r3) : "memory");
}
__device__ __forceinline__ uint4 lds128(uint32_t addr) {
  uint4 v;
  asm volatile("ld.shared.v4.u32 {%0,%1,%2,%3}, [%4];" : "=r"(v.x), "=r"(v.y), "=r"(v.z), "=r"(v.w) : "r"(addr));
  return v;
}
__device__ __forceinline__ float ex2(float x) {
  float y;
  asm("ex2.approx.ftz.f32 %0, %1;" : "=f"(y) : "f"(x));
  return y;
}
__device__ __forceinline__ void pin_order(float v, uint32_t dummy) {
  asm volatile("{\n.reg .pred p;\nsetp.eq.b32 p, %0, 0xFFFFFFFF;\n@p st.shared.b32 [%1], %0;\n}" ::"r"(__float_as_uint(v)), "r"(dummy) : "memory");
}
__device__ __forceinline__ void sched_fence(uint32_t dummy) {
  asm volatile("{\n.reg .pred p;\n.reg .u32 c;\nsetp.eq.b32 p, %0, 0xFFFFFFFF;\nmov.u32 c, %%clock;\n@p st.shared.b32 [%0], c;\n}" ::"r"(dummy) : "memory");
}
__device__ __forceinline__ void stage_store_128(uint32_t base, int lane, const uint32_t* pk) {
  const int row = (lane & 7) + ((lane >> 3) & 1) * 8;
  const uint32_t rb = base + row * 128;
  const int hi = lane >> 4;
#pragma unroll
  for (int j = 0; j < 8; j++) {
    const int chunk = 2 * j + hi;
    const uint32_t a = rb + (j >> 2) * 8192 + (((chunk & 7) ^ (lane & 7)) << 4);
    stsm4(a, pk[4 * j + 0], pk[4 * j + 1], pk[4 * j + 2], pk[4 * j + 3]);
  }
}
__device__ __forceinline__ void ln_round(float mean, float var, float& m_bf, float& inv_s) {
  const uint32_t mv = pack_bf16(mean, var);
  m_bf = bf_lo(mv);
  float sq, rc;
  asm("sqrt.approx.f32 %0, %1;" : "=f"(sq) : "f"(bf_round(bf_hi(mv) + 1e-5f)));
  asm("rcp.approx.ftz.f32 %0, %1;" : "=f"(rc) : "f"(bf_round(sq)));
  inv_s = rc;
}
__device__ __forceinline__ uint32_t hadd2_bf(uint32_t a, uint32_t b) {
  uint32_t r;
  asm("add.rn.bf16x2 %0, %1, %2;" : "=r"(r) : "r"(a), "r"(b));
  return r;
}
__device__ __forceinline__ uint32_t ln_apply(uint32_t h, uint32_t nm2, float inv_s) {
  const uint32_t d = hadd2_bf(h, nm2);
  return pack_bf16(bf_lo(d) * inv_s, bf_hi(d) * inv_s);
}
__device__ __forceinline__ void ldsm4(uint32_t* r, uint32_t addr) {
  asm volatile("ldmatrix.sync.aligned.m8n8.x4.shared.b16 {%0,%1,%2,%3}, [%4];" : "=r"(r[0]), "=r"(r[1]), "=r"(r[2]), "=r"(r[3]) : "r"(addr) : "memory");
}
__device__ __forceinline__ void mma16816(float* d, uint32_t a0, uint32_t a1, uint32_t a2, uint32_t a3, uint32_t b0, uint32_t b1) {
  asm volatile("mma.sync.aligned.m16n8k16.row.col.f32.bf16.bf16.f32 {%0,%1,%2,%3}, {%4,%5,%6,%7}, {%8,%9}, {%0,%1,%2,%3};"
               : "+f"(d[0]), "+f"(d[1]), "+f"(d[2]), "+f"(d[3]) : "r"(a0), "r"(a1), "r"(a2), "r"(a3), "r"(b0), "r"(b1));
}

template <class F>
__device__ __forceinline__ void unroll8(F f) {
  f(std::integral_constant<int, 0>{}); f(std::integral_constant<int, 1>{}); f(std::integral_constant<int, 2>{}); f(std::integral_constant<int, 3>{});
  f(std::integral_constant<int, 4>{}); f(std::integral_constant<int, 5>{}); f(std::integral_constant<int, 6>{}); f(std::integral_constant<int, 7>{});
}

constexpr float AT_C = 0.08838834764831845f * 1.4426950408889634f;
#define AT_LO 0x1p-40f
#define AT_HI 0x1p40f
#define SH_K 4
#define AT_R1 48
#define AT_R2 48
template <int I0, int I1>
__device__ __forceinline__ void at_exp(float* S) {
#pragma unroll
  for (int i = I0; i < I1; i++) asm volatile("ex2.approx.ftz.f32 %0, %0;" : "+f"(S[i]));
}
#define HSUM 1
template <int I0, int I1>
__device__ __forceinline__ void at_fin(const float* S, uint32_t* P, float& l0, float& l1) {
#pragma unroll
  for (int i = I0; i < I1; i += 4) {
    if (!HSUM) { l0 += S[i] + S[i + 1]; l1 += S[i + 2] + S[i + 3]; }
    P[i / 2] = pack_bf16(S[i], S[i + 1]); P[i / 2 + 1] = pack_bf16(S[i + 2], S[i + 3]);
  }
}
__device__ __forceinline__ void at_sum(const uint32_t* P, bool half, float& l0, float& l1) {
  uint32_t u[4];
#pragma unroll
  for (int r = 0; r < 4; r++) {
    const uint32_t* q = P + (r >> 1) * 16 + (r & 1);
    u[r] = hadd2_bf(hadd2_bf(hadd2_bf(q[0], q[2]), hadd2_bf(q[4], q[6])), hadd2_bf(hadd2_bf(q[8], q[10]), hadd2_bf(q[12], q[14])));
  }
  u[0] = hadd2_bf(u[0], half ? 0u : u[2]);
  u[1] = hadd2_bf(u[1], half ? 0u : u[3]);
  l0 += bf_lo(u[0]) + bf_hi(u[0]);
  l1 += bf_lo(u[1]) + bf_hi(u[1]);
}
__device__ __forceinline__ void at_mask(float* S, int r, int lane) {
  const int d = r + (lane >> 2) - (lane & 3) * 2;
#pragma unroll
  for (int j = 0; j < 8; j++) {
    float dummy0 = 0.f, dummy1 = 0.f;
    float& lo0 = j < 7 ? S[4 * (j < 7 ? j + 1 : j) + 2] : dummy0;
    float& lo1 = j < 7 ? S[4 * (j < 7 ? j + 1 : j) + 3] : dummy1;
    asm("{\n.reg .pred p, q;\nsetp.lt.s32 p, %4, %5;\nsetp.le.s32 q, %4, %5;\n"
        "@p add.f32 %0, %0, 0fFF800000;\n@q add.f32 %1, %1, 0fFF800000;\n@p add.f32 %2, %2, 0fFF800000;\n@q add.f32 %3, %3, 0fFF800000;\n}"
        : "+f"(S[4 * j]), "+f"(S[4 * j + 1]), "+f"(lo0), "+f"(lo1) : "r"(d), "r"(8 * j));
  }
}
__device__ __forceinline__ uint32_t ldg32(const __nv_bfloat16* p) { return __ldcg(reinterpret_cast<const uint32_t*>(p)); }
__device__ __forceinline__ uint32_t ldg16x2(const __nv_bfloat16* p, int stride) {
  return (uint32_t)__ldcg(reinterpret_cast<const unsigned short*>(p)) | ((uint32_t)__ldcg(reinterpret_cast<const unsigned short*>(p + stride)) << 16);
}
__device__ __forceinline__ void slow_tile(float* O, uint32_t* Q, float& l0, float& l1, const __nv_bfloat16* wq, int row0, int head, int lane, uint32_t dummy) {
  const int r = lane >> 2, q = lane & 3;
#pragma unroll
  for (int i = 0; i < 64; i++) O[i] = 0.f;
  {
    const __nv_bfloat16* xa = g_xn + (size_t)(row0 + r) * DM + 2 * q;
    const __nv_bfloat16* wb = wq + (size_t)(2 * q) * NQ + head * HD + (r >> 1) * 8 + (r & 1);
#pragma unroll 1
    for (int k = 0; k < DM; k += 16) {
      const uint32_t a0 = ldg32(xa + k), a1 = ldg32(xa + k + 8 * DM), a2 = ldg32(xa + k + 8), a3 = ldg32(xa + k + 8 * DM + 8);
#pragma unroll
      for (int j = 0; j < 16; j++) {
        const __nv_bfloat16* wp = wb + (size_t)k * NQ + (j >> 2) * 32 + (j & 3) * 2;
        mma16816(O + 4 * j, a0, a1, a2, a3, ldg16x2(wp, NQ), ldg16x2(wp + 8 * NQ, NQ));
        if (j == 7) sched_fence(dummy);
      }
    }
  }
#pragma unroll
  for (int i = 0; i < 32; i++) Q[i] = pack_bf16(O[2 * i], O[2 * i + 1]);
#pragma unroll
  for (int i = 0; i < 64; i++) O[i] = 0.f;
  float m0 = -INFINITY, m1 = -INFINITY;
  l0 = l1 = 0.f;
#pragma unroll 1
  for (int kv = 0; kv <= row0; kv += 16) {
    float s[8] = {0.f, 0.f, 0.f, 0.f, 0.f, 0.f, 0.f, 0.f};
    const __nv_bfloat16* kp = g_qkv + (size_t)(SEQ + kv + r) * NQ + head * HD + 2 * q;
#pragma unroll
    for (int k = 0; k < 8; k++) {
      mma16816(s, Q[4 * k], Q[4 * k + 1], Q[4 * k + 2], Q[4 * k + 3], ldg32(kp + 16 * k), ldg32(kp + 16 * k + 8));
      mma16816(s + 4, Q[4 * k], Q[4 * k + 1], Q[4 * k + 2], Q[4 * k + 3], ldg32(kp + 8 * NQ + 16 * k), ldg32(kp + 8 * NQ + 16 * k + 8));
    }
#pragma unroll
    for (int i = 0; i < 8; i++)
      if (kv + (i >> 2) * 8 + 2 * q + (i & 1) > row0 + r + (i & 2) * 4) s[i] = -INFINITY;
    float a = fmaxf(fmaxf(fmaxf(s[0], s[1]), fmaxf(s[4], s[5])), m0), b = fmaxf(fmaxf(fmaxf(s[2], s[3]), fmaxf(s[6], s[7])), m1);
    a = fmaxf(a, __shfl_xor_sync(~0u, a, 1)); b = fmaxf(b, __shfl_xor_sync(~0u, b, 1));
    a = fmaxf(a, __shfl_xor_sync(~0u, a, 2)); b = fmaxf(b, __shfl_xor_sync(~0u, b, 2));
    const float c0 = ex2(m0 - a), c1 = ex2(m1 - b);
    m0 = a; m1 = b;
#pragma unroll
    for (int i = 0; i < 8; i++) s[i] = ex2(s[i] - ((i & 2) ? b : a));
    l0 = l0 * c0 + (s[0] + s[1]) + (s[4] + s[5]);
    l1 = l1 * c1 + (s[2] + s[3]) + (s[6] + s[7]);
    sched_fence(dummy);
    const uint32_t p0 = pack_bf16(s[0], s[1]), p1 = pack_bf16(s[2], s[3]), p2 = pack_bf16(s[4], s[5]), p3 = pack_bf16(s[6], s[7]);
    const __nv_bfloat16* vp = g_qkv + (size_t)(2 * SEQ + kv + 2 * q) * NQ + head * HD + r;
#pragma unroll
    for (int j = 0; j < 16; j++) {
      O[4 * j] *= c0; O[4 * j + 1] *= c0; O[4 * j + 2] *= c1; O[4 * j + 3] *= c1;
      mma16816(O + 4 * j, p0, p1, p2, p3, ldg16x2(vp + 8 * j, NQ), ldg16x2(vp + 8 * NQ + 8 * j, NQ));
      if (j == 7) sched_fence(dummy);
    }
  }
}

constexpr int P1_STAGE = 49152;
constexpr int SLOT = 32768;
constexpr int OFF_LN = 6 * SLOT, OFF_R3 = 0;
constexpr int OFF_BAR = 229376;
constexpr int OFF_MISC = OFF_BAR + 8 * 58;
constexpr int SMEM_BYTES = OFF_MISC + 2080 + TL_BYTES;
enum : int {
  B_FULL1 = 0, B_KF = 4, B_VF = 6, B_FULL3 = 8, B_XF = 14, B_LN = 15, B_DEP = 16, B_OUT2 = 22, B_FIN = 23, B_SET = 24, B_SET2 = 25, B_QP = 26, B_WF2 = 29,
  B_WF = 30, B_WR = 31,
  B_LND = 32,
  B_XE = 33, B_PUB = 34, B_OUT = 40, B_OUT3 = 41,
  B_EMPTY1 = 42, B_KE = 46, B_VE = 48, B_EMPTY3 = 50, B_WE = 56, B_NUM = 58
};
constexpr int PRE = 3;
#define LN_PF 4
#define LN_LD 9
constexpr int LN_PFN = 2;
constexpr int OFF_STG = 0, SL_SCR = 1;
#define SET_NS 100
#define SET_KB 46
#define ST_G 1
#define ST_NS 0
#define P3PF 0
#define P3PF_G 32
#define WQ_D 4
#define WQ_0 18
#define STCS 15
#define HSWAP 0
#define X_KB 24
#define X_D 8
#define G_KB 33
#define W_KB 42
#define W_D 4
#define WD_AT 8
#define OUT_P 0
#define WMODE 2
#define W_G0 22
#define W_PF 2
#define KVPF 1
struct Params {
  CUtensorMap xn, ckv, wq, wk, wv, kv, ctx_ld, ctx_st, wo, x, wd, wg, wu, out;
};

__global__ void __cluster_dims__(2, 1, 1) __launch_bounds__(384, 1)
fused_kernel(const __grid_constant__ Params p, const __nv_bfloat16* __restrict__ x, const __nv_bfloat16* __restrict__ wq,
             const __nv_bfloat16* __restrict__ w_r, const __nv_bfloat16* __restrict__ wgate, const __nv_bfloat16* __restrict__ wup,
             __nv_bfloat16* __restrict__ out) {
  extern __shared__ __align__(1024) uint8_t sp[];
  const uint32_t sb = s2u(sp);
  const uint32_t bar = sb + OFF_BAR;
  auto B = [&](int i) { return bar + 8 * i; };
  const int tid = threadIdx.x, warp = __shfl_sync(~0u, tid >> 5, 0), wg = warp >> 2, lane = tid & 31;
  const int cta = blockIdx.x, rank = cta & 1, cl = cta >> 1;
  const int mp = cl < 4 ? 1 : (cl < 36 ? (cl & 7) : (0x3207654 >> (4 * ((cl - 36) % 7))) & 7);
  const int gq = cl < 4 ? 4 + cl : (cl < 36 ? (cl - 4) >> 3 : 4 + (cl - 36) / 7);
  const int mt = 2 * mp + rank;
  const int ti = (gq & 3) * 2 + rank, hh = mp * 2 + (gq >> 2);
  const int rid = mt * 8 + gq;
  const int fid = mt * 7 + gq;
  const bool ffn = gq < 7;
  uint4* const xr = g_xr + rid * XR_SIZE;
  TL_INIT();
  TL(0, 0, tid == 128);
  if (tid == 32) TS(0);
  if (tid == 0) {
#pragma unroll 1
    for (int kb = 0; kb < PRE; kb++) {
      mbar_init(B(B_FULL1 + kb), 1);
      asm volatile("fence.mbarrier_init.release.cluster;" ::: "memory");
      mbar_expect(B(B_FULL1 + kb), P1_STAGE);
      tma_ld2(sb + kb * P1_STAGE, &p.ckv, B(B_FULL1 + kb), kb * 64, mt * 128);
      tma_ld3(sb + kb * P1_STAGE + 16384 + rank * 16384, &p.wk, B(B_FULL1 + kb), 0, kb * 64, (gq + HSWAP * 8) * 4 + rank * 2);
      tma_ld3(sb + kb * P1_STAGE + 32768 - rank * 16384, &p.wk, B(B_FULL1 + kb), 0, kb * 64, (gq + HSWAP * 8) * 4 + 2 - rank * 2);
    }
  }
  if (lane == 0) {
#pragma unroll 1
    for (int i = warp < PRE ? warp + 12 : warp; i < B_NUM; i += 12) {
      mbar_init(B(i), i >= B_EMPTY1 ? 16 : (i >= B_XE ? 8 : (i == B_LND ? 3 : (i >= B_WF ? 2 : 1))));
    }
    asm volatile("fence.mbarrier_init.release.cluster;" ::: "memory");
  }
  __syncwarp();
  cluster_arrive();
  if (tid == 32) {
    if (mt >= 2 * PRE) asm volatile("cp.async.bulk.prefetch.tensor.3d.L2.global [%0, {%1,%2,%3}];" ::"l"(&p.wk), "r"(0), "r"((mt >> 1) * 64), "r"((gq + HSWAP * 8) * 4 + (mt & 1) * 2) : "memory");
    if (gq >= PRE) asm volatile("cp.async.bulk.prefetch.tensor.2d.L2.global [%0, {%1,%2}];" ::"l"(&p.ckv), "r"(gq * 64), "r"(mt * 128) : "memory");
  } else if (tid == 64) {
    prefetch_tm(&p.wv); prefetch_tm(&p.wq); prefetch_tm(&p.xn);
  }
  __syncwarp();
  cluster_wait();
  if (wg == 0) {
    reg_dealloc<40>();
    if (warp == 0) {
      if (lane == 0) {
        int st = 0; uint32_t ph = 1;
#pragma unroll 1
        for (int t = 0; t < 6; t++) {
          const CUtensorMap* ma = t >= 4 ? &p.xn : &p.ckv;
          const CUtensorMap* mb = t >= 4 ? &p.wq : ((t & 1) ? &p.wv : &p.wk);
          const int nk = t >= 4 ? 16 : 8;
          const int row = (t < 4 ? mt : (t == 4 ? 15 - ti : ti)) * 128;
          const int col = t < 4 ? (gq + ((t >> 1) ^ HSWAP) * 8) * 4 + rank * 2 : (hh + rank * 16) * 2;
          if (t >= 4) mbar_wait(B(B_DEP + t - 4), 0);
#pragma unroll 1
          for (int kb = 0; kb < nk; kb++) {
            const uint32_t d = sb + st * P1_STAGE, fb = B(B_FULL1 + st);
            if (t > 0 || kb >= PRE) {
              mbar_wait(B(B_EMPTY1 + st), ph);
              mbar_expect(fb, P1_STAGE);
              tma_ld2(d, ma, fb, kb * 64, row);
              tma_ld3_mc(d + 16384 + rank * 16384, mb, fb, 0, kb * 64, col, 3);
            }
            if (t < 3 && t * 8 + kb >= LN_PF && t * 8 + kb < LN_PF + LN_PFN) l2_prefetch(x + (size_t)cta * 16 * DM + (t * 8 + kb - LN_PF) * (16 * DM / LN_PFN), 32768 / LN_PFN);
            if (t < 3 && t * 8 + kb == LN_LD) {
              mbar_expect(B(B_LN), 32768);
              asm volatile("cp.async.bulk.shared::cluster.global.mbarrier::complete_tx::bytes [%0], [%1], %2, [%3];" ::"r"(sb + OFF_LN),
                           "l"(x + (size_t)cta * 16 * DM), "r"(32768), "r"(B(B_LN)) : "memory");
            }
            if (t < 3 && kb == 0)
              asm volatile("cp.async.bulk.prefetch.tensor.3d.L2.global [%0, {%1,%2,%3}];" ::"l"((t & 1) ? &p.wk : &p.wv), "r"(0),
                           "r"(mp * 64), "r"((gq + (((t + 1) >> 1) ^ HSWAP) * 8) * 4 + rank * 2) : "memory");
            const int n = t * 8 + kb - WQ_0;
            if (WQ_D && t < 5 && n >= 0 && n < 4 * WQ_D && n % WQ_D == 0)
              asm volatile("cp.async.bulk.prefetch.tensor.3d.L2.global [%0, {%1,%2,%3}];" ::"l"(&p.wq), "r"(0),
                           "r"((n / WQ_D * 4 + (gq & 3)) * 64), "r"((hh + rank * 16) * 2) : "memory");
            if (++st == 4) { st = 0; ph ^= 1; }
          }
        }
        prefetch_tm(&p.kv); prefetch_tm(&p.ctx_ld); prefetch_tm(&p.wo); prefetch_tm(&p.wg); prefetch_tm(&p.wu);
        auto load_kv = [&](int g, int isv) {
          const int h2 = g >= 17, sx = g - 17 * h2, n1 = h2 ? ti + 1 : 16 - ti;
          const int row = (1 + isv) * SEQ + (sx < n1 ? sx : 16 - sx) * 128, col = (hh + 16 * h2) * 2;
          const uint32_t d = sb + (isv ? 2 + 2 * (g & 1) : (g & 1)) * SLOT, fb = B(B_KF + 2 * isv + (g & 1));
          if (g < 2) mbar_wait(B(B_EMPTY1 + (isv ? 1 + 2 * g : g)), 1);
          else mbar_wait(B(B_KE + 2 * isv + (g & 1)), ((g >> 1) & 1) ^ 1);
          mbar_expect(fb, SLOT);
          if (sx != (h2 ? (ti & 6) + 1 : 15 - (ti & 6))) {
            tma_ld3_mc(d + rank * 16384, &p.kv, fb, 0, row, col + rank, 3);
          } else {
            tma_ld3(d, &p.kv, fb, 0, row, col);
            tma_ld3(d + 16384, &p.kv, fb, 0, row, col + 1);
          }
          if (g + KVPF < 34) {
            const int g2 = g + KVPF, h3 = g2 >= 17, s3 = g2 - 17 * h3, n3 = h3 ? ti + 1 : 16 - ti;
            const int row3 = (1 + isv) * SEQ + (s3 < n3 ? s3 : 16 - s3) * 128, col3 = (hh + 16 * h3) * 2;
            asm volatile("cp.async.bulk.prefetch.tensor.3d.L2.global [%0, {%1,%2,%3}];" ::"l"(&p.kv), "r"(0), "r"(row3), "r"(col3 + rank) : "memory");
            if (s3 == (h3 ? (ti & 6) + 1 : 15 - (ti & 6)))
              asm volatile("cp.async.bulk.prefetch.tensor.3d.L2.global [%0, {%1,%2,%3}];" ::"l"(&p.kv), "r"(0), "r"(row3), "r"(col3 + 1 - rank) : "memory");
          }
        };
        int nw = ffn ? 0 : 12;
        auto load_w = [&]() {
          const int c = nw < 8 ? (nw >> 2) + (nw & 2) : nw >> 1;
          if (!(nw & 3)) mbar_expect(B(B_WF - (nw >> 3)), 32768);
          tma_ld2(sb + (c < 4 ? 3 + (c & 2) : 6) * SLOT + (c & 1) * 16384 + (nw & 1) * 8192, (nw & 1) ? &p.wg : &p.wu, B(B_WF - (nw >> 3)), fid * 32, c * 128);
          nw++;
        };
#pragma unroll 1
        for (int g = 0; g < 34; g++) {
          if (g == 0 || g == 17 - KVPF) mbar_wait(B(B_DEP + 2 + (g > 0)), 0);
          load_kv(g, 0);
          if (WMODE == 3 && g >= W_G0 - W_PF && g < W_G0 - W_PF + 12) {
            const int n = g - W_G0 + W_PF, c = n < 8 ? (n >> 2) + (n & 2) : n >> 1;
            l2_prefetch(((n & 1) ? wgate : wup) + (size_t)(c * 128 + cta) * FF, FF * 2);
          }
          if (g > 0) load_kv(g - 1, 1);
          if (P3PF && g == P3PF_G) {
            asm volatile("cp.async.bulk.prefetch.tensor.3d.L2.global [%0, {%1,%2,%3}];" ::"l"(&p.wo), "r"(0), "r"(mp * 64), "r"(gq * 2 + rank) : "memory");
            if (P3PF > 1 && mbar_test(B(B_DEP + 4), 0))
              asm volatile("cp.async.bulk.prefetch.tensor.2d.L2.global [%0, {%1,%2}];" ::"l"(&p.ctx_ld), "r"(gq * 64), "r"(mt * 128) : "memory");
          }
          if (WMODE == 1) { if (nw < 12 && mbar_test(B(B_QP + (nw >> 2)), 0)) { load_w(); load_w(); } }
          else if (g >= W_G0 && nw < 12 && mbar_test(B(B_QP + (nw >> 2)), 0)) load_w();
        }
        load_kv(33, 1);
#pragma unroll 1
        while (nw < 12) { mbar_wait(B(B_QP + (nw >> 2)), 0); load_w(); }
        prefetch_tm(&p.wd); prefetch_tm(&p.x); prefetch_tm(&p.out);
        st = 0; ph = 1;
#pragma unroll 1
        for (int kb = 0; kb < 64; kb++) {
          if ((kb & 31) == 0) mbar_wait(B(B_DEP + 4 + (kb >> 5)), 0);
          if (kb < 6) mbar_wait(B(B_KE + ((0xB3A210 >> (4 * kb)) & 15)), 0);
          else mbar_wait(B(B_EMPTY3 + st), ph);
          const uint32_t d = sb + OFF_R3 + st * SLOT, fb = B(B_FULL3 + st);
          mbar_expect(fb, SLOT);
          tma_ld2(d, &p.ctx_ld, fb, kb * 64, mt * 128);
          tma_ld3_mc(d + 16384 + rank * 8192, &p.wo, fb, 0, kb * 64, gq * 2 + rank, 3);
          if (++st == 6) { st = 0; ph ^= 1; }
          if (kb == SET_KB) mbar_arrive(B(B_SET));
          if (kb == 58) l2_prefetch(xr, XR_CAND * 16);
          if (kb == X_KB) { mbar_wait(B(B_XE), 0); mbar_expect(B(B_XF), 32768); tma_ld3(sb + 6 * SLOT, &p.x, B(B_XF), 0, mt * 128, gq * 2); }
          if (kb == X_KB + X_D) tma_ld3(sb + 6 * SLOT + 16384, &p.x, B(B_XF), 0, mt * 128 + 64, gq * 2);
          if (ffn && kb >= W_KB && kb < W_KB + 4 * W_D && (kb - W_KB) % W_D == 0) {
            const int n = (kb - W_KB) / W_D;
            if (n == 0) { mbar_wait(B(B_XE), 1); mbar_expect(B(B_WF2), 32768); }
            tma_ld2(sb + 6 * SLOT + n * 8192, (n & 1) ? &p.wg : &p.wu, B(B_WF2), fid * 32, (6 + (n >> 1)) * 128);
          }
        }
        if (ffn) {
#pragma unroll 1
          for (int j = 0; j < 2; j++) {
            mbar_wait(B(B_EMPTY3 + st), ph);
            mbar_expect(B(B_FULL3 + st), SLOT);
            tma_ld3(sb + OFF_R3 + st * SLOT, &p.wd, B(B_FULL3 + st), 0, fid * 32, 8 * j);
            st++;
          }
        }
      }
    } else {
      if (warp >= 2) {
#pragma unroll 1
        for (int i = tid - 64; i < XR_CAND; i += 64) xr[i] = make_uint4(~0u, ~0u, ~0u, ~0u);
        if (warp == 2) { __syncwarp(); if (lane == 0) mbar_arrive(B(B_WR)); }
      }
      if (warp == 3) {
        float ws = 0.f;
#pragma unroll
        for (int j = 0; j < 4; j++) {
          const uint4 q = __ldg(reinterpret_cast<const uint4*>(w_r) + j * 32 + lane);
          ws += bf_lo(q.x) + bf_hi(q.x) + bf_lo(q.y) + bf_hi(q.y) + bf_lo(q.z) + bf_hi(q.z) + bf_lo(q.w) + bf_hi(q.w);
        }
#pragma unroll
        for (int o = 16; o; o >>= 1) ws += __shfl_xor_sync(~0u, ws, o);
        uint2* tab = reinterpret_cast<uint2*>(sp + OFF_MISC + 512);
        tab[lane] = make_uint2(0x3F803F80u, 0x3F803F80u);
        tab[32 + lane] = __ldg(reinterpret_cast<const uint2*>(w_r + gq * 128) + lane);
        if (lane == 0) *reinterpret_cast<float*>(sp + OFF_MISC + 1024) = ws;
        __syncwarp();
        if (lane == 0) mbar_arrive(B(B_WR));
      }
      mbar_wait(B(B_LN), 0);
#pragma unroll 1
      for (int r = warp - 1; r < 16; r += 3) {
        uint4 v[4];
        float a0 = 0.f, a1 = 0.f, b0 = 0.f, b1 = 0.f;
#pragma unroll
        for (int j = 0; j < 4; j++) {
          v[j] = lds128(sb + OFF_LN + r * 2048 + lane * 16 + j * 512);
          const uint32_t u[4] = {v[j].x, v[j].y, v[j].z, v[j].w};
#pragma unroll
          for (int i = 0; i < 4; i++) { const float a = bf_lo(u[i]), b = bf_hi(u[i]); a0 += a; a1 += b; b0 = fmaf(a, a, b0); b1 = fmaf(b, b, b1); }
        }
        a0 += a1; b0 += b1;
#pragma unroll
        for (int o = 16; o; o >>= 1) { a0 += __shfl_xor_sync(~0u, a0, o); b0 += __shfl_xor_sync(~0u, b0, o); }
        const float mean = a0 * (1.f / DM);
        float mb, inv;
        ln_round(mean, fmaxf(fmaf(b0, 1.f / DM, -mean * mean), 0.f), mb, inv);
        inv *= AT_C;
        const uint32_t nm2 = pack_bf16(-mb, -mb);
        uint4* dst = reinterpret_cast<uint4*>(g_xn + (size_t)(cta * 16 + r) * DM) + lane;
#pragma unroll
        for (int j = 0; j < 4; j++)
          dst[j * 32] = make_uint4(ln_apply(v[j].x, nm2, inv), ln_apply(v[j].y, nm2, inv), ln_apply(v[j].z, nm2, inv), ln_apply(v[j].w, nm2, inv));
      }
      __syncwarp();
      if (lane == 0) {
        mbar_arrive(B(B_LND));
        fence_gpu();
        red_add(&g_cnt[C_LN + (cta >> 3)], 1);
      }
      TL(3, warp, lane == 0);
      if (warp == 3) {
        if (lane == 0) {
#pragma unroll 1
          for (int i = 0; i < 6; i++) {
            const int c = i < 2 ? C_LN + (i ? ti : 15 - ti) : (i < 4 ? C_QKV + (i - 2) * 8 + mp : C_CTX + (i - 4) * 16 + mt);
            spin_until_ge<true>(&g_cnt[c], i < 2 ? 24 : 16);
            fence_async_all();
            mbar_arrive(B(B_DEP + i));
            TL(3, 4 + i, true);
          }
        }
      } else if (warp == 1 && lane == 0) {
        mbar_wait(B(B_WR), 0);
#pragma unroll 1
        for (int i = 0; i < 6; i++) {
          const int c = i < 2 ? C_QKV + gq + (i ^ HSWAP) * 8 : C_CTX + (i >> 2) * 16 + ((i == 3 || i == 4) ? ti : 15 - ti);
          mbar_wait(B(B_PUB + i), 0);
          if (i >= 2 && i < 5) {
#pragma unroll 1
            for (int n = 0; n < 8 / ST_G; n++) {
              const int h = n / (4 / ST_G), a = n % (4 / ST_G) * ST_G;
              asm volatile("cp.async.bulk.tensor.3d.global.shared::cta.bulk_group [%0, {%2,%3,%4}], [%1];" ::"l"(&p.ctx_st),
                           "r"(sb + (i == 4 ? 6 * SLOT + h * 16384 : (3 + 2 * h) * SLOT + (i - 2) * 16384) + a * 4096),
                           "r"(0), "r"((i == 2 ? 15 - ti : ti) * 128 + h * 64), "r"((hh + (i >> 2) * 16) * 4 + a) : "memory");
              asm volatile("cp.async.bulk.commit_group;\ncp.async.bulk.wait_group.read 0;" ::: "memory");
              if (ST_NS) __nanosleep(ST_NS);
            }
            mbar_arrive(B(B_QP + i - 2));
            asm volatile("cp.async.bulk.wait_group 0;" ::: "memory");
          }
          fence_gpu();
          red_add(&g_cnt[c], 1);
          TS(1 + i);
        }
      }
      if (warp == 2) {
        mbar_wait(B(B_SET), 0);
#pragma unroll 1
        for (int i = XR_CAND + lane; i < XR_SIZE; i += 32) { xr[i] = make_uint4(~0u, ~0u, ~0u, ~0u); if (SET_NS) __nanosleep(SET_NS); }
        __syncwarp();
        if (lane == 0) { fence_gpu(); mbar_arrive(B(B_SET2)); }
        __syncwarp();
      }
      __syncwarp();
      if (warp == 3) {
        mbar_wait(B(B_OUT), 0);
        uint4 kv[2];
        poll_chunks(kv, g_xr + ((lane >> 1) * 8 + gq) * XR_SIZE + XR_KEY + (lane & 1) * 2, 1);
        const uint32_t a1 = max(kv[0].x, kv[0].z), a2 = max(min(kv[0].x, kv[0].z), max(kv[0].y, kv[0].w));
        const uint32_t b1 = max(kv[1].x, kv[1].z), b2 = max(min(kv[1].x, kv[1].z), max(kv[1].y, kv[1].w));
        const uint32_t k1 = max(a1, b1), k2 = max(min(a1, b1), max(a2, b2));
        const uint32_t m1 = __reduce_max_sync(~0u, k1);
        const uint32_t m2 = __reduce_max_sync(~0u, k1 == m1 ? k2 : k1);
        if (lane == 0) {
          *reinterpret_cast<uint2*>(sp + OFF_MISC) = make_uint2(m1, m2);
          mbar_arrive(B(B_OUT2));
        }
        const uint32_t key = (lane & 4) ? m2 : m1;
        const int tk = 0x7FFF - (key & 0x7FFF);
        const uint4* src = g_xr + ((tk >> 7) * 8 + (rid >> 4)) * XR_SIZE;
        poll_chunks(kv, src + XR_CAND + ((tk >> 4) & 7) * 64 + (((lane & 4) && !((m1 ^ m2) & 0x7FF0)) ? 16 : 0) + (rid & 12) + (lane & 3), 32);
        uint32_t u = key >> 16;
        u = (u & 0x8000u) ? (u & 0x7FFFu) : (~u & 0xFFFFu);
        const float rs = bf_round(__fdividef(1.f, 1.f + __expf(-__uint_as_float(u << 16))));
        if (lane < 8)
          *reinterpret_cast<uint4*>(sp + OFF_MISC + 128 + lane * 16) = make_uint4((rid & 2) ? ((rid & 1) ? kv[0].w : kv[0].z) : ((rid & 1) ? kv[0].y : kv[0].x),
              (rid & 2) ? ((rid & 1) ? kv[1].w : kv[1].z) : ((rid & 1) ? kv[1].y : kv[1].x), __float_as_uint(rs), 0);
        uint4 fl[1];
        poll_chunks(fl, src + XR_FLAG, 0);
        fence_gpu();
        __syncwarp();
        if (lane == 0) mbar_arrive(B(B_FIN));
      }
      if (tid == 32) {
        mbar_wait(B(B_OUT3), 0);
#pragma unroll 1
        for (int n = 0; n < 4; n++) {
          asm volatile("cp.async.bulk.tensor.2d.global.shared::cta.bulk_group [%0, {%2,%3}], [%1];" ::"l"(&p.out), "r"(sb + OFF_STG + n * 8192),
                       "r"(gq * 128 + (n & 1) * 64), "r"(mt * 128 + (n >> 1) * 64) : "memory");
          asm volatile("cp.async.bulk.commit_group;" ::: "memory");
          if (OUT_P) asm volatile("cp.async.bulk.wait_group.read 0;" ::: "memory");
        }
        asm volatile("cp.async.bulk.wait_group 0;" ::: "memory");
        fence_async_all();
        fence_gpu();
        __stcg(xr + XR_FLAG, make_uint4(0, 0, 0, 0));
        TL(2, 25, true);
      }
    }
    __syncwarp();
    cluster_arrive();
    cluster_wait();
    TL_DUMP();
    if (tid == 32) TS(8);
  } else {
    reg_alloc<232>();
    const int w = wg - 1, cw = warp - 4;
    int lane = lane_id();
    const uint32_t stg = sb + OFF_STG + w * 16384 + (cw & 3) * 2048;
    auto publish = [&](int i) { __syncwarp(); if (lane == 0) mbar_arrive(B(B_PUB + i)); };
    auto release2 = [&](uint32_t b) { if (lane < 2) mbar_arrive_cta(b, lane); };
    float R[128];
    float O[64], acc[64];
    uint32_t pk[64];
    uint32_t* const Q = pk;
    uint32_t P[32];
    auto packed = [&](int i) {
      const float* v = R + 16 * (i >> 1) + 2 * (i & 1);
      return make_uint4(pack_bf16(v[0], v[1]), pack_bf16(v[4], v[5]), pack_bf16(v[8], v[9]), pack_bf16(v[12], v[13]));
    };
    const uint32_t q_st = sb + (cw & 3) * 1024 + (lane >> 2) * 64 + (((lane & 3) ^ (lane >> 3)) << 4);
    const uint32_t q_ld = sb + (cw & 3) * 1024 + (lane & 15) * 64 + (((lane >> 4) ^ ((lane >> 1) & 3)) << 4);
    auto park = [&](uint32_t off, int i, uint4 v) {
      asm volatile("st.shared.v4.u32 [%0], {%1,%2,%3,%4};" ::"r"(q_st + off + (i >> 1) * 4096 + (i & 1) * 512), "r"(v.x), "r"(v.y), "r"(v.z), "r"(v.w) : "memory");
    };
    auto load_q = [&](uint32_t off, int k) { ldsm4(Q + 4 * k, ((q_ld + off) ^ ((k & 1) << 5)) + (k >> 1) * 4096); };
    {
      TL(0, 1, tid == 128);
      __nv_bfloat16* pdst = g_qkv;
      uint64_t pol_f, pol_n, pol;
      asm("createpolicy.fractional.L2::evict_first.b64 %0, 1.0;" : "=l"(pol_f));
      asm("createpolicy.fractional.L2::evict_normal.b64 %0, 1.0;" : "=l"(pol_n));
      auto put = [&](int i) {
        if (STCS == 15) __stcs(reinterpret_cast<uint4*>(pdst + (i & 1) * 8 * NQ + (i >> 1) * 32), make_uint4(pk[4 * i], pk[4 * i + 1], pk[4 * i + 2], pk[4 * i + 3]));
        else asm volatile("st.global.L1::no_allocate.L2::cache_hint.v4.u32 [%0], {%1,%2,%3,%4}, %5;" ::"l"(pdst + (i & 1) * 8 * NQ + (i >> 1) * 32), "r"(pk[4 * i]), "r"(pk[4 * i + 1]), "r"(pk[4 * i + 2]), "r"(pk[4 * i + 3]), "l"(pol) : "memory");
      };
      const uint64_t da0 = mk_desc(sb + w * 8192, 16, 1024, 1);
      const uint64_t db0 = mk_desc(sb + 16384, 8192, 1024, 1);
      int st = 0; uint32_t ph = 0;
      auto issue = [&](int accum) {
        mbar_wait_c(B(B_FULL1 + st), ph);
        const uint64_t da = desc_add(da0, st * P1_STAGE), db = desc_add(db0, st * P1_STAGE);
        wg_fence();
#pragma unroll
        for (int k = 0; k < 4; k++) mma_n256_ss<1>(R, desc_add(da, k * 32), desc_add(db, k * 2048), k == 0 ? accum : 1);
        wg_commit();
      };
#pragma unroll 1
      for (int t = 0; t < 6; t++) {
        const int nk = t >= 4 ? 16 : 8;
        const bool tr = t > 0 && t < 5;
        issue(0);
        TL(0, 2 + 2 * t + 16 * w, (tid & 127) == 0);
        if (tr) { put(0); put(1); }
        int prev = st;
        if (++st == 4) { st = 0; ph ^= 1; }
#pragma unroll 1
        for (int kb = 1; kb < nk; kb++) {
          if (kb == nk - 1 && w == 1) bar_sync(5, 256);
          issue(1);
          if (kb == nk - 1 && w == 0) bar_arrive(5, 256);
          if (tr) {
#pragma unroll
            for (int i = 1; i < 8; i++) if (kb == i) { put(2 * i); put(2 * i + 1); }
            if (kb == 7 && !(t & 1)) publish((t >> 1) - 1);
          } else if (t == 5 && kb == 2) {
            mbar_wait_c(B(B_LND), 0);
#pragma unroll
            for (int i = 0; i < 8; i++) park(6 * SLOT + w * 16384, i, make_uint4(pk[4 * i], pk[4 * i + 1], pk[4 * i + 2], pk[4 * i + 3]));
            __syncwarp();
#pragma unroll
            for (int k = 0; k < 8; k++) load_q(6 * SLOT + w * 16384, k);
            __syncwarp();
#pragma unroll
            for (int i = 0; i < 8; i++) park(6 * SLOT + w * 16384, i, make_uint4(pk[32 + 4 * i], pk[33 + 4 * i], pk[34 + 4 * i], pk[35 + 4 * i]));
          }
          wg_wait<1>();
          release2(B(B_EMPTY1 + prev));
          prev = st;
          if (++st == 4) { st = 0; ph ^= 1; }
        }
        if (t == 5 && w == 1) bar_arrive(6, 256);
        pdst = g_qkv + (size_t)(((t & 1) + 1) * SEQ + mt * 128 + cw * 16 + (lane >> 2)) * NQ + (gq + ((t >> 1) ^ HSWAP) * 8) * 256 + (lane & 3) * 8;
        pol = ((STCS >> t) & 1) ? pol_f : pol_n;
        wg_wait<0>();
        fence_regs<128>(R);
        release2(B(B_EMPTY1 + prev));
        TL(0, 3 + 2 * t + 16 * w, (tid & 127) == 0);
        if (t == 5) break;
#pragma unroll
        for (int i = 0; i < 16; i++) { const uint4 v = packed(i); pk[4 * i] = v.x; pk[4 * i + 1] = v.y; pk[4 * i + 2] = v.z; pk[4 * i + 3] = v.w; }
      }
    }
    auto issue3 = [&](int st, uint32_t ph, int accum) {
      mbar_wait_c(B(B_FULL3 + st), ph);
      const uint64_t da = mk_desc(sb + OFF_R3 + w * 8192 + st * SLOT, 16, 1024, 1), db = mk_desc(sb + OFF_R3 + 16384 + st * SLOT, 8192, 1024, 1);
      wg_fence();
#pragma unroll
      for (int k = 0; k < 4; k++) mma_n128_ss<1>(acc, desc_add(da, k * 32), desc_add(db, k * 2048), k == 0 ? accum : 1);
      wg_commit();
    };
    uint32_t wf[96];
    auto w_addr = [&](uint32_t off, int m) {
      const uint32_t w_ld = sb + ((lane >> 3) & 1) * 8192 + ((cw >> 1) * 32 + (lane & 7) + (lane >> 4) * 8) * 64 + ((((cw & 1) * 2) ^ ((lane >> 1) & 3)) << 4);
      return ((w_ld + off) ^ ((m & 1) << 4)) + (m >> 2) * 16384 + ((m >> 1) & 1) * 1024;
    };
    auto grab = [&](uint32_t* d, uint32_t off) {
#pragma unroll
      for (int m = 0; m < 8; m++)
        asm volatile("ldmatrix.sync.aligned.m8n8.x4.trans.shared.b16 {%0,%1,%2,%3}, [%4];"
                     : "=r"(d[4 * m]), "=r"(d[4 * m + 1]), "=r"(d[4 * m + 2]), "=r"(d[4 * m + 3]) : "r"(w_addr(off, m)) : "memory");
    };
    uint4 ob[8];
    {
      const int wrow = cw * 16;
      const uint64_t dk0 = mk_desc(sb, 16, 1024, 1);
      const uint64_t dv0 = mk_desc(sb + 2 * SLOT, 16384, 1024, 1);
      const uint32_t pin = sb + OFF_MISC + 1028;
      float l0 = 0.f, l1 = 0.f;
      float inv[2] = {0.f, 0.f};
      int g = 0, t = 0;
      uint32_t fail = 0;
      auto piece = [&](int tt) { return (uint32_t)(tt == 3 ? 6 * SLOT + w * 16384 : (3 + 2 * w) * SLOT + (tt - 1) * 16384); };
      uint32_t par = 0;
      auto issue_s = [&](float* S, auto between) {
        const uint64_t dk = desc_add(dk0, par * 16);
        mma_n128_rs0(S, Q, dk);
#pragma unroll
        for (int k = 1; k < 8; k++) {
          if (k == SH_K) between();
          mma_n128_rs<0>(S, Q + 4 * k, desc_add(dk, (k >> 2) * 16384 + (k & 3) * 32), 1);
        }
        wg_commit();
      };
      auto issue_pv = [&](bool half, int accum) {
        const uint64_t dv = desc_add(dv0, ((g - 1) & 1) * 2 * SLOT);
        wg_fence();
#pragma unroll
        for (int k = 0; k < 4; k++) mma_n128_rs<1>(O, P + 4 * k, desc_add(dv, k * 2048), k == 0 ? accum : 1);
        wg_commit();
        if (UNLIKELY(half)) {
          wg_fence();
          wg_commit();
        } else {
          wg_fence();
#pragma unroll
          for (int k = 4; k < 8; k++) mma_n128_rs<1>(O, P + 4 * k, desc_add(dv, k * 2048), 1);
          wg_commit();
        }
        bar_arrive(2 - w, 256);
        wg_wait<2>();
        fence_regs<32>(Q);
      };
      uint32_t rel;
      asm("mapa.shared::cluster.u32 %0, %1, %2;" : "=r"(rel) : "r"(B(B_KE + 1)), "r"(lane & 1));
      auto release_k = [&]() {
        if (lane < 2) asm volatile("mbarrier.arrive.shared::cluster.b64 _, [%0];" ::"r"(rel) : "memory");
        rel ^= 8;
      };
      auto pv_done = [&]() {
        sched_fence(q_st);
        wg_wait<0>();
        fence_regs<64>(O); fence_regs<32>(P);
        if (lane < 2) asm volatile("mbarrier.arrive.shared::cluster.b64 _, [%0+16];" ::"r"(rel) : "memory");
      };
      auto row_inv = [&]() {
        l0 += __shfl_xor_sync(~0u, l0, 1); l1 += __shfl_xor_sync(~0u, l1, 1);
        l0 += __shfl_xor_sync(~0u, l0, 2); l1 += __shfl_xor_sync(~0u, l1, 2);
        const bool ok = __all_sync(~0u, l0 >= AT_LO && l0 <= AT_HI && l1 >= AT_LO && l1 <= AT_HI) != 0;
        asm("rcp.approx.ftz.f32 %0, %1;" : "=f"(inv[0]) : "f"(l0));
        asm("rcp.approx.ftz.f32 %0, %1;" : "=f"(inv[1]) : "f"(l1));
        l0 = l1 = 0.f;
        return ok;
      };
      auto scaled = [&](int i) {
        const float* o = O + 16 * (i >> 1) + 2 * (i & 1);
        const float c = inv[i & 1];
        return make_uint4(pack_bf16(o[0] * c, o[1] * c), pack_bf16(o[4] * c, o[5] * c), pack_bf16(o[8] * c, o[9] * c), pack_bf16(o[12] * c, o[13] * c));
      };
      auto hand_over = [&](int tt) { asm volatile("fence.proxy.async.shared::cta;" ::: "memory"); publish(2 + tt); };
      {
        if (w == 0) { bar_arrive(7, 256); bar_sync(6, 256); } else { bar_arrive(1, 256); bar_sync(7, 256); }
#pragma unroll
        for (int i = 0; i < 8; i++) park(piece(1), i, packed(i));
        mbar_wait_c(B(B_KF), 0);
        bar_sync(1 + w, 256);
        float S[64];
        wg_fence();
        issue_s(S, []() {});
        bar_arrive(2 - w, 256);
        TL(1, 0, tid == 128);
#pragma unroll
        for (int i = 0; i < 8; i++) park(piece(2), i, packed(8 + i));
        wg_wait<0>();
        fence_regs<64>(S);
        release2(B(B_KE));
        TL(1, 1, tid == 128);
        at_exp<0, 16>(S);
        sched_fence(q_st);
        at_exp<16, 32>(S); at_fin<0, 16>(S, P, l0, l1);
        sched_fence(q_st);
        at_exp<32, 48>(S); at_fin<16, 32>(S, P, l0, l1);
        mbar_wait_f(B(B_KF + 1), 0);
        sched_fence(q_st);
        at_exp<48, 64>(S); at_fin<32, 64>(S, P, l0, l1);
        TL(1, 2, tid == 128);
      }
      const uint64_t m_first = 1ull | (1ull << (16 - ti)) | (1ull << 17) | (1ull << (18 + ti));
      const uint64_t m_diag = (3ull << (15 - ti)) | (3ull << (17 + ti));
      const uint64_t m_last = m_first >> 1;
      enum { F_FIRST = 1, F_DIAG = 2, F_LAST = 4, F_PFIRST = 8, F_PHALF = 16, F_FLUSH = 32, F_PUB = 64, F_STOP = 128, F_END = 256 };
      auto kind = [&](int gn) {
        const uint32_t a = (uint32_t)((m_first << 2) >> gn), d = (uint32_t)((m_diag << 1) >> gn);
        return ((a >> 2) & 1) * F_FIRST | ((d >> 1) & 1) * F_DIAG | ((uint32_t)(m_last >> gn) & 1) * F_LAST | ((a >> 1) & 1) * (gn > 1 ? F_PFIRST | F_FLUSH : F_PFIRST) |
               (w == 0 ? (d & 1) * F_PHALF | ((d >> 1) & 1) * F_STOP : 0) | (gn > 2 ? (a & 1) * F_PUB : 0) | (gn == 34 ? F_STOP : 0) | (gn == 33 ? F_END : 0);
      };
      const uint32_t kinds = pinned(kind(lane + 3));
      uint32_t f = F_PFIRST, fn;
      int tp = 0;
      bool vok, early = false;
      auto shadow1 = [&]() {
        vok = mbar_try(B(B_VF + ((g - 1) & 1)), ((g - 1) >> 1) & 1);
        at_sum(P, f & F_PHALF, l0, l1);
        fn = __shfl_sync(~0u, kinds, max(g - 2, 0));
      };
      auto shadow2 = [&]() {
        if (UNLIKELY(!vok || (f & (F_PUB | F_FLUSH | F_FIRST)))) {
          if (f & F_PUB) { if (!((fail >> tp) & 1)) hand_over(tp); tp++; }
          if (f & F_FLUSH) {
#pragma unroll
            for (int i = 0; i < 8; i++) park(piece(t), i, scaled(i));
          }
          if (f & F_FIRST) { if (!row_inv()) fail |= 1u << t; t++; }
          if (!vok) mbar_wait_c(B(B_VF + ((g - 1) & 1)), ((g - 1) >> 1) & 1);
        }
      };
      auto exp_q = [&](float* S, auto kc, auto nc) {
        constexpr int k = decltype(kc)::value, n = decltype(nc)::value;
        asm volatile("{\n.reg .pred p;\nsetp.ne.b32 p, %5, 0;\n@p ldmatrix.sync.aligned.m8n8.x4.shared.b16 {%0,%1,%2,%3}, [%4];\n}"
                     : "+r"(Q[4 * k]), "+r"(Q[4 * k + 1]), "+r"(Q[4 * k + 2]), "+r"(Q[4 * k + 3])
                     : "r"(((q_ld + piece(t + 1)) ^ ((k & 1) << 5)) + (k >> 1) * 4096), "r"(f & F_LAST) : "memory");
        at_exp<n * k, n * k + n>(S);
      };
      g = 1; par = SLOT / 16;
#pragma unroll 1
      for (;;) {
        {
          TC(w, g, 6);
          bar_sync(1 + w, 256);
          fence_regs<32>(Q);
          float S[64];
          wg_fence();
          issue_s(S, [&]() { sched_fence(q_st); TCF(w, g); shadow1(); sched_fence(q_st); });
          TC(w, g, 7);
          shadow2();
          fence_regs<64>(O); fence_regs<32>(P);
          issue_pv(f & F_PHALF, ~f & F_PFIRST);
          fence_regs<64>(S);
          TC(w, g, 0);
          release_k();
          at_exp<0, 8>(S);
          if (UNLIKELY(f & (F_DIAG | F_LAST | F_END))) {
            early = mbar_test(B(ffn ? B_WF : B_QP + 1), 0) && (f & F_END);
            at_mask(S + 32, (f & F_DIAG) ? wrow - 64 : 64, lane);
            unroll8([&](auto kc) {
              constexpr int m = decltype(kc)::value;
              asm volatile("{\n.reg .pred p;\nsetp.ne.b32 p, %5, 0;\n@p ldmatrix.sync.aligned.m8n8.x4.trans.shared.b16 {%0,%1,%2,%3}, [%4];\n}"
                           : "+r"(Q[4 * m]), "+r"(Q[4 * m + 1]), "+r"(Q[4 * m + 2]), "+r"(Q[4 * m + 3])
                           : "r"(w_addr(3 * SLOT, m)), "r"((int)early) : "memory");
              exp_q(S + 8, kc, std::integral_constant<int, AT_R1 / 8 - 1>{});
            });
          } else {
            at_exp<8, AT_R1>(S);
          }
          TC(w, g, 1);
          if (AT_R1 != AT_R2) {
            sched_fence(q_st);
            wg_wait<1>();
            fence_regs<16>(P);
            at_exp<AT_R1, AT_R2>(S); at_fin<0, AT_R1>(S, P, l0, l1);
          }
          TC(w, g, 2);
          pv_done();
          g = pinned(g + 1); par = pinned(par ^ (SLOT / 16)); f = fn;
          const bool kok = mbar_try(B(B_KF + (g & 1)), g < 34 ? (g >> 1) & 1 : 0);
          at_exp<AT_R2, 64>(S); at_fin<AT_R1 != AT_R2 ? AT_R1 : 0, 64>(S, P, l0, l1);
          TC(w, g, 5);
          if (!TCLK) TL(1, 1 + g, tid == 128);
          if (kok && !(f & F_STOP)) continue;
          if (g == 34) break;
          mbar_wait_c(B(B_KF + (g & 1)), (g >> 1) & 1);
        }
#pragma unroll 1
        while (f & F_STOP) {
          TC(w, g, 6);
          TCF(w, g);
          shadow1();
          shadow2();
          bar_sync(1, 256);
          fence_regs<64>(O); fence_regs<32>(Q); fence_regs<32>(P);
          float S[32];
          const uint64_t dk = desc_add(dk0, par * 16);
          wg_fence();
          mma_n64_rs0(S, Q, dk);
#pragma unroll
          for (int k = 1; k < 8; k++) mma_n64_rs(S, Q + 4 * k, desc_add(dk, (k >> 2) * 16384 + (k & 3) * 32), 1);
          wg_commit();
          TC(w, g, 7);
          issue_pv(f & F_PHALF, ~f & F_PFIRST);
          fence_regs<32>(S);
          TC(w, g, 0);
          release_k();
          at_mask(S, wrow, lane);
          unroll8([&](auto kc) { exp_q(S, kc, std::integral_constant<int, 4>{}); });
          pv_done();
          g++; par ^= SLOT / 16; f = fn;
          at_fin<0, 32>(S, P, l0, l1);
          if (!TCLK) TL(1, 1 + g, tid == 128);
          mbar_wait_c(B(B_KF + (g & 1)), (g >> 1) & 1);
        }
      }
      if (early) { pin_order(__uint_as_float(Q[28] & Q[24]), pin); __syncwarp(); release2(B(B_WE)); }
      mbar_wait_c(B(B_VF + 1), 0);
      bar_sync(1 + w, 256);
      fence_regs<64>(O); fence_regs<32>(P);
      wg_fence();
#pragma unroll
      for (int k = 0; k < 8; k++) mma_n128_rs<1>(O, P + 4 * k, desc_add(dv0, 2 * SLOT + k * 2048), 1);
      wg_commit();
      if (w == 0) bar_arrive(2, 256);
      sched_fence(q_st);
      at_sum(P, false, l0, l1);
      if (!row_inv()) fail |= 8;
      if (UNLIKELY(fail != 0)) {
        wg_wait<0>();
        fence_regs<64>(O); fence_regs<32>(P);
#pragma unroll 1
        for (int tt = 0; tt < 4; tt++) {
          if (tt < 3 && !((fail >> tt) & 1)) continue;
          slow_tile(O, P, l0, l1, wq, (((tt + 1) & 2) ? ti : 15 - ti) * 128 + wrow, hh + (tt & 2) * 8, lane, q_st);
          row_inv();
          if (tt < 3) {
#pragma unroll
            for (int i = 0; i < 8; i++) park(piece(tt + 1), i, scaled(i));
            hand_over(tt);
          }
        }
      }
      TL(3, 12 + 16 * w, (tid & 127) == 0);
      issue3(0, 0, 0);
      TL(3, 13 + 16 * w, (tid & 127) == 0);
      if (UNLIKELY(!early)) {
        mbar_wait_c(B(ffn ? B_WF : B_QP + 1), 0);
        grab(Q, 3 * SLOT);
        pin_order(__uint_as_float(Q[28] & Q[24]), pin);
        __syncwarp();
        release2(B(B_WE));
      }
      wg_wait<1>();
      fence_regs<64>(O); fence_regs<32>(P);
      release2(B(B_VE + 1));
      grab(wf, 5 * SLOT);
      TL(3, 14 + 16 * w, (tid & 127) == 0);
      issue3(1, 0, 1);
      pin_order(__uint_as_float(wf[28] & wf[24]), pin);
      __syncwarp();
      release2(B(B_WE + 1));
      wg_wait<1>();
      release2(B(B_EMPTY3));
      TL(3, 15 + 16 * w, (tid & 127) == 0);
      issue3(2, 0, 1);
      sched_fence(q_st);
#pragma unroll
      for (int i = 0; i < 8; i++) ob[i] = scaled(i);
      sched_fence(q_st);
      wg_wait<1>();
      release2(B(B_EMPTY3 + 1));
      TL(1, 36, tid == 128);
      TL(3, 16 + 16 * w, (tid & 127) == 0);
    }
    uint32_t hp[32];
    lane = lane_id();
    {
      int st = 3, prev = 2; uint32_t ph = 0;
      __nv_bfloat16* dst = g_qkv + (size_t)((15 - ti) * 128 + cw * 16 + (lane >> 2)) * NQ + (hh + 16) * 128 + (lane & 3) * 8;
      auto kblock = [&](auto between) {
        issue3(st, ph, 1);
        between();
        wg_wait<1>();
        release2(B(B_EMPTY3 + prev));
        prev = st;
        if (++st == 6) { st = 0; ph ^= 1; }
      };
#pragma unroll 1
      for (int kb = 3; kb < 11; kb++)
        kblock([&]() {
#pragma unroll
          for (int i = 0; i < 8; i++) if (kb == i + 3) *reinterpret_cast<uint4*>(dst + (i & 1) * 8 * NQ + (i >> 1) * 32) = ob[i];
          TL(3, 14 + kb + 16 * w, (tid & 127) == 0);
          if (kb == 8) TL(2, 2, tid == 128);
        });
      publish(5);
      kblock([&]() { mbar_wait_c(B(ffn ? B_WF2 : B_QP + 2), 0); grab(wf + 32, 6 * SLOT); });
#pragma unroll 1
      for (int kb = 12; kb < G_KB; kb++) {
        kblock([&]() { if ((kb & 7) == 0) TL(2, 1 + (kb >> 3), tid == 128); });
        if (kb == 13 && lane == 0) mbar_arrive(B(B_XE));
      }
      kblock([&]() {
        mbar_wait_c(B(B_XF), 0);
#pragma unroll
        for (int i = 0; i < 8; i++)
          ldsm4(hp + 4 * i, sb + 6 * SLOT + w * 16384 + ((cw & 3) * 16 + (lane & 15)) * 128 + (i >> 2) * 8192 + ((((i & 3) * 2 + (lane >> 4)) ^ (lane & 7)) << 4));
      });
#pragma unroll 1
      for (int kb = G_KB + 1; kb < 64; kb++) {
        kblock([&]() { if ((kb & 7) == 0) TL(2, 1 + (kb >> 3), tid == 128); if (kb >= 48) TL(0, kb - 16, tid == 128); });
        if (kb == G_KB + 2 && lane == 0) mbar_arrive(B(B_XE));
      }
    }
    lane = lane_id();
    const int r0 = lane >> 2, q4 = lane & 3, ct = cw * 32 + lane;
    uint32_t tb[16];
    mbar_wait_c(B(B_WR), 0);
#pragma unroll
    for (int i = 0; i < 4; i++) ldsm4(tb + 4 * i, sb + OFF_MISC + 512 + (lane & 1) * 256 + (lane >> 3) * 16 + i * 64);
    mbar_wait_c(B(B_SET2), 0);
    float4* const psd = reinterpret_cast<float4*>(xr + XR_PS + cw * 16 + r0);
    const uint4* const pss = g_xr + (mt * 8 + (ct & 1) * 4) * XR_SIZE + XR_PS + (ct >> 1);
    sched_fence(stg);
    wg_wait<0>();
    fence_regs<64>(acc);
    TL(2, 10, tid == 128);
    {
      float d[2][4] = {}, qa[2][4] = {}, qb[2][4] = {};
#pragma unroll
      for (int j = 0; j < 16; j++) {
        hp[2 * j] = hadd2_bf(hp[2 * j], pack_bf16(acc[4 * j], acc[4 * j + 1]));
        hp[2 * j + 1] = hadd2_bf(hp[2 * j + 1], pack_bf16(acc[4 * j + 2], acc[4 * j + 3]));
        if (j & 1) {
          mma16816(d[(j >> 1) & 1], hp[2 * j - 2], hp[2 * j - 1], hp[2 * j], hp[2 * j + 1], tb[j - 1], tb[j]);
          mma16816(qa[(j >> 1) & 1], hp[2 * j - 2], hp[2 * j - 1], hp[2 * j], hp[2 * j + 1], hp[2 * j - 2], hp[2 * j]);
          mma16816(qb[(j >> 1) & 1], hp[2 * j - 2], hp[2 * j - 1], hp[2 * j], hp[2 * j + 1], hp[2 * j - 1], hp[2 * j + 1]);
        }
      }
      if (q4 == (r0 >> 1)) {
        __stcg(psd, make_float4(d[0][0] + d[1][0], (r0 & 1) ? qa[0][1] + qa[1][1] : qa[0][0] + qa[1][0], d[0][1] + d[1][1], 0.f));
        __stcg(psd + 8, make_float4(d[0][2] + d[1][2], (r0 & 1) ? qb[0][3] + qb[1][3] : qb[0][2] + qb[1][2], d[0][3] + d[1][3], 0.f));
      }
    }
    TL(2, 11, tid == 128);
    mbar_wait_c(B(B_EMPTY3), 0);
    stage_store_128(stg, lane, hp);
    if (ffn) mbar_wait_c(B(B_WF2), 1);
    grab(wf + 64, 6 * SLOT);
    const float wsum = *reinterpret_cast<const float*>(sp + OFF_MISC + 1024);
    __syncwarp();
    {
      uint4 ps[4];
      poll_chunks(ps, pss, XR_SIZE);
      TL(2, 12, tid == 128);
      auto F = [](uint32_t u) { return __uint_as_float(u); };
      float s1 = (F(ps[0].x) + F(ps[1].x)) + (F(ps[2].x) + F(ps[3].x)), s2 = (F(ps[0].y) + F(ps[1].y)) + (F(ps[2].y) + F(ps[3].y));
      float s3 = (F(ps[0].z) + F(ps[1].z)) + (F(ps[2].z) + F(ps[3].z));
      __syncwarp();
      s1 += __shfl_xor_sync(~0u, s1, 1); s2 += __shfl_xor_sync(~0u, s2, 1); s3 += __shfl_xor_sync(~0u, s3, 1);
      const float mean = s1 * (1.f / DM);
      float mb, inv;
      ln_round(mean, fmaxf(fmaf(s2, 1.f / DM, -mean * mean), 0.f), mb, inv);
      uint32_t u = pack_bf16((s3 - mb * wsum) * inv, 0.f);
      if (u == 0x8000u) u = 0;
      u = (u & 0x8000u) ? (~u & 0xFFFFu) : (u | 0x8000u);
      const uint32_t key = (u << 16) | (0x7FFFu - (mt * 128 + (ct >> 1)));
      const uint32_t nm2 = pack_bf16(-mb, -mb);
      const uint32_t c1 = __reduce_max_sync(~0u, key);
      const uint32_t c2 = __reduce_max_sync(~0u, key == c1 ? 0u : key);
      if (lane == 0) {
        __stcg(reinterpret_cast<uint2*>(xr + XR_KEY) + cw, make_uint2(c1, c2));
        mbar_arrive(B(B_OUT));
      }
      TL(2, 13, tid == 128);
      const int row = (0x7FFF - (((lane >> 4) ? c2 : c1) & 0x7FFF)) & 15;
      const uint32_t rn = __shfl_sync(~0u, nm2, row * 2);
      const float ri = __shfl_sync(~0u, inv, row * 2);
      uint32_t v[4];
#pragma unroll
      for (int i = 0; i < 4; i++)
        asm volatile("ld.shared.u32 %0, [%1];" : "=r"(v[i]) : "r"(stg + ((lane >> 3) & 1) * 8192 + row * 128 + ((((lane & 4) + i) ^ (row & 7)) << 4) + q4 * 4) : "memory");
      __stcg(xr + XR_CAND + cw * 64 + 32 + lane, make_uint4(ln_apply(v[0], rn, ri), ln_apply(v[1], rn, ri), ln_apply(v[2], rn, ri), ln_apply(v[3], rn, ri)));
      __stcg(xr + XR_CAND + cw * 64 + lane, make_uint4(v[0], v[1], v[2], v[3]));
      sched_fence(stg);
      const uint32_t na = __shfl_sync(~0u, nm2, r0 * 2), nb = __shfl_sync(~0u, nm2, r0 * 2 + 16);
      const float ia = __shfl_sync(~0u, inv, r0 * 2), ib = __shfl_sync(~0u, inv, r0 * 2 + 16);
#pragma unroll
      for (int i = 0; i < 32; i++) hp[i] = hadd2_bf(hp[i], ln_apply(hp[i], (i & 1) ? nb : na, (i & 1) ? ib : ia));
      __syncwarp();
      stage_store_128(stg, lane, hp);
      asm volatile("fence.proxy.async.shared::cta;" ::: "memory");
      publish(B_OUT3 - B_PUB);
    }
    uint32_t wd[16][4];
    sched_fence(stg);
    if (ffn) mbar_wait_c(B(B_FULL3 + 64 % 6 + w), (64 / 6) & 1);
    auto load_wd = [&](int h) {
#pragma unroll
      for (int i = h; i < 16; i += 2)
        asm volatile("ldmatrix.sync.aligned.m8n8.x4.trans.shared.b16 {%0,%1,%2,%3}, [%4];"
                     : "=r"(wd[i][0]), "=r"(wd[i][1]), "=r"(wd[i][2]), "=r"(wd[i][3])
                     : "r"(sb + OFF_R3 + (64 % 6 + w) * SLOT + (2 * (cw & 3) + (i >> 3)) * 4096 + (h * 16 + (lane & 7) + (lane >> 4) * 8) * 128 +
                           (((2 * ((i >> 1) & 3) + ((lane >> 3) & 1)) ^ (lane & 7)) << 4)) : "memory");
    };
    load_wd(0);
    __syncwarp();
    cluster_arrive();
    TL(2, 22, tid == 128);
    mbar_wait_c(B(B_OUT2), 0);
    const uint2 top = *reinterpret_cast<const uint2*>(sp + OFF_MISC);
    TL(2, 14, tid == 128);
    const int t0 = 0x7FFF - (top.x & 0x7FFF), t1 = 0x7FFF - (top.y & 0x7FFF);
    auto cand = [&](int second) {
      const int tk = second ? t1 : t0;
      return g_xr + (tk >> 7) * 8 * XR_SIZE + XR_CAND + ((tk >> 4) & 7) * 64 + ((second && (t0 >> 4) == (t1 >> 4)) ? 16 : 0);
    };
    if (ffn) {
      uint4 xb[2];
      poll_chunks(xb, cand(r0 & 1) + (r0 >> 1) * XR_SIZE + 32 + (cw >> 1) * 4 + q4, 4 * XR_SIZE);
      __syncwarp();
      TL(2, 15, tid == 128);
      float d[8][4] = {};
#pragma unroll
      for (int n = 0; n < 32; n++) {
        if (n == WD_AT) { sched_fence(stg); load_wd(1); }
        const int s = (n >> 4) * 4 + ((n >> 1) & 3), m = ((n >> 3) & 1) * 2 + (n & 1);
        const uint32_t* a = (s < 2 ? Q + 16 * s : wf + 16 * (s < 2 ? 0 : s - 2)) + 4 * m;
        mma16816(d[n & 7], a[0], a[1], a[2], a[3], (m & 2) ? xb[s >> 2].z : xb[s >> 2].x, (m & 2) ? xb[s >> 2].w : xb[s >> 2].y);
      }
      float v[8];
#pragma unroll
      for (int i = 0; i < 8; i++) {
        const float lo = (q4 & 1) ? d[2 + (i >> 2)][i & 3] : d[i >> 2][i & 3], hi = (q4 & 1) ? d[6 + (i >> 2)][i & 3] : d[4 + (i >> 2)][i & 3];
        v[i] = (q4 & 2) ? hi : lo;
      }
#pragma unroll
      for (int i = 0; i < 4; i++) v[i] = ((q4 & 2) ? v[i + 4] : v[i]) + __shfl_xor_sync(~0u, (q4 & 2) ? v[i] : v[i + 4], 2);
#pragma unroll
      for (int i = 0; i < 2; i++) v[i] = ((q4 & 1) ? v[i + 2] : v[i]) + __shfl_xor_sync(~0u, (q4 & 1) ? v[i] : v[i + 2], 1);
      float4* red = reinterpret_cast<float4*>(sp + SL_SCR * SLOT);
      reinterpret_cast<float2*>(red + cw * 16 + (q4 >> 1) * 8 + r0)[q4 & 1] = make_float2(v[0], v[1]);
      bar_sync(3, 256);
      TL(2, 16, tid == 128);
      const float4 z0 = red[lane], z1 = red[32 + lane], z2 = red[64 + lane], z3 = red[96 + lane];
      const uint32_t ub = pack_bf16((z0.x + z1.x) + (z2.x + z3.x), (z0.y + z1.y) + (z2.y + z3.y));
      const uint32_t gb = pack_bf16((z0.z + z1.z) + (z2.z + z3.z), (z0.w + z1.w) + (z2.w + z3.w));
      const float g0 = bf_lo(gb), g1 = bf_hi(gb);
      const uint32_t sg = pack_bf16(__fdividef(g0, 1.f + __expf(-g0)), __fdividef(g1, 1.f + __expf(-g1)));
      const uint32_t act = pack_bf16(bf_lo(sg) * bf_lo(ub), bf_hi(sg) * bf_hi(ub));
      const uint32_t pr = __byte_perm(act, __shfl_xor_sync(~0u, act, 1), (lane & 1) ? 0x3276 : 0x5410);
      const int src = q4 * 2 + (r0 & 1);
      const uint32_t a0 = __shfl_sync(~0u, pr, src), a1 = __shfl_sync(~0u, pr, src + 8), a2 = __shfl_sync(~0u, pr, src + 16), a3 = __shfl_sync(~0u, pr, src + 24);
      TL(2, 17, tid == 128);
      float y[8][4] = {};
#pragma unroll
      for (int i = 0; i < 8; i++) mma16816(y[i], wd[2 * i][0], wd[2 * i][1], wd[2 * i][2], wd[2 * i][3], a0, a1);
#pragma unroll
      for (int i = 0; i < 8; i++) mma16816(y[i], wd[2 * i + 1][0], wd[2 * i + 1][1], wd[2 * i + 1][2], wd[2 * i + 1][3], a2, a3);
      float2* yd = reinterpret_cast<float2*>(g_xr + (cw * 16 + 2 * q4) * XR_SIZE + XR_Y + fid * 4) + r0;
#pragma unroll
      for (int j = 0; j < 2; j++) {
        float v[4];
#pragma unroll
        for (int e = 0; e < 4; e++) {
          const float lo = (q4 & 1) ? y[4 * j + 1][e] : y[4 * j][e], hi = (q4 & 1) ? y[4 * j + 3][e] : y[4 * j + 2][e];
          v[e] = (q4 & 2) ? hi : lo;
        }
        __stcg(yd + j * 16 * XR_SIZE, make_float2(v[0], v[1]));
        __stcg(yd + j * 16 * XR_SIZE + 2 * XR_SIZE, make_float2(v[2], v[3]));
      }
    }
    TL(2, 18, tid == 128);
    if (rid == 127 && ct < C_NUM) g_cnt[ct] = 0;
    if (cw < 2) {
      const int tok = (lane >> 1) & 1, pair = cw * 2 + (lane & 1);
      uint4 z[7];
      poll_chunks(z, xr + XR_Y + (lane >> 1) * 4 + pair, 64);
      __syncwarp();
      TL(2, 19, tid == 128);
      mbar_wait_c(B(B_FIN), 0);
      const uint4 op = lds128(sb + OFF_MISC + 128 + (tok * 4 + pair) * 16);
      auto F = [](uint32_t u) { return __uint_as_float(u); };
      const float v0 = ((F(z[0].x) + F(z[1].x)) + (F(z[2].x) + F(z[3].x))) + ((F(z[4].x) + F(z[5].x)) + F(z[6].x));
      const float v1 = ((F(z[0].y) + F(z[1].y)) + (F(z[2].y) + F(z[3].y))) + ((F(z[4].y) + F(z[5].y)) + F(z[6].y));
      const float v2 = ((F(z[0].z) + F(z[1].z)) + (F(z[2].z) + F(z[3].z))) + ((F(z[4].z) + F(z[5].z)) + F(z[6].z));
      const float v3 = ((F(z[0].w) + F(z[1].w)) + (F(z[2].w) + F(z[3].w))) + ((F(z[4].w) + F(z[5].w)) + F(z[6].w));
      float ya = (tok ? v1 : v0) + __shfl_xor_sync(~0u, tok ? v0 : v1, 2), yb = (tok ? v3 : v2) + __shfl_xor_sync(~0u, tok ? v2 : v3, 2);
#pragma unroll
      for (int o = 4; o < 32; o <<= 1) { ya += __shfl_xor_sync(~0u, ya, o); yb += __shfl_xor_sync(~0u, yb, o); }
      const uint32_t yp = pack_bf16(ya, yb);
      if (lane < 4) reinterpret_cast<uint32_t*>(out + (size_t)(tok ? t1 : t0) * DM)[rid * 4 + pair] = hadd2_bf(op.x, hadd2_bf(op.y, pack_bf16(bf_lo(yp) * F(op.z), bf_hi(yp) * F(op.z))));
      TL(2, 21, tid == 128);
    }
    TL(2, 20, tid == 128);
    __syncwarp();
    cluster_wait();
    TL_DUMP();
  }
}

typedef CUresult (*EncodeFn)(CUtensorMap*, CUtensorMapDataType, cuuint32_t, void*, const cuuint64_t*, const cuuint64_t*, const cuuint32_t*,
                             const cuuint32_t*, CUtensorMapInterleave, CUtensorMapSwizzle, CUtensorMapL2promotion, CUtensorMapFloatOOBfill);
EncodeFn g_enc = nullptr;

void map2(CUtensorMap* m, const void* ptr, uint64_t rows, uint64_t cols, uint32_t bc, uint32_t br) {
  const CUtensorMapSwizzle sw = bc == 64 ? CU_TENSOR_MAP_SWIZZLE_128B : CU_TENSOR_MAP_SWIZZLE_64B;
  cuuint64_t gd[2] = {cols, rows}, gs[1] = {cols * 2};
  cuuint32_t bd[2] = {bc, br}, es[2] = {1, 1};
  g_enc(m, CU_TENSOR_MAP_DATA_TYPE_BFLOAT16, 2, (void*)ptr, gd, gs, bd, es, CU_TENSOR_MAP_INTERLEAVE_NONE, sw,
        CU_TENSOR_MAP_L2_PROMOTION_L2_128B, CU_TENSOR_MAP_FLOAT_OOB_FILL_NONE);
}
void map3(CUtensorMap* m, const void* ptr, uint64_t rows, uint64_t cols, uint32_t br, uint32_t bch, uint32_t bc = 64) {
  cuuint64_t gd[3] = {bc, rows, cols / bc}, gs[2] = {cols * 2, bc * 2};
  cuuint32_t bd[3] = {bc, br, bch}, es[3] = {1, 1, 1};
  g_enc(m, CU_TENSOR_MAP_DATA_TYPE_BFLOAT16, 3, (void*)ptr, gd, gs, bd, es, CU_TENSOR_MAP_INTERLEAVE_NONE, bc == 64 ? CU_TENSOR_MAP_SWIZZLE_128B : CU_TENSOR_MAP_SWIZZLE_64B,
        CU_TENSOR_MAP_L2_PROMOTION_L2_128B, CU_TENSOR_MAP_FLOAT_OOB_FILL_NONE);
}

}

extern "C" void kernel_launch(void* const* d_in, const int* in_sizes, int n_in, void* d_out, int out_size) {
  const __nv_bfloat16* x = (const __nv_bfloat16*)d_in[0];
  const __nv_bfloat16* ckv = (const __nv_bfloat16*)d_in[1];
  const __nv_bfloat16* wq = (const __nv_bfloat16*)d_in[2];
  const __nv_bfloat16* wk = (const __nv_bfloat16*)d_in[3];
  const __nv_bfloat16* wv = (const __nv_bfloat16*)d_in[4];
  const __nv_bfloat16* wo = (const __nv_bfloat16*)d_in[5];
  const __nv_bfloat16* w_r = (const __nv_bfloat16*)d_in[7];
  const __nv_bfloat16* wgate = (const __nv_bfloat16*)d_in[8];
  const __nv_bfloat16* wup = (const __nv_bfloat16*)d_in[9];
  const __nv_bfloat16* wdown = (const __nv_bfloat16*)d_in[10];
  __nv_bfloat16* out = (__nv_bfloat16*)d_out;

  if (!g_enc) {
    void* fn = nullptr;
    cudaDriverEntryPointQueryResult qr;
    cudaGetDriverEntryPoint("cuTensorMapEncodeTiled", &fn, cudaEnableDefault, &qr);
    g_enc = (EncodeFn)fn;
    cudaFuncSetAttribute(fused_kernel, cudaFuncAttributeMaxDynamicSharedMemorySize, SMEM_BYTES);
  }
  void *xn, *qkv;
  cudaGetSymbolAddress(&xn, g_xn);
  cudaGetSymbolAddress(&qkv, g_qkv);

  Params p;
  map2(&p.xn, xn, SEQ, DM, 64, 128);
  map2(&p.ckv, ckv, SEQ, DC, 64, 128);
  map3(&p.wq, wq, DM, NQ, 64, 2);
  map3(&p.wk, wk, DC, NQ, 64, 2);
  map3(&p.wv, wv, DC, NQ, 64, 2);
  map3(&p.kv, qkv, 3 * SEQ, NQ, 128, 1);
  map2(&p.ctx_ld, qkv, SEQ, NQ, 64, 128);
  map3(&p.ctx_st, qkv, SEQ, NQ, 64, ST_G, 32);
  map3(&p.wo, wo, NQ, DM, 64, 1);
  map3(&p.x, x, SEQ, DM, 64, 2);
  map3(&p.wd, wdown, FF, DM, 32, 8);
  map2(&p.out, out, SEQ, DM, 64, 64);
  map2(&p.wg, wgate, DM, FF, 32, 128);
  map2(&p.wu, wup, DM, FF, 32, 128);
  fused_kernel<<<128, 384, SMEM_BYTES, cudaStreamPerThread>>>(p, x, wq, w_r, wgate, wup, out);
}
```

```cpp
#include <cuda_runtime.h>
#include <cuda_bf16.h>
#include <cuda.h>
#include <stdint.h>
#include <type_traits>

#pragma nv_diag_suppress 549
namespace {

constexpr int SEQ = 2048, DM = 1024, NH = 32, HD = 128, DC = 512, NQ = NH * HD, FF = 3584;

__device__ __align__(1024) __nv_bfloat16 g_xn[SEQ * DM];
__device__ __align__(1024) __nv_bfloat16 g_qkv[3 * SEQ * NQ];
constexpr int XR_PS = 0;
constexpr int XR_KEY = 128;
constexpr int XR_FLAG = 132;
constexpr int XR_CAND = 136;
constexpr int XR_Y = 648;
constexpr int XR_SIZE = 1104;
__device__ __align__(1024) uint4 g_xr[128 * XR_SIZE];
constexpr int C_LN = 0, C_QKV = 16, C_CTX = 32, C_NUM = 64;
__device__ unsigned g_cnt[C_NUM];

#define TL(k, i, cond) do {} while (0)
#define TL_BYTES 0
#define TL_INIT() do {} while (0)
#define TL_DUMP() do {} while (0)
#define TC(g, i) do {} while (0)
#define TCF() do {} while (0)
#define TS(i) do {} while (0)
#undef TCLK
#define TCLK 0

__device__ __forceinline__ uint32_t s2u(const void* p) { return (uint32_t)__cvta_generic_to_shared(p); }
__device__ __forceinline__ void mbar_init(uint32_t b, uint32_t c) { asm volatile("mbarrier.init.shared::cta.b64 [%0], %1;" ::"r"(b), "r"(c) : "memory"); }
__device__ __forceinline__ void mbar_expect(uint32_t b, uint32_t bytes) { asm volatile("mbarrier.arrive.expect_tx.shared::cta.b64 _, [%0], %1;" ::"r"(b), "r"(bytes) : "memory"); }
__device__ __forceinline__ void mbar_arrive(uint32_t b) { asm volatile("mbarrier.arrive.shared::cta.b64 _, [%0];" ::"r"(b) : "memory"); }
__device__ __forceinline__ void mbar_arrive_cta(uint32_t b, uint32_t cta) {
  asm volatile("{\n.reg .b32 r;\nmapa.shared::cluster.u32 r, %0, %1;\nmbarrier.arrive.shared::cluster.b64 _, [r];\n}" ::"r"(b), "r"(cta) : "memory");
}
__device__ __forceinline__ bool mbar_test(uint32_t b, uint32_t ph) {
  uint32_t ok;
  asm volatile("{\n.reg .pred p;\nmbarrier.test_wait.parity.shared::cta.b64 p, [%1], %2;\nselp.u32 %0, 1, 0, p;\n}" : "=r"(ok) : "r"(b), "r"(ph) : "memory");
  return ok;
}
__device__ __forceinline__ void mbar_wait(uint32_t b, uint32_t ph) {
  asm volatile(
      "{\n.reg .pred p;\n.reg .u32 n;\nmov.u32 n, 0;\n"
      "LW:\nmbarrier.try_wait.parity.shared::cta.b64 p, [%0], %1, 20000;\n@p bra LD;\n"
      "add.u32 n, n, 1;\nsetp.lt.u32 p, n, 0x40000;\n@p bra LW;\ntrap;\nLD:\n}" ::"r"(b), "r"(ph) : "memory");
}
__device__ __forceinline__ void mbar_wait_c(uint32_t b, uint32_t ph) {
  asm volatile(
      "{\n.reg .pred p;\n.reg .u32 n;\nmov.u32 n, 0;\n"
      "LW:\nmbarrier.try_wait.parity.shared::cta.b64 p, [%0], %1;\n@p bra LD;\n"
      "add.u32 n, n, 1;\nsetp.lt.u32 p, n, 0x100000;\n@p bra LW;\ntrap;\nLD:\n}" ::"r"(b), "r"(ph) : "memory");
}
__device__ __forceinline__ bool mbar_try(uint32_t b, uint32_t ph) {
  uint32_t ok;
  asm volatile("{\n.reg .pred p;\nmbarrier.try_wait.parity.shared::cta.b64 p, [%1], %2;\nselp.u32 %0, 1, 0, p;\n}" : "=r"(ok) : "r"(b), "r"(ph) : "memory");
  return ok;
}
#define UNLIKELY(c) __builtin_expect(!!(c), 0)
__device__ __forceinline__ void mbar_wait_f(uint32_t b, uint32_t ph) { if (UNLIKELY(!mbar_try(b, ph))) mbar_wait_c(b, ph); }
__device__ __forceinline__ uint32_t pinned(uint32_t v) { uint32_t r; asm volatile("mov.b32 %0, %1;" : "=r"(r) : "r"(v)); return r; }
__device__ __forceinline__ bool elect_one() {
  uint32_t p;
  asm volatile("{\n.reg .pred p;\nelect.sync _|p, 0xFFFFFFFF;\nselp.u32 %0, 1, 0, p;\n}" : "=r"(p));
  return p;
}
__device__ __forceinline__ int lane_id() { int r; asm volatile("mov.u32 %0, %%laneid;" : "=r"(r)); return r; }
template <bool SLEEP = false>
__device__ __forceinline__ void spin_until_ge(const unsigned* p, unsigned target) {
  asm volatile(
      "{\n.reg .pred p, q;\n.reg .u32 n, v;\nmov.u32 n, 0;\nsetp.ne.u32 q, %2, 0;\n"
      "LW:\nld.acquire.gpu.global.u32 v, [%0];\nsetp.ge.u32 p, v, %1;\n@p bra LD;\n@q nanosleep.u32 200;\n"
      "add.u32 n, n, 1;\nsetp.lt.u32 p, n, 0x400000;\n@p bra LW;\ntrap;\nLD:\n}" ::"l"(p), "r"(target), "n"((int)SLEEP) : "memory");
}
template <int N>
__device__ __forceinline__ void poll_chunks(uint4 (&v)[N], const uint4* p, int stride) {
#pragma unroll 1
  for (int n = 0; n < 0x400000; n++) {
    uint32_t m = 0;
#pragma unroll
    for (int i = 0; i < N; i++) {
      asm volatile("ld.relaxed.gpu.global.v4.u32 {%0,%1,%2,%3}, [%4];" : "=r"(v[i].x), "=r"(v[i].y), "=r"(v[i].z), "=r"(v[i].w) : "l"(p + i * stride) : "memory");
    }
#pragma unroll
    for (int i = 0; i < N; i++) m = max(max(m, max(v[i].x, v[i].y)), max(v[i].z, v[i].w));
    if (__all_sync(~0u, m != 0xFFFFFFFFu)) break;
  }
}
__device__ __forceinline__ void fence_async_all() { asm volatile("fence.proxy.async;" ::: "memory"); }
__device__ __forceinline__ void bar_sync(int id, int n) { asm volatile("bar.sync %0, %1;" ::"r"(id), "r"(n) : "memory"); }
__device__ __forceinline__ void bar_arrive(int id, int n) { asm volatile("bar.arrive %0, %1;" ::"r"(id), "r"(n) : "memory"); }
__device__ __forceinline__ void cluster_arrive() { asm volatile("barrier.cluster.arrive.relaxed.aligned;" ::: "memory"); }
__device__ __forceinline__ void cluster_wait() { asm volatile("barrier.cluster.wait.acquire.aligned;" ::: "memory"); }
__device__ __forceinline__ void fence_gpu() { asm volatile("fence.acq_rel.gpu;" ::: "memory"); }
__device__ __forceinline__ void red_add(unsigned* p, unsigned v) { asm volatile("red.relaxed.gpu.global.add.u32 [%0], %1;" ::"l"(p), "r"(v) : "memory"); }
__device__ __forceinline__ void prefetch_tm(const CUtensorMap* m) { asm volatile("prefetch.tensormap [%0];" ::"l"(m) : "memory"); }

__device__ __forceinline__ void tma_ld2(uint32_t dst, const CUtensorMap* m, uint32_t bar, int c0, int c1) {
  asm volatile("cp.async.bulk.tensor.2d.shared::cta.global.mbarrier::complete_tx::bytes [%0], [%1, {%3,%4}], [%2];" ::"r"(dst), "l"(m), "r"(bar), "r"(c0), "r"(c1) : "memory");
}
__device__ __forceinline__ void tma_ld3(uint32_t dst, const CUtensorMap* m, uint32_t bar, int c0, int c1, int c2) {
  asm volatile("cp.async.bulk.tensor.3d.shared::cta.global.mbarrier::complete_tx::bytes [%0], [%1, {%3,%4,%5}], [%2];" ::"r"(dst), "l"(m), "r"(bar), "r"(c0), "r"(c1), "r"(c2) : "memory");
}
__device__ __forceinline__ void tma_ld3_mc(uint32_t dst, const CUtensorMap* m, uint32_t bar, int c0, int c1, int c2, uint16_t mask) {
  asm volatile("cp.async.bulk.tensor.3d.shared::cluster.global.mbarrier::complete_tx::bytes.multicast::cluster [%0], [%1, {%3,%4,%5}], [%2], %6;" ::"r"(dst), "l"(m), "r"(bar), "r"(c0), "r"(c1), "r"(c2), "h"(mask) : "memory");
}
__device__ __forceinline__ void tma_pf3(const CUtensorMap* m, int c0, int c1, int c2) {
  asm volatile("cp.async.bulk.prefetch.tensor.3d.L2.global [%0, {%1,%2,%3}];" ::"l"(m), "r"(c0), "r"(c1), "r"(c2) : "memory");
}
__device__ __forceinline__ void l2_prefetch(const void* p, uint32_t bytes) { asm volatile("cp.async.bulk.prefetch.L2.global [%0], %1;" ::"l"(p), "r"(bytes) : "memory"); }

__device__ __forceinline__ void wg_fence() { asm volatile("wgmma.fence.sync.aligned;" ::: "memory"); }
__device__ __forceinline__ void wg_commit() { asm volatile("wgmma.commit_group.sync.aligned;" ::: "memory"); }
template <int N> __device__ __forceinline__ void wg_wait() { asm volatile("wgmma.wait_group.sync.aligned %0;" ::"n"(N) : "memory"); }
template <int N> __device__ __forceinline__ void reg_alloc() { asm volatile("setmaxnreg.inc.sync.aligned.u32 %0;" ::"n"(N)); }
template <int N> __device__ __forceinline__ void reg_dealloc() { asm volatile("setmaxnreg.dec.sync.aligned.u32 %0;" ::"n"(N)); }
template <int N> __device__ __forceinline__ void fence_regs(float* d) {
#pragma unroll
  for (int i = 0; i < N; i++) asm volatile("" : "+f"(d[i])::"memory");
}
template <int N> __device__ __forceinline__ void fence_regs(uint32_t* d) {
#pragma unroll
  for (int i = 0; i < N; i++) asm volatile("" : "+r"(d[i])::"memory");
}

__device__ __forceinline__ uint64_t mk_desc(uint32_t addr, uint32_t lbo, uint32_t sbo, uint32_t swz) {
  uint32_t lo = ((addr & 0x3FFFF) >> 4) | ((lbo >> 4) << 16);
  uint32_t hi = (sbo >> 4) | (swz << 30);
  return ((uint64_t)hi << 32) | lo;
}
__device__ __forceinline__ uint64_t desc_add(uint64_t d, uint32_t bytes) {
  uint32_t lo = (uint32_t)d + (bytes >> 4);
  return (d & 0xFFFFFFFF00000000ull) | lo;
}

#define R8(b) "+f"(d[b + 0]), "+f"(d[b + 1]), "+f"(d[b + 2]), "+f"(d[b + 3]), "+f"(d[b + 4]), "+f"(d[b + 5]), "+f"(d[b + 6]), "+f"(d[b + 7])
#define REGS32 "%0,%1,%2,%3,%4,%5,%6,%7,%8,%9,%10,%11,%12,%13,%14,%15,%16,%17,%18,%19,%20,%21,%22,%23,%24,%25,%26,%27,%28,%29,%30,%31"
#define REGS64 REGS32 ",%32,%33,%34,%35,%36,%37,%38,%39,%40,%41,%42,%43,%44,%45,%46,%47,%48,%49,%50,%51,%52,%53,%54,%55,%56,%57,%58,%59,%60,%61,%62,%63"
#define REGS128 REGS64 ",%64,%65,%66,%67,%68,%69,%70,%71,%72,%73,%74,%75,%76,%77,%78,%79,%80,%81,%82,%83,%84,%85,%86,%87,%88,%89,%90,%91,%92,%93,%94,%95," \
               "%96,%97,%98,%99,%100,%101,%102,%103,%104,%105,%106,%107,%108,%109,%110,%111,%112,%113,%114,%115,%116,%117,%118,%119,%120,%121,%122,%123,%124,%125,%126,%127"

template <int TB>
__device__ __forceinline__ void mma_n256_ss(float (&d)[128], uint64_t a, uint64_t b, int acc) {
  asm volatile("{\n.reg .pred p;\nsetp.ne.b32 p, %130, 0;\n"
               "wgmma.mma_async.sync.aligned.m64n256k16.f32.bf16.bf16 {" REGS128 "}, %128, %129, p, 1, 1, 0, %131;\n}\n"
               : R8(0), R8(8), R8(16), R8(24), R8(32), R8(40), R8(48), R8(56), R8(64), R8(72), R8(80), R8(88), R8(96), R8(104), R8(112), R8(120)
               : "l"(a), "l"(b), "r"(acc), "n"(TB));
}
template <int TB>
__device__ __forceinline__ void mma_n128_ss(float* d, uint64_t a, uint64_t b, int acc) {
  asm volatile("{\n.reg .pred p;\nsetp.ne.b32 p, %66, 0;\n"
               "wgmma.mma_async.sync.aligned.m64n128k16.f32.bf16.bf16 {" REGS64 "}, %64, %65, p, 1, 1, 0, %67;\n}\n"
               : R8(0), R8(8), R8(16), R8(24), R8(32), R8(40), R8(48), R8(56)
               : "l"(a), "l"(b), "r"(acc), "n"(TB));
}
template <int TB>
__device__ __forceinline__ void mma_n128_rs(float* d, const uint32_t* a, uint64_t b, int acc) {
  asm volatile("{\n.reg .pred p;\nsetp.ne.b32 p, %69, 0;\n"
               "wgmma.mma_async.sync.aligned.m64n128k16.f32.bf16.bf16 {" REGS64 "}, {%64,%65,%66,%67}, %68, p, 1, 1, %70;\n}\n"
               : R8(0), R8(8), R8(16), R8(24), R8(32), R8(40), R8(48), R8(56)
               : "r"(a[0]), "r"(a[1]), "r"(a[2]), "r"(a[3]), "l"(b), "r"(acc), "n"(TB));
}
__device__ __forceinline__ void mma_n64_rs(float* d, const uint32_t* a, uint64_t b, int acc) {
  asm volatile("{\n.reg .pred p;\nsetp.ne.b32 p, %37, 0;\n"
               "wgmma.mma_async.sync.aligned.m64n64k16.f32.bf16.bf16 {" REGS32 "}, {%32,%33,%34,%35}, %36, p, 1, 1, 0;\n}\n"
               : R8(0), R8(8), R8(16), R8(24)
               : "r"(a[0]), "r"(a[1]), "r"(a[2]), "r"(a[3]), "l"(b), "r"(acc));
}
#define W8(b) "=f"(d[b + 0]), "=f"(d[b + 1]), "=f"(d[b + 2]), "=f"(d[b + 3]), "=f"(d[b + 4]), "=f"(d[b + 5]), "=f"(d[b + 6]), "=f"(d[b + 7])
__device__ __forceinline__ void mma_n128_rs0(float* d, const uint32_t* a, uint64_t b) {
  asm volatile("wgmma.mma_async.sync.aligned.m64n128k16.f32.bf16.bf16 {" REGS64 "}, {%64,%65,%66,%67}, %68, 0, 1, 1, 0;\n"
               : W8(0), W8(8), W8(16), W8(24), W8(32), W8(40), W8(48), W8(56)
               : "r"(a[0]), "r"(a[1]), "r"(a[2]), "r"(a[3]), "l"(b));
}
__device__ __forceinline__ void mma_n64_rs0(float* d, const uint32_t* a, uint64_t b) {
  asm volatile("wgmma.mma_async.sync.aligned.m64n64k16.f32.bf16.bf16 {" REGS32 "}, {%32,%33,%34,%35}, %36, 0, 1, 1, 0;\n"
               : W8(0), W8(8), W8(16), W8(24)
               : "r"(a[0]), "r"(a[1]), "r"(a[2]), "r"(a[3]), "l"(b));
}
__device__ __forceinline__ uint32_t pack_bf16(float lo, float hi) {
  uint32_t r;
  asm("cvt.rn.bf16x2.f32 %0, %1, %2;" : "=r"(r) : "f"(hi), "f"(lo));
  return r;
}
__device__ __forceinline__ float bf_lo(uint32_t v) { return __uint_as_float(v << 16); }
__device__ __forceinline__ float bf_hi(uint32_t v) { return __uint_as_float(v & 0xFFFF0000u); }
__device__ __forceinline__ float bf_round(float v) { return bf_lo(pack_bf16(v, v)); }
__device__ __forceinline__ void stsm4(uint32_t addr, uint32_t r0, uint32_t r1, uint32_t r2, uint32_t r3) {
  asm volatile("stmatrix.sync.aligned.m8n8.x4.shared.b16 [%0], {%1,%2,%3,%4};" ::"r"(addr), "r"(r0), "r"(r1), "r"(r2), "r"(r3) : "memory");
}
__device__ __forceinline__ uint4 lds128(uint32_t addr) {
  uint4 v;
  asm volatile("ld.shared.v4.u32 {%0,%1,%2,%3}, [%4];" : "=r"(v.x), "=r"(v.y), "=r"(v.z), "=r"(v.w) : "r"(addr));
  return v;
}
__device__ __forceinline__ float ex2(float x) {
  float y;
  asm("ex2.approx.ftz.f32 %0, %1;" : "=f"(y) : "f"(x));
  return y;
}
__device__ __forceinline__ void pin_order(float v, uint32_t dummy) {
  asm volatile("{\n.reg .pred p;\nsetp.eq.b32 p, %0, 0xFFFFFFFF;\n@p st.shared.b32 [%1], %0;\n}" ::"r"(__float_as_uint(v)), "r"(dummy) : "memory");
}
__device__ __forceinline__ void sched_fence(uint32_t dummy) {
  asm volatile("{\n.reg .pred p;\n.reg .u32 c;\nsetp.eq.b32 p, %0, 0xFFFFFFFF;\nmov.u32 c, %%clock;\n@p st.shared.b32 [%0], c;\n}" ::"r"(dummy) : "memory");
}
__device__ __forceinline__ void stage_store_128(uint32_t base, int lane, const uint32_t* pk) {
  const int row = (lane & 7) + ((lane >> 3) & 1) * 8;
  const uint32_t rb = base + row * 128;
  const int hi = lane >> 4;
#pragma unroll
  for (int j = 0; j < 8; j++) {
    const int chunk = 2 * j + hi;
    const uint32_t a = rb + (j >> 2) * 8192 + (((chunk & 7) ^ (lane & 7)) << 4);
    stsm4(a, pk[4 * j + 0], pk[4 * j + 1], pk[4 * j + 2], pk[4 * j + 3]);
  }
}
__device__ __forceinline__ void ln_round(float mean, float var, float& m_bf, float& inv_s) {
  const uint32_t mv = pack_bf16(mean, var);
  m_bf = bf_lo(mv);
  float sq, rc;
  asm("sqrt.approx.f32 %0, %1;" : "=f"(sq) : "f"(bf_round(bf_hi(mv) + 1e-5f)));
  asm("rcp.approx.ftz.f32 %0, %1;" : "=f"(rc) : "f"(bf_round(sq)));
  inv_s = rc;
}
__device__ __forceinline__ uint32_t hadd2_bf(uint32_t a, uint32_t b) {
  uint32_t r;
  asm("add.rn.bf16x2 %0, %1, %2;" : "=r"(r) : "r"(a), "r"(b));
  return r;
}
__device__ __forceinline__ uint32_t ln_apply(uint32_t h, uint32_t nm2, float inv_s) {
  const uint32_t d = hadd2_bf(h, nm2);
  return pack_bf16(bf_lo(d) * inv_s, bf_hi(d) * inv_s);
}
__device__ __forceinline__ void ldsm4(uint32_t* r, uint32_t addr) {
  asm volatile("ldmatrix.sync.aligned.m8n8.x4.shared.b16 {%0,%1,%2,%3}, [%4];" : "=r"(r[0]), "=r"(r[1]), "=r"(r[2]), "=r"(r[3]) : "r"(addr) : "memory");
}
__device__ __forceinline__ void mma16816(float* d, uint32_t a0, uint32_t a1, uint32_t a2, uint32_t a3, uint32_t b0, uint32_t b1) {
  asm volatile("mma.sync.aligned.m16n8k16.row.col.f32.bf16.bf16.f32 {%0,%1,%2,%3}, {%4,%5,%6,%7}, {%8,%9}, {%0,%1,%2,%3};"
               : "+f"(d[0]), "+f"(d[1]), "+f"(d[2]), "+f"(d[3]) : "r"(a0), "r"(a1), "r"(a2), "r"(a3), "r"(b0), "r"(b1));
}

template <class F>
__device__ __forceinline__ void unroll8(F f) {
  f(std::integral_constant<int, 0>{}); f(std::integral_constant<int, 1>{}); f(std::integral_constant<int, 2>{}); f(std::integral_constant<int, 3>{});
  f(std::integral_constant<int, 4>{}); f(std::integral_constant<int, 5>{}); f(std::integral_constant<int, 6>{}); f(std::integral_constant<int, 7>{});
}

constexpr float AT_C = 0.08838834764831845f * 1.4426950408889634f;
#define AT_LO 0x1p-40f
#define AT_HI 0x1p40f
#define H_LATE 0
#define AT_R1 48
template <int I0, int I1>
__device__ __forceinline__ void at_exp(float* S) {
#pragma unroll
  for (int i = I0; i < I1; i++) asm volatile("ex2.approx.ftz.f32 %0, %0;" : "+f"(S[i]));
}
template <int I0, int I1>
__device__ __forceinline__ void at_fin(const float* S, uint32_t* P) {
#pragma unroll
  for (int i = I0; i < I1; i += 4) {
    P[i / 2] = pack_bf16(S[i], S[i + 1]); P[i / 2 + 1] = pack_bf16(S[i + 2], S[i + 3]);
  }
}
__device__ __forceinline__ void at_sum(const uint32_t* P, bool half, float& l0, float& l1) {
  uint32_t u[4];
#pragma unroll
  for (int r = 0; r < 4; r++) {
    const uint32_t* q = P + (r >> 1) * 16 + (r & 1);
    u[r] = hadd2_bf(hadd2_bf(hadd2_bf(q[0], q[2]), hadd2_bf(q[4], q[6])), hadd2_bf(hadd2_bf(q[8], q[10]), hadd2_bf(q[12], q[14])));
  }
  u[0] = hadd2_bf(u[0], half ? 0u : u[2]);
  u[1] = hadd2_bf(u[1], half ? 0u : u[3]);
  l0 += bf_lo(u[0]) + bf_hi(u[0]);
  l1 += bf_lo(u[1]) + bf_hi(u[1]);
}
__device__ __forceinline__ void at_mask(float* S, int r, int lane) {
  const int d = r + (lane >> 2) - (lane & 3) * 2;
#pragma unroll
  for (int j = 0; j < 8; j++) {
    float dummy0 = 0.f, dummy1 = 0.f;
    float& lo0 = j < 7 ? S[4 * (j < 7 ? j + 1 : j) + 2] : dummy0;
    float& lo1 = j < 7 ? S[4 * (j < 7 ? j + 1 : j) + 3] : dummy1;
    asm("{\n.reg .pred p, q;\nsetp.lt.s32 p, %4, %5;\nsetp.le.s32 q, %4, %5;\n"
        "@p add.f32 %0, %0, 0fFF800000;\n@q add.f32 %1, %1, 0fFF800000;\n@p add.f32 %2, %2, 0fFF800000;\n@q add.f32 %3, %3, 0fFF800000;\n}"
        : "+f"(S[4 * j]), "+f"(S[4 * j + 1]), "+f"(lo0), "+f"(lo1) : "r"(d), "r"(8 * j));
  }
}
__device__ __forceinline__ uint32_t ldg32(const __nv_bfloat16* p) { return __ldcg(reinterpret_cast<const uint32_t*>(p)); }
__device__ __forceinline__ uint32_t ldg16x2(const __nv_bfloat16* p, int stride) {
  return (uint32_t)__ldcg(reinterpret_cast<const unsigned short*>(p)) | ((uint32_t)__ldcg(reinterpret_cast<const unsigned short*>(p + stride)) << 16);
}
__device__ __forceinline__ void slow_tile(float* O, uint32_t* Q, float& l0, float& l1, const __nv_bfloat16* wq, int row0, int head, int lane, uint32_t dummy) {
  const int r = lane >> 2, q = lane & 3;
#pragma unroll
  for (int i = 0; i < 64; i++) O[i] = 0.f;
  {
    const __nv_bfloat16* xa = g_xn + (size_t)(row0 + r) * DM + 2 * q;
    const __nv_bfloat16* wb = wq + (size_t)(2 * q) * NQ + head * HD + (r >> 1) * 8 + (r & 1);
#pragma unroll 1
    for (int k = 0; k < DM; k += 16) {
      const uint32_t a0 = ldg32(xa + k), a1 = ldg32(xa + k + 8 * DM), a2 = ldg32(xa + k + 8), a3 = ldg32(xa + k + 8 * DM + 8);
#pragma unroll
      for (int j = 0; j < 16; j++) {
        const __nv_bfloat16* wp = wb + (size_t)k * NQ + (j >> 2) * 32 + (j & 3) * 2;
        mma16816(O + 4 * j, a0, a1, a2, a3, ldg16x2(wp, NQ), ldg16x2(wp + 8 * NQ, NQ));
        if (j == 7) sched_fence(dummy);
      }
    }
  }
#pragma unroll
  for (int i = 0; i < 32; i++) Q[i] = pack_bf16(O[2 * i], O[2 * i + 1]);
#pragma unroll
  for (int i = 0; i < 64; i++) O[i] = 0.f;
  float m0 = -INFINITY, m1 = -INFINITY;
  l0 = l1 = 0.f;
#pragma unroll 1
  for (int kv = 0; kv <= row0; kv += 16) {
    float s[8] = {0.f, 0.f, 0.f, 0.f, 0.f, 0.f, 0.f, 0.f};
    const __nv_bfloat16* kp = g_qkv + (size_t)(SEQ + kv + r) * NQ + head * HD + 2 * q;
#pragma unroll
    for (int k = 0; k < 8; k++) {
      mma16816(s, Q[4 * k], Q[4 * k + 1], Q[4 * k + 2], Q[4 * k + 3], ldg32(kp + 16 * k), ldg32(kp + 16 * k + 8));
      mma16816(s + 4, Q[4 * k], Q[4 * k + 1], Q[4 * k + 2], Q[4 * k + 3], ldg32(kp + 8 * NQ + 16 * k), ldg32(kp + 8 * NQ + 16 * k + 8));
    }
#pragma unroll
    for (int i = 0; i < 8; i++)
      if (kv + (i >> 2) * 8 + 2 * q + (i & 1) > row0 + r + (i & 2) * 4) s[i] = -INFINITY;
    float a = fmaxf(fmaxf(fmaxf(s[0], s[1]), fmaxf(s[4], s[5])), m0), b = fmaxf(fmaxf(fmaxf(s[2], s[3]), fmaxf(s[6], s[7])), m1);
    a = fmaxf(a, __shfl_xor_sync(~0u, a, 1)); b = fmaxf(b, __shfl_xor_sync(~0u, b, 1));
    a = fmaxf(a, __shfl_xor_sync(~0u, a, 2)); b = fmaxf(b, __shfl_xor_sync(~0u, b, 2));
    const float c0 = ex2(m0 - a), c1 = ex2(m1 - b);
    m0 = a; m1 = b;
#pragma unroll
    for (int i = 0; i < 8; i++) s[i] = ex2(s[i] - ((i & 2) ? b : a));
    l0 = l0 * c0 + (s[0] + s[1]) + (s[4] + s[5]);
    l1 = l1 * c1 + (s[2] + s[3]) + (s[6] + s[7]);
    sched_fence(dummy);
    const uint32_t p0 = pack_bf16(s[0], s[1]), p1 = pack_bf16(s[2], s[3]), p2 = pack_bf16(s[4], s[5]), p3 = pack_bf16(s[6], s[7]);
    const __nv_bfloat16* vp = g_qkv + (size_t)(2 * SEQ + kv + 2 * q) * NQ + head * HD + r;
#pragma unroll
    for (int j = 0; j < 16; j++) {
      O[4 * j] *= c0; O[4 * j + 1] *= c0; O[4 * j + 2] *= c1; O[4 * j + 3] *= c1;
      mma16816(O + 4 * j, p0, p1, p2, p3, ldg16x2(vp + 8 * j, NQ), ldg16x2(vp + 8 * NQ + 8 * j, NQ));
      if (j == 7) sched_fence(dummy);
    }
  }
}

constexpr int P1_STAGE = 49152;
constexpr int SLOT = 32768;
constexpr int OFF_LN = 6 * SLOT, OFF_R3 = 0;
constexpr int OFF_BAR = 229376;
constexpr int OFF_MISC = OFF_BAR + 8 * 58;
constexpr int SMEM_BYTES = OFF_MISC + 2080 + TL_BYTES;
enum : int {
  B_FULL1 = 0, B_KF = 4, B_VF = 6, B_FULL3 = 8, B_XF = 14, B_LN = 15, B_DEP = 16, B_OUT2 = 22, B_FIN = 23, B_SET = 24, B_SET2 = 25, B_QP = 26, B_WF2 = 29,
  B_WF = 30, B_WR = 31,
  B_LND = 32,
  B_XE = 33, B_PUB = 34, B_OUT = 40, B_OUT3 = 41,
  B_EMPTY1 = 42, B_KE = 46, B_VE = 48, B_EMPTY3 = 50, B_WE = 56, B_NUM = 57
};
constexpr int PRE = 3;
#define LN_PF 4
#define LN_LD 9
constexpr int LN_PFN = 2;
constexpr int OFF_STG = SLOT, SL_SCR = 2;
#define SET_NS 50
#define ST_G 1
#define ST_NS 0
#define OBS 99
#define PFALL 0
#define WQ_D 4
#define WQ_0 18
#define STCS 15
#define HSWAP 0
#define SL_NS 600
#define X_KB 20
#define G_KB 35
#define WD_AT 8
#define OUT_P 0
#define W_G0 22
#define KVPF 1
struct Params {
  CUtensorMap xn, ckv, wq, wk, wv, kv, ctx_ld, ctx_st, wo, x, wd, wg, wu, out;
};

__global__ void __cluster_dims__(2, 1, 1) __launch_bounds__(384, 1)
fused_kernel(const __grid_constant__ Params p, const __nv_bfloat16* __restrict__ x, const __nv_bfloat16* __restrict__ wq,
             const __nv_bfloat16* __restrict__ w_r,
             __nv_bfloat16* __restrict__ out) {
  extern __shared__ __align__(1024) uint8_t sp[];
  const uint32_t sb = s2u(sp);
  const uint32_t bar = sb + OFF_BAR;
  auto B = [&](int i) { return bar + 8 * i; };
  const int tid = threadIdx.x, warp = __shfl_sync(~0u, tid >> 5, 0), wg = warp >> 2, lane = tid & 31;
  const int cta = blockIdx.x, rank = cta & 1, cl = cta >> 1;
  const int mp = cl < 4 ? 1 : (cl < 36 ? (cl & 7) : (0x3207654 >> (4 * ((cl - 36) % 7))) & 7);
  const int gq = cl < 4 ? 4 + cl : (cl < 36 ? (cl - 4) >> 3 : 4 + (cl - 36) / 7);
  const int mt = 2 * mp + rank;
  const int ti = (gq & 3) * 2 + rank, hh = mp * 2 + (gq >> 2);
  const int rid = mt * 8 + gq;
  const int fid = mt * 7 + gq;
  const bool ffn = gq < 7;
  uint4* const xr = g_xr + rid * XR_SIZE;
  TL_INIT();
  TL(0, 0, tid == 128);
  if (tid == 32) TS(0);
  if (warp == 0 && elect_one()) {
#pragma unroll 1
    for (int kb = 0; kb < PRE; kb++) {
      mbar_init(B(B_FULL1 + kb), 1);
      asm volatile("fence.mbarrier_init.release.cluster;" ::: "memory");
      mbar_expect(B(B_FULL1 + kb), P1_STAGE);
      tma_ld2(sb + kb * P1_STAGE, &p.ckv, B(B_FULL1 + kb), kb * 64, mt * 128);
      tma_ld3(sb + kb * P1_STAGE + 16384 + rank * 16384, &p.wk, B(B_FULL1 + kb), 0, kb * 64, (gq + HSWAP * 8) * 4 + rank * 2);
      tma_ld3(sb + kb * P1_STAGE + 32768 - rank * 16384, &p.wk, B(B_FULL1 + kb), 0, kb * 64, (gq + HSWAP * 8) * 4 + 2 - rank * 2);
    }
  }
  if (lane == 0) {
#pragma unroll 1
    for (int i = warp < PRE ? warp + 12 : warp; i < B_NUM; i += 12) {
      mbar_init(B(i), i >= B_EMPTY1 ? 16 : (i >= B_XE ? 8 : (i == B_LND ? 3 : (i >= B_WF ? 2 : 1))));
    }
    asm volatile("fence.mbarrier_init.release.cluster;" ::: "memory");
  }
  __syncwarp();
  cluster_arrive();
  if (warp == 1 && elect_one()) {
    if (mt >= 2 * PRE) asm volatile("cp.async.bulk.prefetch.tensor.3d.L2.global [%0, {%1,%2,%3}];" ::"l"(&p.wk), "r"(0), "r"((mt >> 1) * 64), "r"((gq + HSWAP * 8) * 4 + (mt & 1) * 2) : "memory");
    if (gq >= PRE) asm volatile("cp.async.bulk.prefetch.tensor.2d.L2.global [%0, {%1,%2}];" ::"l"(&p.ckv), "r"(gq * 64), "r"(mt * 128) : "memory");
  } else if (warp == 2 && elect_one()) {
    prefetch_tm(&p.wv); prefetch_tm(&p.wq); prefetch_tm(&p.xn);
  }
  __syncwarp();
  cluster_wait();
  if (wg == 0) {
    reg_dealloc<40>();
    if (warp == 0) {
      int st = 0; uint32_t ph = 1;
#pragma unroll 1
      for (int t = 0; t < 6; t++) {
        const CUtensorMap* ma = t >= 4 ? &p.xn : &p.ckv;
        const CUtensorMap* mb = t >= 4 ? &p.wq : ((t & 1) ? &p.wv : &p.wk);
        const int nk = t >= 4 ? 16 : 8;
        const int row = (t < 4 ? mt : (t == 4 ? 15 - ti : ti)) * 128;
        const int col = t < 4 ? (gq + ((t >> 1) ^ HSWAP) * 8) * 4 + rank * 2 : (hh + rank * 16) * 2;
        if (t >= 4) mbar_wait(B(B_DEP + t - 4), 0);
#pragma unroll 1
        for (int kb = 0; kb < nk; kb++) {
          const uint32_t d = sb + st * P1_STAGE, fb = B(B_FULL1 + st);
          const int n = t * 8 + kb;
          if (n >= PRE) {
            mbar_wait_c(B(B_EMPTY1 + st), ph);
            if (elect_one()) {
              mbar_expect(fb, P1_STAGE);
              tma_ld2(d, ma, fb, kb * 64, row);
              tma_ld3_mc(d + 16384 + rank * 16384, mb, fb, 0, kb * 64, col, 3);
            }
          }
          if (t < 5 && elect_one()) {
            if (n >= LN_PF && n < LN_PF + LN_PFN) l2_prefetch(x + (size_t)cta * 16 * DM + (n - LN_PF) * (16 * DM / LN_PFN), 32768 / LN_PFN);
            if (n == LN_LD) {
              mbar_expect(B(B_LN), 32768);
              asm volatile("cp.async.bulk.shared::cluster.global.mbarrier::complete_tx::bytes [%0], [%1], %2, [%3];" ::"r"(sb + OFF_LN),
                           "l"(x + (size_t)cta * 16 * DM), "r"(32768), "r"(B(B_LN)) : "memory");
            }
            if (t < 3 && kb == 0) tma_pf3((t & 1) ? &p.wk : &p.wv, 0, mp * 64, (gq + (((t + 1) >> 1) ^ HSWAP) * 8) * 4 + rank * 2);
            if (n >= WQ_0 && n < WQ_0 + 4 * WQ_D && (n - WQ_0) % WQ_D == 0) tma_pf3(&p.wq, 0, ((n - WQ_0) / WQ_D * 4 + (gq & 3)) * 64, (hh + rank * 16) * 2);
          }
          if (++st == 4) { st = 0; ph ^= 1; }
        }
      }
      if (elect_one()) { prefetch_tm(&p.kv); prefetch_tm(&p.ctx_ld); prefetch_tm(&p.wo); prefetch_tm(&p.wg); prefetch_tm(&p.wu); }
      auto load_kv = [&](int g, int isv) {
        const int h2 = g >= 17, sx = g - 17 * h2, n1 = h2 ? ti + 1 : 16 - ti;
        const int row = (1 + isv) * SEQ + (sx < n1 ? sx : 16 - sx) * 128, col = (hh + 16 * h2) * 2;
        const uint32_t d = sb + (isv ? 2 + 2 * (g & 1) : (g & 1)) * SLOT, fb = B(B_KF + 2 * isv + (g & 1));
        const bool shared = sx != (h2 ? (ti & 6) + 1 : 15 - (ti & 6));
        const int g2 = g + KVPF, h3 = g2 >= 17, s3 = g2 - 17 * h3;
        const int pb = PFALL ? (g2 < 34 ? (s3 < (h3 ? ti + 1 : 16 - ti) ? s3 : 16 - s3) : -1)
                             : (ti < 2 ? (h3 ? (s3 >= 1 && s3 <= 8 ? 16 - s3 : -1) : (s3 < 16 ? s3 : -1)) : (ti >= 6 && h3 && s3 < 8 ? s3 : -1));
        mbar_wait_c(g < 2 ? B(B_EMPTY1 + (isv ? 1 + 2 * g : g)) : B(B_KE + 2 * isv + (g & 1)), g < 2 ? 1 : ((g >> 1) & 1) ^ 1);
        if (elect_one()) {
          mbar_expect(fb, SLOT);
          if (shared) {
            tma_ld3_mc(d + rank * 16384, &p.kv, fb, 0, row, col + rank, 3);
          } else {
            tma_ld3(d, &p.kv, fb, 0, row, col);
            tma_ld3(d + 16384, &p.kv, fb, 0, row, col + 1);
          }
          if (KVPF && pb >= 0) tma_pf3(&p.kv, 0, (1 + isv) * SEQ + pb * 128, (hh + 16 * h3) * 2 + rank);
        }
      };
      int nw = ffn ? 0 : 12;
      auto load_w = [&]() {
        const int c = nw < 8 ? (nw >> 2) + (nw & 2) : nw >> 1;
        if (elect_one()) {
          if (!(nw & 3)) mbar_expect(B(B_WF - (nw >> 3)), 32768);
          tma_ld2(sb + (c < 2 ? 3 : 4) * SLOT + c * 16384 + (nw & 1) * 8192, (nw & 1) ? &p.wg : &p.wu, B(B_WF - (nw >> 3)), fid * 32, c * 128);
        }
        nw++;
      };
#pragma unroll 1
      for (int g = 0; g < 34; g++) {
        if (g == 0 || g == 17 - KVPF) mbar_wait(B(B_DEP + 2 + (g > 0)), 0);
        load_kv(g, 0);
        if (g > 0) load_kv(g - 1, 1);
        if (g >= W_G0 && nw < 12 && __any_sync(~0u, mbar_test(B(B_QP + (nw >> 2)), 0))) load_w();
      }
      load_kv(33, 1);
#pragma unroll 1
      while (nw < 12) { mbar_wait(B(B_QP + (nw >> 2)), 0); load_w(); }
      if (elect_one()) { prefetch_tm(&p.wd); prefetch_tm(&p.x); prefetch_tm(&p.out); }
      auto load3 = [&](int kb, int sl) {
        if (elect_one()) {
          mbar_expect(B(B_FULL3 + sl), SLOT);
          tma_ld2(sb + OFF_R3 + sl * SLOT, &p.ctx_ld, B(B_FULL3 + sl), kb * 64, mt * 128);
          tma_ld3_mc(sb + OFF_R3 + sl * SLOT + 16384 + rank * 8192, &p.wo, B(B_FULL3 + sl), 0, kb * 64, gq * 2 + rank, 3);
          if (kb >= OBS && kb < OBS + 11) TL(0, 32 + kb - OBS, true);
        }
      };
      mbar_wait(B(B_DEP + 4), 0);
#pragma unroll
      for (int kb = 0; kb < 5; kb++) {
        mbar_wait_c(B(kb == 3 ? B_WE : (kb == 4 ? B_VE + 1 : B_KE + kb)), 0);
        load3(kb, kb);
      }
      if (elect_one()) mbar_arrive(B(B_FULL3 + 5));
#pragma unroll 1
      for (int r = 1; r < 11; r++) {
#pragma unroll
        for (int j = 0; j < 6; j++) {
          if (j == 5 && r == 10) break;
          if (j == 3 && r == 5) mbar_wait(B(B_DEP + 5), 0);
          mbar_wait_c(B(B_EMPTY3 + j), ~r & 1);
          load3(r * 6 + j - 1, j);
          if (j == 5 && r == 9 && elect_one()) l2_prefetch(xr, XR_CAND * 16);
        }
      }
      if (ffn) {
#pragma unroll
        for (int j = 1; j >= 0; j--) {
          mbar_wait(B(B_EMPTY3 + 5 * j), j);
          if (elect_one()) {
            mbar_expect(B(B_FULL3 + 5 * j), SLOT);
            tma_ld3(sb + OFF_R3 + 5 * j * SLOT, &p.wd, B(B_FULL3 + 5 * j), 0, fid * 32, 8 * j);
          }
        }
      }
    } else {
      if (warp >= 2) {
#pragma unroll 1
        for (int i = tid - 64; i < XR_CAND; i += 64) xr[i] = make_uint4(~0u, ~0u, ~0u, ~0u);
        if (warp == 2) { __syncwarp(); if (lane == 0) mbar_arrive(B(B_WR)); }
      }
      if (warp == 3) {
        float ws = 0.f;
#pragma unroll
        for (int j = 0; j < 4; j++) {
          const uint4 q = __ldg(reinterpret_cast<const uint4*>(w_r) + j * 32 + lane);
          ws += bf_lo(q.x) + bf_hi(q.x) + bf_lo(q.y) + bf_hi(q.y) + bf_lo(q.z) + bf_hi(q.z) + bf_lo(q.w) + bf_hi(q.w);
        }
#pragma unroll
        for (int o = 16; o; o >>= 1) ws += __shfl_xor_sync(~0u, ws, o);
        uint2* tab = reinterpret_cast<uint2*>(sp + OFF_MISC + 512);
        tab[lane] = make_uint2(0x3F803F80u, 0x3F803F80u);
        tab[32 + lane] = __ldg(reinterpret_cast<const uint2*>(w_r + gq * 128) + lane);
        if (lane == 0) *reinterpret_cast<float*>(sp + OFF_MISC + 1024) = ws;
        __syncwarp();
        if (lane == 0) mbar_arrive(B(B_WR));
      }
      mbar_wait(B(B_LN), 0);
#pragma unroll 1
      for (int r = warp - 1; r < 16; r += 3) {
        uint4 v[4];
        float a0 = 0.f, a1 = 0.f, b0 = 0.f, b1 = 0.f;
#pragma unroll
        for (int j = 0; j < 4; j++) {
          v[j] = lds128(sb + OFF_LN + r * 2048 + lane * 16 + j * 512);
          const uint32_t u[4] = {v[j].x, v[j].y, v[j].z, v[j].w};
#pragma unroll
          for (int i = 0; i < 4; i++) { const float a = bf_lo(u[i]), b = bf_hi(u[i]); a0 += a; a1 += b; b0 = fmaf(a, a, b0); b1 = fmaf(b, b, b1); }
        }
        a0 += a1; b0 += b1;
#pragma unroll
        for (int o = 16; o; o >>= 1) { a0 += __shfl_xor_sync(~0u, a0, o); b0 += __shfl_xor_sync(~0u, b0, o); }
        const float mean = a0 * (1.f / DM);
        float mb, inv;
        ln_round(mean, fmaxf(fmaf(b0, 1.f / DM, -mean * mean), 0.f), mb, inv);
        inv *= AT_C;
        const uint32_t nm2 = pack_bf16(-mb, -mb);
        uint4* dst = reinterpret_cast<uint4*>(g_xn + (size_t)(cta * 16 + r) * DM) + lane;
#pragma unroll
        for (int j = 0; j < 4; j++)
          dst[j * 32] = make_uint4(ln_apply(v[j].x, nm2, inv), ln_apply(v[j].y, nm2, inv), ln_apply(v[j].z, nm2, inv), ln_apply(v[j].w, nm2, inv));
      }
      __syncwarp();
      if (lane == 0) {
        mbar_arrive(B(B_LND));
        fence_gpu();
        red_add(&g_cnt[C_LN + (cta >> 3)], 1);
      }
      TL(3, warp, lane == 0);
      __syncwarp();
      if (warp == 3) {
        if (lane == 0) {
#pragma unroll 1
          for (int i = 0; i < 6; i++) {
            const int c = i < 2 ? C_LN + (i ? ti : 15 - ti) : (i < 4 ? C_QKV + (i - 2) * 8 + mp : C_CTX + (i - 4) * 16 + mt);
            spin_until_ge<true>(&g_cnt[c], i < 2 ? 24 : 16);
            fence_async_all();
            mbar_arrive(B(B_DEP + i));
            TL(3, 4 + i, true);
          }
        }
      } else if (warp == 1 && elect_one()) {
        mbar_wait(B(B_WR), 0);
#pragma unroll 1
        for (int i = 0; i < 6; i++) {
          const int c = i < 2 ? C_QKV + gq + (i ^ HSWAP) * 8 : C_CTX + (i >> 2) * 16 + ((i == 3 || i == 4) ? ti : 15 - ti);
          mbar_wait(B(B_PUB + i), 0);
          if (i >= 2 && i < 5) {
            asm volatile("fence.proxy.async.shared::cta;" ::: "memory");
#pragma unroll 1
            for (int n = 0; n < 8 / ST_G; n++) {
              const int h = n / (4 / ST_G), a = n % (4 / ST_G) * ST_G;
              asm volatile("cp.async.bulk.tensor.3d.global.shared::cta.bulk_group [%0, {%2,%3,%4}], [%1];" ::"l"(&p.ctx_st),
                           "r"(sb + (i == 4 ? 6 * SLOT + h * 16384 : (3 + 2 * h) * SLOT + (i - 2) * 16384) + a * 4096),
                           "r"(0), "r"((i == 2 ? 15 - ti : ti) * 128 + h * 64), "r"((hh + (i >> 2) * 16) * 4 + a) : "memory");
              asm volatile("cp.async.bulk.commit_group;\ncp.async.bulk.wait_group.read 0;" ::: "memory");
              if (ST_NS) __nanosleep(ST_NS);
            }
            mbar_arrive(B(B_QP + i - 2));
            asm volatile("cp.async.bulk.wait_group 0;" ::: "memory");
          }
          fence_gpu();
          red_add(&g_cnt[c], 1);
          TS(1 + i);
        }
      }
      if (warp == 2) {
#pragma unroll 1
        for (int n = 0; n < 8; n++) {
          if (!(n & 3)) mbar_wait(B(B_XE), n >> 2);
          if ((n < 4 || ffn) && elect_one()) {
            const uint32_t fb = B(n < 4 ? B_XF : B_WF2), d = sb + 6 * SLOT + (n & 3) * 8192;
            if (!(n & 3)) mbar_expect(fb, 32768);
            if (n < 4) tma_ld3(d, &p.x, fb, 0, mt * 128 + (n >> 1) * 64, gq * 2 + (n & 1));
            else tma_ld2(d, (n & 1) ? &p.wg : &p.wu, fb, fid * 32, (4 + (n >> 1)) * 128);
          }
          __nanosleep(SL_NS);
        }
#pragma unroll 1
        for (int i = XR_CAND + lane; i < XR_SIZE; i += 32) { xr[i] = make_uint4(~0u, ~0u, ~0u, ~0u); if (SET_NS) __nanosleep(SET_NS); }
        __syncwarp();
        if (lane == 0) { fence_gpu(); mbar_arrive(B(B_SET2)); }
        TL(2, 26, lane == 0);
        __syncwarp();
      }
      __syncwarp();
      if (warp == 3) {
        mbar_wait(B(B_OUT), 0);
        uint4 kv[2];
        poll_chunks(kv, g_xr + ((lane >> 1) * 8 + gq) * XR_SIZE + XR_KEY + (lane & 1) * 2, 1);
        const uint32_t a1 = max(kv[0].x, kv[0].z), a2 = max(min(kv[0].x, kv[0].z), max(kv[0].y, kv[0].w));
        const uint32_t b1 = max(kv[1].x, kv[1].z), b2 = max(min(kv[1].x, kv[1].z), max(kv[1].y, kv[1].w));
        const uint32_t k1 = max(a1, b1), k2 = max(min(a1, b1), max(a2, b2));
        const uint32_t m1 = __reduce_max_sync(~0u, k1);
        const uint32_t m2 = __reduce_max_sync(~0u, k1 == m1 ? k2 : k1);
        if (lane == 0) {
          *reinterpret_cast<uint2*>(sp + OFF_MISC) = make_uint2(m1, m2);
          mbar_arrive(B(B_OUT2));
        }
        const uint32_t key = (lane & 4) ? m2 : m1;
        const int tk = 0x7FFF - (key & 0x7FFF);
        const uint4* src = g_xr + ((tk >> 7) * 8 + (rid >> 4)) * XR_SIZE;
        poll_chunks(kv, src + XR_CAND + ((tk >> 4) & 7) * 64 + (((lane & 4) && !((m1 ^ m2) & 0x7FF0)) ? 16 : 0) + (rid & 12) + (lane & 3), 32);
        uint32_t u = key >> 16;
        u = (u & 0x8000u) ? (u & 0x7FFFu) : (~u & 0xFFFFu);
        const float rs = bf_round(__fdividef(1.f, 1.f + __expf(-__uint_as_float(u << 16))));
        if (lane < 8)
          *reinterpret_cast<uint4*>(sp + OFF_MISC + 128 + lane * 16) = make_uint4((rid & 2) ? ((rid & 1) ? kv[0].w : kv[0].z) : ((rid & 1) ? kv[0].y : kv[0].x),
              (rid & 2) ? ((rid & 1) ? kv[1].w : kv[1].z) : ((rid & 1) ? kv[1].y : kv[1].x), __float_as_uint(rs), 0);
        uint4 fl[1];
        poll_chunks(fl, src + XR_FLAG, 0);
        fence_gpu();
        __syncwarp();
        if (lane == 0) mbar_arrive(B(B_FIN));
      }
      if (warp == 1 && elect_one()) {
        mbar_wait(B(B_OUT3), 0);
#pragma unroll 1
        for (int n = 0; n < 4; n++) {
          asm volatile("cp.async.bulk.tensor.2d.global.shared::cta.bulk_group [%0, {%2,%3}], [%1];" ::"l"(&p.out), "r"(sb + OFF_STG + n * 8192),
                       "r"(gq * 128 + (n & 1) * 64), "r"(mt * 128 + (n >> 1) * 64) : "memory");
          asm volatile("cp.async.bulk.commit_group;" ::: "memory");
          if (OUT_P) asm volatile("cp.async.bulk.wait_group.read 0;" ::: "memory");
        }
        asm volatile("cp.async.bulk.wait_group 0;" ::: "memory");
        fence_async_all();
        fence_gpu();
        __stcg(xr + XR_FLAG, make_uint4(0, 0, 0, 0));
        TL(2, 25, true);
      }
    }
    __syncwarp();
    cluster_arrive();
    cluster_wait();
    TL_DUMP();
    if (tid == 32) TS(8);
  } else {
    reg_alloc<232>();
    const int w = wg - 1, cw = warp - 4;
    int lane = lane_id();
    const uint32_t stg = sb + OFF_STG + w * 16384 + (cw & 3) * 2048;
    auto publish = [&](int i) { __syncwarp(); if (lane == 0) mbar_arrive(B(B_PUB + i)); };
    auto release2 = [&](uint32_t b) { if (lane < 2) mbar_arrive_cta(b, lane); };
    float R[128];
    float O[64], acc[64];
    uint32_t pk[64];
    uint32_t* const Q = pk;
    uint32_t P[32];
    auto packed = [&](int i) {
      const float* v = R + 16 * (i >> 1) + 2 * (i & 1);
      return make_uint4(pack_bf16(v[0], v[1]), pack_bf16(v[4], v[5]), pack_bf16(v[8], v[9]), pack_bf16(v[12], v[13]));
    };
    const uint32_t q_st = sb + (cw & 3) * 1024 + (lane >> 2) * 64 + (((lane & 3) ^ (lane >> 3)) << 4);
    const uint32_t q_ld = sb + (cw & 3) * 1024 + (lane & 15) * 64 + (((lane >> 4) ^ ((lane >> 1) & 3)) << 4);
    auto park = [&](uint32_t off, int i, uint4 v) {
      asm volatile("st.shared.v4.u32 [%0], {%1,%2,%3,%4};" ::"r"(q_st + off + (i >> 1) * 4096 + (i & 1) * 512), "r"(v.x), "r"(v.y), "r"(v.z), "r"(v.w) : "memory");
    };
    auto load_q = [&](uint32_t off, int k) { ldsm4(Q + 4 * k, ((q_ld + off) ^ ((k & 1) << 5)) + (k >> 1) * 4096); };
    {
      TL(0, 1, tid == 128);
      __nv_bfloat16* pdst = g_qkv;
      uint64_t pol_f, pol_n, pol;
      asm("createpolicy.fractional.L2::evict_first.b64 %0, 1.0;" : "=l"(pol_f));
      asm("createpolicy.fractional.L2::evict_normal.b64 %0, 1.0;" : "=l"(pol_n));
      auto put = [&](int i) {
        if (STCS == 15) __stcs(reinterpret_cast<uint4*>(pdst + (i & 1) * 8 * NQ + (i >> 1) * 32), make_uint4(pk[4 * i], pk[4 * i + 1], pk[4 * i + 2], pk[4 * i + 3]));
        else asm volatile("st.global.L1::no_allocate.L2::cache_hint.v4.u32 [%0], {%1,%2,%3,%4}, %5;" ::"l"(pdst + (i & 1) * 8 * NQ + (i >> 1) * 32), "r"(pk[4 * i]), "r"(pk[4 * i + 1]), "r"(pk[4 * i + 2]), "r"(pk[4 * i + 3]), "l"(pol) : "memory");
      };
      const uint64_t da0 = mk_desc(sb + w * 8192, 16, 1024, 1);
      const uint64_t db0 = mk_desc(sb + 16384, 8192, 1024, 1);
      int st = 0; uint32_t ph = 0;
      auto issue = [&](int accum) {
        mbar_wait_c(B(B_FULL1 + st), ph);
        const uint64_t da = desc_add(da0, st * P1_STAGE), db = desc_add(db0, st * P1_STAGE);
        wg_fence();
#pragma unroll
        for (int k = 0; k < 4; k++) mma_n256_ss<1>(R, desc_add(da, k * 32), desc_add(db, k * 2048), k == 0 ? accum : 1);
        wg_commit();
      };
#pragma unroll 1
      for (int t = 0; t < 6; t++) {
        const int nk = t >= 4 ? 16 : 8;
        const bool tr = t > 0 && t < 5;
        issue(0);
        TL(0, 2 + 2 * t + 16 * w, (tid & 127) == 0);
        if (tr) { put(0); put(1); }
        int prev = st;
        if (++st == 4) { st = 0; ph ^= 1; }
#pragma unroll 1
        for (int kb = 1; kb < nk; kb++) {
          if (kb == nk - 1 && w == 1) bar_sync(5, 256);
          issue(1);
          if (kb == nk - 1 && w == 0) bar_arrive(5, 256);
          if (tr) {
#pragma unroll
            for (int i = 1; i < 8; i++) if (kb == i) { put(2 * i); put(2 * i + 1); }
            if (kb == 7 && !(t & 1)) publish((t >> 1) - 1);
          } else if (t == 5 && kb == 2) {
            mbar_wait_c(B(B_LND), 0);
#pragma unroll
            for (int i = 0; i < 8; i++) park(6 * SLOT + w * 16384, i, make_uint4(pk[4 * i], pk[4 * i + 1], pk[4 * i + 2], pk[4 * i + 3]));
            __syncwarp();
#pragma unroll
            for (int k = 0; k < 8; k++) load_q(6 * SLOT + w * 16384, k);
            __syncwarp();
#pragma unroll
            for (int i = 0; i < 8; i++) park(6 * SLOT + w * 16384, i, make_uint4(pk[32 + 4 * i], pk[33 + 4 * i], pk[34 + 4 * i], pk[35 + 4 * i]));
          }
          wg_wait<1>();
          release2(B(B_EMPTY1 + prev));
          prev = st;
          if (++st == 4) { st = 0; ph ^= 1; }
        }
        if (t == 5 && w == 1) bar_arrive(6, 256);
        pdst = g_qkv + (size_t)(((t & 1) + 1) * SEQ + mt * 128 + cw * 16 + (lane >> 2)) * NQ + (gq + ((t >> 1) ^ HSWAP) * 8) * 256 + (lane & 3) * 8;
        pol = ((STCS >> t) & 1) ? pol_f : pol_n;
        wg_wait<0>();
        fence_regs<128>(R);
        release2(B(B_EMPTY1 + prev));
        TL(0, 3 + 2 * t + 16 * w, (tid & 127) == 0);
        if (t == 5) break;
#pragma unroll
        for (int i = 0; i < 16; i++) { const uint4 v = packed(i); pk[4 * i] = v.x; pk[4 * i + 1] = v.y; pk[4 * i + 2] = v.z; pk[4 * i + 3] = v.w; }
      }
    }
    auto issue3 = [&](int st, uint32_t ph, int accum) {
      mbar_wait_c(B(B_FULL3 + st), ph);
      const uint64_t da = mk_desc(sb + OFF_R3 + w * 8192 + st * SLOT, 16, 1024, 1), db = mk_desc(sb + OFF_R3 + 16384 + st * SLOT, 8192, 1024, 1);
      wg_fence();
#pragma unroll
      for (int k = 0; k < 4; k++) mma_n128_ss<1>(acc, desc_add(da, k * 32), desc_add(db, k * 2048), k == 0 ? accum : 1);
      wg_commit();
    };
    uint32_t wf[128];
    auto w_addr = [&](uint32_t off, int m) {
      const uint32_t w_ld = sb + ((lane >> 3) & 1) * 8192 + ((cw >> 1) * 32 + (lane & 7) + (lane >> 4) * 8) * 64 + ((((cw & 1) * 2) ^ ((lane >> 1) & 3)) << 4);
      return ((w_ld + off) ^ ((m & 1) << 4)) + (m >> 2) * 16384 + ((m >> 1) & 1) * 1024;
    };
    auto grab = [&](uint32_t* d, uint32_t off, int m0, int m1) {
#pragma unroll
      for (int m = m0; m < m1; m++)
        asm volatile("ldmatrix.sync.aligned.m8n8.x4.trans.shared.b16 {%0,%1,%2,%3}, [%4];"
                     : "=r"(d[4 * m]), "=r"(d[4 * m + 1]), "=r"(d[4 * m + 2]), "=r"(d[4 * m + 3]) : "r"(w_addr(off, m)) : "memory");
    };
    float inv[2] = {0.f, 0.f};
    auto scaled = [&](int i) {
      const float* o = O + 16 * (i >> 1) + 2 * (i & 1);
      const float c = inv[i & 1];
      return make_uint4(pack_bf16(o[0] * c, o[1] * c), pack_bf16(o[4] * c, o[5] * c), pack_bf16(o[8] * c, o[9] * c), pack_bf16(o[12] * c, o[13] * c));
    };
    {
      const int wrow = cw * 16;
      const uint64_t dk0 = mk_desc(sb, 16, 1024, 1);
      const uint64_t dv0 = mk_desc(sb + 2 * SLOT, 16384, 1024, 1);
      const uint32_t pin = sb + OFF_MISC + 1028;
      float l0 = 0.f, l1 = 0.f;
      int g = 0, t = 0;
      uint32_t fail = 0;
      auto piece = [&](int tt) { return (uint32_t)(tt == 3 ? 6 * SLOT + w * 16384 : (3 + 2 * w) * SLOT + (tt - 1) * 16384); };
      uint32_t par = 0;
      auto issue_s = [&](float* S) {
        const uint64_t dk = desc_add(dk0, par * 16);
        mma_n128_rs0(S, Q, dk);
#pragma unroll
        for (int k = 1; k < 8; k++) mma_n128_rs<0>(S, Q + 4 * k, desc_add(dk, (k >> 2) * 16384 + (k & 3) * 32), 1);
        wg_commit();
      };
      auto issue_pv = [&](bool half, int accum) {
        const uint64_t dv = desc_add(dv0, ((g - 1) & 1) * 2 * SLOT);
        wg_fence();
#pragma unroll
        for (int k = 0; k < 4; k++) mma_n128_rs<1>(O, P + 4 * k, desc_add(dv, k * 2048), k == 0 ? accum : 1);
        wg_commit();
        if (UNLIKELY(half)) {
          wg_fence();
          wg_commit();
        } else {
          wg_fence();
#pragma unroll
          for (int k = 4; k < 8; k++) mma_n128_rs<1>(O, P + 4 * k, desc_add(dv, k * 2048), 1);
          wg_commit();
        }
        bar_arrive(2 - w, 256);
        wg_wait<2>();
        fence_regs<32>(Q);
      };
      uint32_t rel;
      asm("mapa.shared::cluster.u32 %0, %1, %2;" : "=r"(rel) : "r"(B(B_KE + 1)), "r"(lane & 1));
      auto release_k = [&]() {
        if (lane < 2) asm volatile("mbarrier.arrive.shared::cluster.b64 _, [%0];" ::"r"(rel) : "memory");
        rel ^= 8;
      };
      auto pv_done = [&]() {
        TC(g, 3);
        sched_fence(q_st);
        wg_wait<0>();
        fence_regs<64>(O); fence_regs<32>(P);
        TC(g, 4);
        if (lane < 2) asm volatile("mbarrier.arrive.shared::cluster.b64 _, [%0+16];" ::"r"(rel) : "memory");
      };
      auto row_inv = [&](bool go) {
        float a = l0 + __shfl_xor_sync(~0u, l0, 1), b = l1 + __shfl_xor_sync(~0u, l1, 1);
        a += __shfl_xor_sync(~0u, a, 2); b += __shfl_xor_sync(~0u, b, 2);
        const bool ok = __all_sync(~0u, a >= AT_LO && a <= AT_HI && b >= AT_LO && b <= AT_HI) != 0;
        asm("rcp.approx.ftz.f32 %0, %1;" : "=f"(inv[0]) : "f"(a));
        asm("rcp.approx.ftz.f32 %0, %1;" : "=f"(inv[1]) : "f"(b));
        fail |= (uint32_t)(go && !ok) << t;
        l0 = go ? 0.f : l0; l1 = go ? 0.f : l1;
        t += go;
      };
      {
        if (w == 0) { bar_arrive(7, 256); bar_sync(6, 256); } else { bar_arrive(1, 256); bar_sync(7, 256); }
#pragma unroll
        for (int i = 0; i < 8; i++) park(piece(1), i, packed(i));
        mbar_wait_c(B(B_KF), 0);
        bar_sync(1 + w, 256);
        float S[64];
        wg_fence();
        issue_s(S);
        bar_arrive(2 - w, 256);
        TL(1, 0, tid == 128);
#pragma unroll
        for (int i = 0; i < 8; i++) park(piece(2), i, packed(8 + i));
        wg_wait<0>();
        fence_regs<64>(S);
        release2(B(B_KE));
        TL(1, 1, tid == 128);
        at_exp<0, 16>(S);
        sched_fence(q_st);
        at_exp<16, 32>(S); at_fin<0, 16>(S, P);
        sched_fence(q_st);
        at_exp<32, 48>(S); at_fin<16, 32>(S, P);
        mbar_wait_f(B(B_KF + 1), 0);
        sched_fence(q_st);
        at_exp<48, 64>(S); at_fin<32, 64>(S, P);
        TL(1, 2, tid == 128);
      }
      const uint64_t m_first = 1ull | (1ull << (16 - ti)) | (1ull << 17) | (1ull << (18 + ti));
      const uint64_t m_diag = (3ull << (15 - ti)) | (3ull << (17 + ti));
      enum { F_FIRST = 1, F_DIAG = 2, F_LAST = 4, F_PFIRST = 8, F_PHALF = 16, F_STOP = 32 };
      auto kind = [&](int gn) {
        const uint32_t a = (uint32_t)((m_first << 1) >> gn), d = (uint32_t)((m_diag << 1) >> gn);
        return ((a >> 1) & 1) * F_FIRST | ((d >> 1) & 1) * F_DIAG | ((a >> 2) & 1) * F_LAST | (a & 1) * F_PFIRST |
               (w == 0 ? (d & 1) * F_PHALF | ((d >> 1) & 1) * F_STOP : 0) | (gn == 34 ? F_STOP : 0);
      };
      const uint32_t kinds = pinned(kind(lane + 3));
      uint32_t f = F_PFIRST, fn;
      auto shadow = [&]() {
        const bool vok = mbar_try(B(B_VF + ((g - 1) & 1)), ((g - 1) >> 1) & 1);
        at_sum(P, f & F_PHALF, l0, l1);
        fn = __shfl_sync(~0u, kinds, max(g - 2, 0));
        if (UNLIKELY(!vok)) mbar_wait_c(B(B_VF + ((g - 1) & 1)), ((g - 1) >> 1) & 1);
      };
      auto hand_over = [&]() { __syncwarp(); if (lane == 0 && !((fail >> (t - 1)) & 1)) mbar_arrive(B(B_PUB + 1 + t)); };
      auto exp_q = [&](float* S, auto kc, auto nc) {
        constexpr int k = decltype(kc)::value, n = decltype(nc)::value;
        asm volatile("{\n.reg .pred p;\nsetp.ne.b32 p, %5, 0;\n@p ldmatrix.sync.aligned.m8n8.x4.shared.b16 {%0,%1,%2,%3}, [%4];\n}"
                     : "+r"(Q[4 * k]), "+r"(Q[4 * k + 1]), "+r"(Q[4 * k + 2]), "+r"(Q[4 * k + 3])
                     : "r"(((q_ld + piece(t + 1)) ^ ((k & 1) << 5)) + (k >> 1) * 4096), "r"(f & F_LAST) : "memory");
        at_exp<n * k, n * k + n>(S);
      };
      g = 1; par = SLOT / 16;
#pragma unroll 1
      for (;;) {
        {
          TC(g, 0); TC(g - 1, 6);
          bar_sync(1 + w, 256);
          fence_regs<32>(Q);
          float S[64];
          wg_fence();
          issue_s(S);
          sched_fence(q_st);
          TC(g, 1);
          shadow();
          fence_regs<64>(O); fence_regs<32>(P);
          issue_pv(f & F_PHALF, ~f & F_PFIRST);
          fence_regs<64>(S);
          TC(g, 2);
          release_k();
          at_exp<0, 8>(S);
          const bool first = f & F_FIRST;
          if (UNLIKELY(f & (F_FIRST | F_LAST))) {
            row_inv(first);
            at_mask(S + 32, (f & F_DIAG) ? wrow - 64 : 64, lane);
            unroll8([&](auto kc) { exp_q(S + 8, kc, std::integral_constant<int, AT_R1 / 8 - 1>{}); });
          } else {
            at_exp<8, AT_R1>(S);
          }
          pv_done();
          g = pinned(g + 1); par = pinned(par ^ (SLOT / 16)); f = fn;
          const bool kok = mbar_try(B(B_KF + (g & 1)), g < 34 ? (g >> 1) & 1 : 0);
          if (UNLIKELY(first)) {
            unroll8([&](auto ic) {
              constexpr int i = decltype(ic)::value, n = (64 - AT_R1) / 8;
              at_exp<AT_R1 + n * i, AT_R1 + n * i + n>(S);
              park(piece(t), i, scaled(i));
            });
            at_fin<0, 64>(S, P);
            hand_over();
          } else {
            at_exp<AT_R1, 64>(S); at_fin<0, 64>(S, P);
          }
          TC(g - 1, 5);
          if (!TCLK) TL(1, 1 + g, tid == 128);
          if (kok && !(f & F_STOP)) continue;
          if (g == 34) break;
          mbar_wait_c(B(B_KF + (g & 1)), (g >> 1) & 1);
        }
#pragma unroll 1
        while (f & F_STOP) {
          TC(g, 0); TC(g - 1, 6);
          shadow();
          const bool first = f & F_FIRST;
          row_inv(first);
          bar_sync(1, 256);
          fence_regs<64>(O); fence_regs<32>(Q); fence_regs<32>(P);
          float S[32];
          const uint64_t dk = desc_add(dk0, par * 16);
          wg_fence();
          mma_n64_rs0(S, Q, dk);
#pragma unroll
          for (int k = 1; k < 8; k++) mma_n64_rs(S, Q + 4 * k, desc_add(dk, (k >> 2) * 16384 + (k & 3) * 32), 1);
          wg_commit();
          TC(g, 1);
          issue_pv(f & F_PHALF, ~f & F_PFIRST);
          fence_regs<32>(S);
          TC(g, 2);
          release_k();
          if (H_LATE) pv_done();
          sched_fence(q_st);
          at_mask(S, wrow, lane);
          unroll8([&](auto kc) { exp_q(S, kc, std::integral_constant<int, 4>{}); });
          if (!H_LATE) pv_done();
          g++; par ^= SLOT / 16; f = fn;
          at_fin<0, 32>(S, P);
          if (first) {
#pragma unroll
            for (int i = 0; i < 8; i++) park(piece(t), i, scaled(i));
            hand_over();
          }
          TC(g - 1, 5);
          if (!TCLK) TL(1, 1 + g, tid == 128);
          mbar_wait_c(B(B_KF + (g & 1)), (g >> 1) & 1);
        }
      }
      TCF();
      const bool wok = mbar_test(B(ffn ? B_WF : B_QP + 1), 0);
      grab(wf, 3 * SLOT, 0, 8);
      mbar_wait_c(B(B_VF + 1), 0);
      bar_sync(1 + w, 256);
      fence_regs<64>(O); fence_regs<32>(P);
      wg_fence();
#pragma unroll
      for (int k = 0; k < 8; k++) mma_n128_rs<1>(O, P + 4 * k, desc_add(dv0, 2 * SLOT + k * 2048), 1);
      wg_commit();
      if (w == 0) bar_arrive(2, 256);
      pin_order(__uint_as_float(wf[28] & wf[24]), pin);
      __syncwarp();
      if (wok) release2(B(B_WE));
      TL(3, 12 + 16 * w, (tid & 127) == 0);
      sched_fence(q_st);
      at_sum(P, false, l0, l1);
      row_inv(true);
      sched_fence(q_st);
      wg_wait<0>();
      fence_regs<64>(O); fence_regs<32>(P);
      release2(B(B_VE + 1));
      if (UNLIKELY(!wok || fail != 0)) {
#pragma unroll 1
        for (int tt = 0; tt < 4; tt++) {
          if (!((tt < 3 ? fail >> tt : fail != 0) & 1)) continue;
          slow_tile(O, P, l0, l1, wq, (((tt + 1) & 2) ? ti : 15 - ti) * 128 + wrow, hh + (tt & 2) * 8, lane, q_st);
          row_inv(false);
          if (tt < 3) {
#pragma unroll
            for (int i = 0; i < 8; i++) park(piece(tt + 1), i, scaled(i));
            publish(2 + tt);
          }
        }
        if (!wok) {
          mbar_wait_c(B(ffn ? B_WF : B_QP + 1), 0);
          grab(wf, 3 * SLOT, 0, 8);
          pin_order(__uint_as_float(wf[28] & wf[24]), pin);
          __syncwarp();
          release2(B(B_WE));
        }
      }
      TL(3, 13 + 16 * w, (tid & 127) == 0);
      issue3(0, 0, 0);
      TL(3, 14 + 16 * w, (tid & 127) == 0);
      TL(1, 36, tid == 128);
    }
    uint32_t hp[32];
    lane = lane_id();
    {
      int st = 1, prev = 0; uint32_t ph = 0;
      __nv_bfloat16* dst = g_qkv + (size_t)((15 - ti) * 128 + cw * 16 + (lane >> 2)) * NQ + (hh + 16) * 128 + (lane & 3) * 8;
      auto kblock = [&](auto between, int lim = 6) {
        issue3(st, ph, 1);
        between();
        wg_wait<1>();
        release2(B(B_EMPTY3 + prev));
        prev = st;
        if (++st == lim) { st = 0; ph ^= 1; }
      };
      kblock([&]() { TL(3, 15 + 16 * w, (tid & 127) == 0); });
      kblock([&]() { grab(wf + 32, 5 * SLOT, 0, 8); TL(3, 16 + 16 * w, (tid & 127) == 0); });
#pragma unroll 1
      for (int kb = 3; kb < 11; kb++) {
        kblock([&]() {
#pragma unroll
          for (int i = 0; i < 8; i++) if (kb == i + 3) *reinterpret_cast<uint4*>(dst + (i & 1) * 8 * NQ + (i >> 1) * 32) = scaled(i);
          TL(3, 14 + kb + 16 * w, (tid & 127) == 0);
          if (kb == 8) TL(2, 2, tid == 128);
        }, kb == 4 ? 5 : 6);
        if (kb == 4) release2(B(B_EMPTY3 + 5));
      }
      publish(5);
      kblock([&]() { mbar_wait_c(B(ffn ? B_WF2 : B_QP + 2), 0); grab(wf + 32, 5 * SLOT, 8, 16); });
#pragma unroll 1
      for (int kb = 12; kb < G_KB; kb++) {
        kblock([&]() { if ((kb & 7) == 0) TL(2, 1 + (kb >> 3), tid == 128); });
        if (kb == X_KB && lane == 0) mbar_arrive(B(B_XE));
      }
      kblock([&]() {
        mbar_wait_c(B(B_XF), 0);
#pragma unroll
        for (int i = 0; i < 8; i++)
          ldsm4(hp + 4 * i, sb + 6 * SLOT + w * 16384 + ((cw & 3) * 16 + (lane & 15)) * 128 + (i >> 2) * 8192 + ((((i & 3) * 2 + (lane >> 4)) ^ (lane & 7)) << 4));
      });
#pragma unroll 1
      for (int kb = G_KB + 1; kb < 64; kb++) {
        kblock([&]() { if ((kb & 7) == 0) TL(2, 1 + (kb >> 3), tid == 128); });
        if (kb == G_KB + 2 && lane == 0) mbar_arrive(B(B_XE));
      }
    }
    lane = lane_id();
    const int r0 = lane >> 2, q4 = lane & 3, ct = cw * 32 + lane;
    uint32_t tb[16];
    mbar_wait_c(B(B_WR), 0);
#pragma unroll
    for (int i = 0; i < 4; i++) ldsm4(tb + 4 * i, sb + OFF_MISC + 512 + (lane & 1) * 256 + (lane >> 3) * 16 + i * 64);
    mbar_wait_c(B(B_SET2), 0);
    float4* const psd = reinterpret_cast<float4*>(xr + XR_PS + cw * 16 + r0);
    const uint4* const pss = g_xr + (mt * 8 + (ct & 1) * 4) * XR_SIZE + XR_PS + (ct >> 1);
    sched_fence(stg);
    wg_wait<0>();
    fence_regs<64>(acc);
    TL(2, 10, tid == 128);
    {
      float d[2][4] = {}, qa[2][4] = {}, qb[2][4] = {};
#pragma unroll
      for (int j = 0; j < 16; j++) {
        hp[2 * j] = hadd2_bf(hp[2 * j], pack_bf16(acc[4 * j], acc[4 * j + 1]));
        hp[2 * j + 1] = hadd2_bf(hp[2 * j + 1], pack_bf16(acc[4 * j + 2], acc[4 * j + 3]));
        if (j & 1) {
          mma16816(d[(j >> 1) & 1], hp[2 * j - 2], hp[2 * j - 1], hp[2 * j], hp[2 * j + 1], tb[j - 1], tb[j]);
          mma16816(qa[(j >> 1) & 1], hp[2 * j - 2], hp[2 * j - 1], hp[2 * j], hp[2 * j + 1], hp[2 * j - 2], hp[2 * j]);
          mma16816(qb[(j >> 1) & 1], hp[2 * j - 2], hp[2 * j - 1], hp[2 * j], hp[2 * j + 1], hp[2 * j - 1], hp[2 * j + 1]);
        }
      }
      if (q4 == (r0 >> 1)) {
        __stcg(psd, make_float4(d[0][0] + d[1][0], (r0 & 1) ? qa[0][1] + qa[1][1] : qa[0][0] + qa[1][0], d[0][1] + d[1][1], 0.f));
        __stcg(psd + 8, make_float4(d[0][2] + d[1][2], (r0 & 1) ? qb[0][3] + qb[1][3] : qb[0][2] + qb[1][2], d[0][3] + d[1][3], 0.f));
      }
    }
    TL(2, 11, tid == 128);
    mbar_wait_c(B(B_EMPTY3 + 1), 0);
    stage_store_128(stg, lane, hp);
    if (ffn) mbar_wait_c(B(B_WF2), 1);
    grab(wf + 96, 6 * SLOT, 0, 8);
    const float wsum = *reinterpret_cast<const float*>(sp + OFF_MISC + 1024);
    __syncwarp();
    {
      uint4 ps[4];
      poll_chunks(ps, pss, XR_SIZE);
      TL(2, 12, tid == 128);
      auto F = [](uint32_t u) { return __uint_as_float(u); };
      float s1 = (F(ps[0].x) + F(ps[1].x)) + (F(ps[2].x) + F(ps[3].x)), s2 = (F(ps[0].y) + F(ps[1].y)) + (F(ps[2].y) + F(ps[3].y));
      float s3 = (F(ps[0].z) + F(ps[1].z)) + (F(ps[2].z) + F(ps[3].z));
      __syncwarp();
      s1 += __shfl_xor_sync(~0u, s1, 1); s2 += __shfl_xor_sync(~0u, s2, 1); s3 += __shfl_xor_sync(~0u, s3, 1);
      const float mean = s1 * (1.f / DM);
      float mb, inv;
      ln_round(mean, fmaxf(fmaf(s2, 1.f / DM, -mean * mean), 0.f), mb, inv);
      uint32_t u = pack_bf16((s3 - mb * wsum) * inv, 0.f);
      if (u == 0x8000u) u = 0;
      u = (u & 0x8000u) ? (~u & 0xFFFFu) : (u | 0x8000u);
      const uint32_t key = (u << 16) | (0x7FFFu - (mt * 128 + (ct >> 1)));
      const uint32_t nm2 = pack_bf16(-mb, -mb);
      const uint32_t c1 = __reduce_max_sync(~0u, key);
      const uint32_t c2 = __reduce_max_sync(~0u, key == c1 ? 0u : key);
      if (lane == 0) {
        __stcg(reinterpret_cast<uint2*>(xr + XR_KEY) + cw, make_uint2(c1, c2));
        mbar_arrive(B(B_OUT));
      }
      TL(2, 13, tid == 128);
      const int row = (0x7FFF - (((lane >> 4) ? c2 : c1) & 0x7FFF)) & 15;
      const uint32_t rn = __shfl_sync(~0u, nm2, row * 2);
      const float ri = __shfl_sync(~0u, inv, row * 2);
      uint32_t v[4];
#pragma unroll
      for (int i = 0; i < 4; i++)
        asm volatile("ld.shared.u32 %0, [%1];" : "=r"(v[i]) : "r"(stg + ((lane >> 3) & 1) * 8192 + row * 128 + ((((lane & 4) + i) ^ (row & 7)) << 4) + q4 * 4) : "memory");
      __stcg(xr + XR_CAND + cw * 64 + 32 + lane, make_uint4(ln_apply(v[0], rn, ri), ln_apply(v[1], rn, ri), ln_apply(v[2], rn, ri), ln_apply(v[3], rn, ri)));
      __stcg(xr + XR_CAND + cw * 64 + lane, make_uint4(v[0], v[1], v[2], v[3]));
      sched_fence(stg);
      const uint32_t na = __shfl_sync(~0u, nm2, r0 * 2), nb = __shfl_sync(~0u, nm2, r0 * 2 + 16);
      const float ia = __shfl_sync(~0u, inv, r0 * 2), ib = __shfl_sync(~0u, inv, r0 * 2 + 16);
#pragma unroll
      for (int i = 0; i < 32; i++) hp[i] = hadd2_bf(hp[i], ln_apply(hp[i], (i & 1) ? nb : na, (i & 1) ? ib : ia));
      __syncwarp();
      stage_store_128(stg, lane, hp);
      asm volatile("fence.proxy.async.shared::cta;" ::: "memory");
      publish(B_OUT3 - B_PUB);
    }
    uint32_t wd[16][4];
    sched_fence(stg);
    if (ffn) mbar_wait_c(B(B_FULL3 + 5 * w), 1 - w);
    auto load_wd = [&](int h) {
#pragma unroll
      for (int i = h; i < 16; i += 2)
        asm volatile("ldmatrix.sync.aligned.m8n8.x4.trans.shared.b16 {%0,%1,%2,%3}, [%4];"
                     : "=r"(wd[i][0]), "=r"(wd[i][1]), "=r"(wd[i][2]), "=r"(wd[i][3])
                     : "r"(sb + OFF_R3 + 5 * w * SLOT + (2 * (cw & 3) + (i >> 3)) * 4096 + (h * 16 + (lane & 7) + (lane >> 4) * 8) * 128 +
                           (((2 * ((i >> 1) & 3) + ((lane >> 3) & 1)) ^ (lane & 7)) << 4)) : "memory");
    };
    load_wd(0);
    __syncwarp();
    cluster_arrive();
    TL(2, 22, tid == 128);
    mbar_wait_c(B(B_OUT2), 0);
    const uint2 top = *reinterpret_cast<const uint2*>(sp + OFF_MISC);
    TL(2, 14, tid == 128);
    const int t0 = 0x7FFF - (top.x & 0x7FFF), t1 = 0x7FFF - (top.y & 0x7FFF);
    auto cand = [&](int second) {
      const int tk = second ? t1 : t0;
      return g_xr + (tk >> 7) * 8 * XR_SIZE + XR_CAND + ((tk >> 4) & 7) * 64 + ((second && (t0 >> 4) == (t1 >> 4)) ? 16 : 0);
    };
    if (ffn) {
      uint4 xb[2];
      poll_chunks(xb, cand(r0 & 1) + (r0 >> 1) * XR_SIZE + 32 + (cw >> 1) * 4 + q4, 4 * XR_SIZE);
      __syncwarp();
      TL(2, 15, tid == 128);
      float d[8][4] = {};
#pragma unroll
      for (int n = 0; n < 32; n++) {
        if (n == WD_AT) { sched_fence(stg); load_wd(1); }
        const int s = (n >> 4) * 4 + ((n >> 1) & 3), m = ((n >> 3) & 1) * 2 + (n & 1);
        const uint32_t* a = wf + 16 * s + 4 * m;
        mma16816(d[n & 7], a[0], a[1], a[2], a[3], (m & 2) ? xb[s >> 2].z : xb[s >> 2].x, (m & 2) ? xb[s >> 2].w : xb[s >> 2].y);
      }
      float v[8];
#pragma unroll
      for (int i = 0; i < 8; i++) {
        const float lo = (q4 & 1) ? d[2 + (i >> 2)][i & 3] : d[i >> 2][i & 3], hi = (q4 & 1) ? d[6 + (i >> 2)][i & 3] : d[4 + (i >> 2)][i & 3];
        v[i] = (q4 & 2) ? hi : lo;
      }
#pragma unroll
      for (int i = 0; i < 4; i++) v[i] = ((q4 & 2) ? v[i + 4] : v[i]) + __shfl_xor_sync(~0u, (q4 & 2) ? v[i] : v[i + 4], 2);
#pragma unroll
      for (int i = 0; i < 2; i++) v[i] = ((q4 & 1) ? v[i + 2] : v[i]) + __shfl_xor_sync(~0u, (q4 & 1) ? v[i] : v[i + 2], 1);
      float4* red = reinterpret_cast<float4*>(sp + SL_SCR * SLOT);
      reinterpret_cast<float2*>(red + cw * 16 + (q4 >> 1) * 8 + r0)[q4 & 1] = make_float2(v[0], v[1]);
      bar_sync(3, 256);
      TL(2, 16, tid == 128);
      const float4 z0 = red[lane], z1 = red[32 + lane], z2 = red[64 + lane], z3 = red[96 + lane];
      const uint32_t ub = pack_bf16((z0.x + z1.x) + (z2.x + z3.x), (z0.y + z1.y) + (z2.y + z3.y));
      const uint32_t gb = pack_bf16((z0.z + z1.z) + (z2.z + z3.z), (z0.w + z1.w) + (z2.w + z3.w));
      const float g0 = bf_lo(gb), g1 = bf_hi(gb);
      const uint32_t sg = pack_bf16(__fdividef(g0, 1.f + __expf(-g0)), __fdividef(g1, 1.f + __expf(-g1)));
      const uint32_t act = pack_bf16(bf_lo(sg) * bf_lo(ub), bf_hi(sg) * bf_hi(ub));
      const uint32_t pr = __byte_perm(act, __shfl_xor_sync(~0u, act, 1), (lane & 1) ? 0x3276 : 0x5410);
      const int src = q4 * 2 + (r0 & 1);
      const uint32_t a0 = __shfl_sync(~0u, pr, src), a1 = __shfl_sync(~0u, pr, src + 8), a2 = __shfl_sync(~0u, pr, src + 16), a3 = __shfl_sync(~0u, pr, src + 24);
      TL(2, 17, tid == 128);
      float y[8][4] = {};
#pragma unroll
      for (int i = 0; i < 8; i++) mma16816(y[i], wd[2 * i][0], wd[2 * i][1], wd[2 * i][2], wd[2 * i][3], a0, a1);
#pragma unroll
      for (int i = 0; i < 8; i++) mma16816(y[i], wd[2 * i + 1][0], wd[2 * i + 1][1], wd[2 * i + 1][2], wd[2 * i + 1][3], a2, a3);
      float2* yd = reinterpret_cast<float2*>(g_xr + (cw * 16 + 2 * q4) * XR_SIZE + XR_Y + fid * 4) + r0;
#pragma unroll
      for (int j = 0; j < 2; j++) {
        float v[4];
#pragma unroll
        for (int e = 0; e < 4; e++) {
          const float lo = (q4 & 1) ? y[4 * j + 1][e] : y[4 * j][e], hi = (q4 & 1) ? y[4 * j + 3][e] : y[4 * j + 2][e];
          v[e] = (q4 & 2) ? hi : lo;
        }
        __stcg(yd + j * 16 * XR_SIZE, make_float2(v[0], v[1]));
        __stcg(yd + j * 16 * XR_SIZE + 2 * XR_SIZE, make_float2(v[2], v[3]));
      }
    }
    TL(2, 18, tid == 128);
    if (rid == 127 && ct < C_NUM) g_cnt[ct] = 0;
    if (cw < 2) {
      const int tok = (lane >> 1) & 1, pair = cw * 2 + (lane & 1);
      uint4 z[7];
      poll_chunks(z, xr + XR_Y + (lane >> 1) * 4 + pair, 64);
      __syncwarp();
      TL(2, 19, tid == 128);
      mbar_wait_c(B(B_FIN), 0);
      const uint4 op = lds128(sb + OFF_MISC + 128 + (tok * 4 + pair) * 16);
      auto F = [](uint32_t u) { return __uint_as_float(u); };
      const float v0 = ((F(z[0].x) + F(z[1].x)) + (F(z[2].x) + F(z[3].x))) + ((F(z[4].x) + F(z[5].x)) + F(z[6].x));
      const float v1 = ((F(z[0].y) + F(z[1].y)) + (F(z[2].y) + F(z[3].y))) + ((F(z[4].y) + F(z[5].y)) + F(z[6].y));
      const float v2 = ((F(z[0].z) + F(z[1].z)) + (F(z[2].z) + F(z[3].z))) + ((F(z[4].z) + F(z[5].z)) + F(z[6].z));
      const float v3 = ((F(z[0].w) + F(z[1].w)) + (F(z[2].w) + F(z[3].w))) + ((F(z[4].w) + F(z[5].w)) + F(z[6].w));
      float ya = (tok ? v1 : v0) + __shfl_xor_sync(~0u, tok ? v0 : v1, 2), yb = (tok ? v3 : v2) + __shfl_xor_sync(~0u, tok ? v2 : v3, 2);
#pragma unroll
      for (int o = 4; o < 32; o <<= 1) { ya += __shfl_xor_sync(~0u, ya, o); yb += __shfl_xor_sync(~0u, yb, o); }
      const uint32_t yp = pack_bf16(ya, yb);
      if (lane < 4) reinterpret_cast<uint32_t*>(out + (size_t)(tok ? t1 : t0) * DM)[rid * 4 + pair] = hadd2_bf(op.x, hadd2_bf(op.y, pack_bf16(bf_lo(yp) * F(op.z), bf_hi(yp) * F(op.z))));
      TL(2, 21, tid == 128);
    }
    TL(2, 20, tid == 128);
    __syncwarp();
    cluster_wait();
    TL_DUMP();
  }
}

typedef CUresult (*EncodeFn)(CUtensorMap*, CUtensorMapDataType, cuuint32_t, void*, const cuuint64_t*, const cuuint64_t*, const cuuint32_t*,
                             const cuuint32_t*, CUtensorMapInterleave, CUtensorMapSwizzle, CUtensorMapL2promotion, CUtensorMapFloatOOBfill);
EncodeFn g_enc = nullptr;

void map2(CUtensorMap* m, const void* ptr, uint64_t rows, uint64_t cols, uint32_t bc, uint32_t br) {
  const CUtensorMapSwizzle sw = bc == 64 ? CU_TENSOR_MAP_SWIZZLE_128B : CU_TENSOR_MAP_SWIZZLE_64B;
  cuuint64_t gd[2] = {cols, rows}, gs[1] = {cols * 2};
  cuuint32_t bd[2] = {bc, br}, es[2] = {1, 1};
  g_enc(m, CU_TENSOR_MAP_DATA_TYPE_BFLOAT16, 2, (void*)ptr, gd, gs, bd, es, CU_TENSOR_MAP_INTERLEAVE_NONE, sw,
        CU_TENSOR_MAP_L2_PROMOTION_L2_128B, CU_TENSOR_MAP_FLOAT_OOB_FILL_NONE);
}
void map3(CUtensorMap* m, const void* ptr, uint64_t rows, uint64_t cols, uint32_t br, uint32_t bch, uint32_t bc = 64) {
  cuuint64_t gd[3] = {bc, rows, cols / bc}, gs[2] = {cols * 2, bc * 2};
  cuuint32_t bd[3] = {bc, br, bch}, es[3] = {1, 1, 1};
  g_enc(m, CU_TENSOR_MAP_DATA_TYPE_BFLOAT16, 3, (void*)ptr, gd, gs, bd, es, CU_TENSOR_MAP_INTERLEAVE_NONE, bc == 64 ? CU_TENSOR_MAP_SWIZZLE_128B : CU_TENSOR_MAP_SWIZZLE_64B,
        CU_TENSOR_MAP_L2_PROMOTION_L2_128B, CU_TENSOR_MAP_FLOAT_OOB_FILL_NONE);
}

}

extern "C" void kernel_launch(void* const* d_in, const int* in_sizes, int n_in, void* d_out, int out_size) {
  const __nv_bfloat16* x = (const __nv_bfloat16*)d_in[0];
  const __nv_bfloat16* ckv = (const __nv_bfloat16*)d_in[1];
  const __nv_bfloat16* wq = (const __nv_bfloat16*)d_in[2];
  const __nv_bfloat16* wk = (const __nv_bfloat16*)d_in[3];
  const __nv_bfloat16* wv = (const __nv_bfloat16*)d_in[4];
  const __nv_bfloat16* wo = (const __nv_bfloat16*)d_in[5];
  const __nv_bfloat16* w_r = (const __nv_bfloat16*)d_in[7];
  const __nv_bfloat16* wgate = (const __nv_bfloat16*)d_in[8];
  const __nv_bfloat16* wup = (const __nv_bfloat16*)d_in[9];
  const __nv_bfloat16* wdown = (const __nv_bfloat16*)d_in[10];
  __nv_bfloat16* out = (__nv_bfloat16*)d_out;

  if (!g_enc) {
    void* fn = nullptr;
    cudaDriverEntryPointQueryResult qr;
    cudaGetDriverEntryPoint("cuTensorMapEncodeTiled", &fn, cudaEnableDefault, &qr);
    g_enc = (EncodeFn)fn;
    cudaFuncSetAttribute(fused_kernel, cudaFuncAttributeMaxDynamicSharedMemorySize, SMEM_BYTES);
  }
  void *xn, *qkv;
  cudaGetSymbolAddress(&xn, g_xn);
  cudaGetSymbolAddress(&qkv, g_qkv);

  Params p;
  map2(&p.xn, xn, SEQ, DM, 64, 128);
  map2(&p.ckv, ckv, SEQ, DC, 64, 128);
  map3(&p.wq, wq, DM, NQ, 64, 2);
  map3(&p.wk, wk, DC, NQ, 64, 2);
  map3(&p.wv, wv, DC, NQ, 64, 2);
  map3(&p.kv, qkv, 3 * SEQ, NQ, 128, 1);
  map2(&p.ctx_ld, qkv, SEQ, NQ, 64, 128);
  map3(&p.ctx_st, qkv, SEQ, NQ, 64, ST_G, 32);
  map3(&p.wo, wo, NQ, DM, 64, 1);
  map3(&p.x, x, SEQ, DM, 64, 1);
  map3(&p.wd, wdown, FF, DM, 32, 8);
  map2(&p.out, out, SEQ, DM, 64, 64);
  map2(&p.wg, wgate, DM, FF, 32, 128);
  map2(&p.wu, wup, DM, FF, 32, 128);
  fused_kernel<<<128, 384, SMEM_BYTES, cudaStreamPerThread>>>(p, x, wq, w_r, out);
}
```

```cpp
#include <cuda_runtime.h>
#include <cuda_bf16.h>
#include <cuda.h>
#include <stdint.h>
#include <type_traits>

#pragma nv_diag_suppress 549
namespace {

constexpr int SEQ = 2048, DM = 1024, NH = 32, HD = 128, DC = 512, NQ = NH * HD, FF = 3584;

__device__ __align__(1024) __nv_bfloat16 g_xn[SEQ * DM];
__device__ __align__(1024) __nv_bfloat16 g_qkv[3 * SEQ * NQ];
constexpr int XR_PS = 0;
constexpr int XR_KEY = 128;
constexpr int XR_FLAG = 132;
constexpr int XR_CAND = 136;
constexpr int XR_Y = 648;
constexpr int XR_SIZE = 1104;
__device__ __align__(1024) uint4 g_xr[128 * XR_SIZE];
constexpr int C_LN = 0, C_QKV = 16, C_CTX = 32, C_NUM = 64;
__device__ unsigned g_cnt[C_NUM];

#define TL(k, i, cond) do {} while (0)
#define TL_BYTES 0
#define TL_INIT() do {} while (0)
#define TL_DUMP() do {} while (0)
#define TC(g, i) do {} while (0)
#define TCF() do {} while (0)
#define TS(i) do {} while (0)
#undef TCLK
#define TCLK 0

__device__ __forceinline__ uint32_t s2u(const void* p) { return (uint32_t)__cvta_generic_to_shared(p); }
__device__ __forceinline__ void mbar_init(uint32_t b, uint32_t c) { asm volatile("mbarrier.init.shared::cta.b64 [%0], %1;" ::"r"(b), "r"(c) : "memory"); }
__device__ __forceinline__ void mbar_expect(uint32_t b, uint32_t bytes) { asm volatile("mbarrier.arrive.expect_tx.shared::cta.b64 _, [%0], %1;" ::"r"(b), "r"(bytes) : "memory"); }
__device__ __forceinline__ void mbar_arrive(uint32_t b) { asm volatile("mbarrier.arrive.shared::cta.b64 _, [%0];" ::"r"(b) : "memory"); }
__device__ __forceinline__ bool mbar_test(uint32_t b, uint32_t ph) {
  uint32_t ok;
  asm volatile("{\n.reg .pred p;\nmbarrier.test_wait.parity.shared::cta.b64 p, [%1], %2;\nselp.u32 %0, 1, 0, p;\n}" : "=r"(ok) : "r"(b), "r"(ph) : "memory");
  return ok;
}
__device__ __forceinline__ void mbar_wait(uint32_t b, uint32_t ph) {
  asm volatile(
      "{\n.reg .pred p;\n.reg .u32 n;\nmov.u32 n, 0;\n"
      "LW:\nmbarrier.try_wait.parity.shared::cta.b64 p, [%0], %1, 20000;\n@p bra LD;\n"
      "add.u32 n, n, 1;\nsetp.lt.u32 p, n, 0x40000;\n@p bra LW;\ntrap;\nLD:\n}" ::"r"(b), "r"(ph) : "memory");
}
__device__ __forceinline__ void mbar_wait_c(uint32_t b, uint32_t ph) {
  asm volatile(
      "{\n.reg .pred p;\n.reg .u32 n;\nmov.u32 n, 0;\n"
      "LW:\nmbarrier.try_wait.parity.shared::cta.b64 p, [%0], %1;\n@p bra LD;\n"
      "add.u32 n, n, 1;\nsetp.lt.u32 p, n, 0x100000;\n@p bra LW;\ntrap;\nLD:\n}" ::"r"(b), "r"(ph) : "memory");
}
__device__ __forceinline__ bool mbar_try(uint32_t b, uint32_t ph) {
  uint32_t ok;
  asm volatile("{\n.reg .pred p;\nmbarrier.try_wait.parity.shared::cta.b64 p, [%1], %2;\nselp.u32 %0, 1, 0, p;\n}" : "=r"(ok) : "r"(b), "r"(ph) : "memory");
  return ok;
}
#define UNLIKELY(c) __builtin_expect(!!(c), 0)
__device__ __forceinline__ uint32_t pinned(uint32_t v) { uint32_t r; asm volatile("mov.b32 %0, %1;" : "=r"(r) : "r"(v)); return r; }
__device__ __forceinline__ bool elect_one() {
  uint32_t p;
  asm volatile("{\n.reg .pred p;\nelect.sync _|p, 0xFFFFFFFF;\nselp.u32 %0, 1, 0, p;\n}" : "=r"(p));
  return p;
}
__device__ __forceinline__ int lane_id() { int r; asm volatile("mov.u32 %0, %%laneid;" : "=r"(r)); return r; }
template <bool SLEEP = false>
__device__ __forceinline__ void spin_until_ge(const unsigned* p, unsigned target) {
  asm volatile(
      "{\n.reg .pred p, q;\n.reg .u32 n, v;\nmov.u32 n, 0;\nsetp.ne.u32 q, %2, 0;\n"
      "LW:\nld.acquire.gpu.global.u32 v, [%0];\nsetp.ge.u32 p, v, %1;\n@p bra LD;\n@q nanosleep.u32 200;\n"
      "add.u32 n, n, 1;\nsetp.lt.u32 p, n, 0x400000;\n@p bra LW;\ntrap;\nLD:\n}" ::"l"(p), "r"(target), "n"((int)SLEEP) : "memory");
}
template <int N>
__device__ __forceinline__ void poll_chunks(uint4 (&v)[N], const uint4* p, int stride) {
#pragma unroll 1
  for (int n = 0; n < 0x400000; n++) {
    uint32_t m = 0;
#pragma unroll
    for (int i = 0; i < N; i++) {
      asm volatile("ld.relaxed.gpu.global.v4.u32 {%0,%1,%2,%3}, [%4];" : "=r"(v[i].x), "=r"(v[i].y), "=r"(v[i].z), "=r"(v[i].w) : "l"(p + i * stride) : "memory");
    }
#pragma unroll
    for (int i = 0; i < N; i++) m = max(max(m, max(v[i].x, v[i].y)), max(v[i].z, v[i].w));
    if (__all_sync(~0u, m != 0xFFFFFFFFu)) break;
  }
}
__device__ __forceinline__ void fence_async_all() { asm volatile("fence.proxy.async;" ::: "memory"); }
__device__ __forceinline__ void bar_sync(int id, int n) { asm volatile("bar.sync %0, %1;" ::"r"(id), "r"(n) : "memory"); }
__device__ __forceinline__ void bar_arrive(int id, int n) { asm volatile("bar.arrive %0, %1;" ::"r"(id), "r"(n) : "memory"); }
__device__ __forceinline__ void cluster_arrive() { asm volatile("barrier.cluster.arrive.relaxed.aligned;" ::: "memory"); }
__device__ __forceinline__ void cluster_wait() { asm volatile("barrier.cluster.wait.acquire.aligned;" ::: "memory"); }
__device__ __forceinline__ void fence_gpu() { asm volatile("fence.acq_rel.gpu;" ::: "memory"); }
__device__ __forceinline__ void red_add(unsigned* p, unsigned v) { asm volatile("red.relaxed.gpu.global.add.u32 [%0], %1;" ::"l"(p), "r"(v) : "memory"); }
__device__ __forceinline__ void prefetch_tm(const CUtensorMap* m) { asm volatile("prefetch.tensormap [%0];" ::"l"(m) : "memory"); }

__device__ __forceinline__ void tma_ld2(uint32_t dst, const CUtensorMap* m, uint32_t bar, int c0, int c1) {
  asm volatile("cp.async.bulk.tensor.2d.shared::cta.global.mbarrier::complete_tx::bytes [%0], [%1, {%3,%4}], [%2];" ::"r"(dst), "l"(m), "r"(bar), "r"(c0), "r"(c1) : "memory");
}
__device__ __forceinline__ void tma_ld3(uint32_t dst, const CUtensorMap* m, uint32_t bar, int c0, int c1, int c2) {
  asm volatile("cp.async.bulk.tensor.3d.shared::cta.global.mbarrier::complete_tx::bytes [%0], [%1, {%3,%4,%5}], [%2];" ::"r"(dst), "l"(m), "r"(bar), "r"(c0), "r"(c1), "r"(c2) : "memory");
}
__device__ __forceinline__ void tma_ld3_mc(uint32_t dst, const CUtensorMap* m, uint32_t bar, int c0, int c1, int c2, uint16_t mask) {
  asm volatile("cp.async.bulk.tensor.3d.shared::cluster.global.mbarrier::complete_tx::bytes.multicast::cluster [%0], [%1, {%3,%4,%5}], [%2], %6;" ::"r"(dst), "l"(m), "r"(bar), "r"(c0), "r"(c1), "r"(c2), "h"(mask) : "memory");
}
__device__ __forceinline__ void tma_pf3(const CUtensorMap* m, int c0, int c1, int c2) {
  asm volatile("cp.async.bulk.prefetch.tensor.3d.L2.global [%0, {%1,%2,%3}];" ::"l"(m), "r"(c0), "r"(c1), "r"(c2) : "memory");
}
__device__ __forceinline__ void l2_prefetch(const void* p, uint32_t bytes) { asm volatile("cp.async.bulk.prefetch.L2.global [%0], %1;" ::"l"(p), "r"(bytes) : "memory"); }

__device__ __forceinline__ void wg_fence() { asm volatile("wgmma.fence.sync.aligned;" ::: "memory"); }
__device__ __forceinline__ void wg_commit() { asm volatile("wgmma.commit_group.sync.aligned;" ::: "memory"); }
template <int N> __device__ __forceinline__ void wg_wait() { asm volatile("wgmma.wait_group.sync.aligned %0;" ::"n"(N) : "memory"); }
template <int N> __device__ __forceinline__ void reg_alloc() { asm volatile("setmaxnreg.inc.sync.aligned.u32 %0;" ::"n"(N)); }
template <int N> __device__ __forceinline__ void reg_dealloc() { asm volatile("setmaxnreg.dec.sync.aligned.u32 %0;" ::"n"(N)); }
template <int N> __device__ __forceinline__ void fence_regs(float* d) {
#pragma unroll
  for (int i = 0; i < N; i++) asm volatile("" : "+f"(d[i])::"memory");
}
template <int N> __device__ __forceinline__ void fence_regs(uint32_t* d) {
#pragma unroll
  for (int i = 0; i < N; i++) asm volatile("" : "+r"(d[i])::"memory");
}

__device__ __forceinline__ uint64_t mk_desc(uint32_t addr, uint32_t lbo, uint32_t sbo, uint32_t swz) {
  uint32_t lo = ((addr & 0x3FFFF) >> 4) | ((lbo >> 4) << 16);
  uint32_t hi = (sbo >> 4) | (swz << 30);
  return ((uint64_t)hi << 32) | lo;
}
__device__ __forceinline__ uint64_t desc_add(uint64_t d, uint32_t bytes) {
  uint32_t lo = (uint32_t)d + (bytes >> 4);
  return (d & 0xFFFFFFFF00000000ull) | lo;
}

#define R8(b) "+f"(d[b + 0]), "+f"(d[b + 1]), "+f"(d[b + 2]), "+f"(d[b + 3]), "+f"(d[b + 4]), "+f"(d[b + 5]), "+f"(d[b + 6]), "+f"(d[b + 7])
#define REGS32 "%0,%1,%2,%3,%4,%5,%6,%7,%8,%9,%10,%11,%12,%13,%14,%15,%16,%17,%18,%19,%20,%21,%22,%23,%24,%25,%26,%27,%28,%29,%30,%31"
#define REGS64 REGS32 ",%32,%33,%34,%35,%36,%37,%38,%39,%40,%41,%42,%43,%44,%45,%46,%47,%48,%49,%50,%51,%52,%53,%54,%55,%56,%57,%58,%59,%60,%61,%62,%63"
#define REGS128 REGS64 ",%64,%65,%66,%67,%68,%69,%70,%71,%72,%73,%74,%75,%76,%77,%78,%79,%80,%81,%82,%83,%84,%85,%86,%87,%88,%89,%90,%91,%92,%93,%94,%95," \
               "%96,%97,%98,%99,%100,%101,%102,%103,%104,%105,%106,%107,%108,%109,%110,%111,%112,%113,%114,%115,%116,%117,%118,%119,%120,%121,%122,%123,%124,%125,%126,%127"

template <int TB>
__device__ __forceinline__ void mma_n256_ss(float (&d)[128], uint64_t a, uint64_t b, int acc) {
  asm volatile("{\n.reg .pred p;\nsetp.ne.b32 p, %130, 0;\n"
               "wgmma.mma_async.sync.aligned.m64n256k16.f32.bf16.bf16 {" REGS128 "}, %128, %129, p, 1, 1, 0, %131;\n}\n"
               : R8(0), R8(8), R8(16), R8(24), R8(32), R8(40), R8(48), R8(56), R8(64), R8(72), R8(80), R8(88), R8(96), R8(104), R8(112), R8(120)
               : "l"(a), "l"(b), "r"(acc), "n"(TB));
}
template <int TB>
__device__ __forceinline__ void mma_n128_ss(float* d, uint64_t a, uint64_t b, int acc) {
  asm volatile("{\n.reg .pred p;\nsetp.ne.b32 p, %66, 0;\n"
               "wgmma.mma_async.sync.aligned.m64n128k16.f32.bf16.bf16 {" REGS64 "}, %64, %65, p, 1, 1, 0, %67;\n}\n"
               : R8(0), R8(8), R8(16), R8(24), R8(32), R8(40), R8(48), R8(56)
               : "l"(a), "l"(b), "r"(acc), "n"(TB));
}
template <int TB>
__device__ __forceinline__ void mma_n128_rs(float* d, const uint32_t* a, uint64_t b, int acc) {
  asm volatile("{\n.reg .pred p;\nsetp.ne.b32 p, %69, 0;\n"
               "wgmma.mma_async.sync.aligned.m64n128k16.f32.bf16.bf16 {" REGS64 "}, {%64,%65,%66,%67}, %68, p, 1, 1, %70;\n}\n"
               : R8(0), R8(8), R8(16), R8(24), R8(32), R8(40), R8(48), R8(56)
               : "r"(a[0]), "r"(a[1]), "r"(a[2]), "r"(a[3]), "l"(b), "r"(acc), "n"(TB));
}
__device__ __forceinline__ void mma_n64_rs(float* d, const uint32_t* a, uint64_t b, int acc) {
  asm volatile("{\n.reg .pred p;\nsetp.ne.b32 p, %37, 0;\n"
               "wgmma.mma_async.sync.aligned.m64n64k16.f32.bf16.bf16 {" REGS32 "}, {%32,%33,%34,%35}, %36, p, 1, 1, 0;\n}\n"
               : R8(0), R8(8), R8(16), R8(24)
               : "r"(a[0]), "r"(a[1]), "r"(a[2]), "r"(a[3]), "l"(b), "r"(acc));
}
#define W8(b) "=f"(d[b + 0]), "=f"(d[b + 1]), "=f"(d[b + 2]), "=f"(d[b + 3]), "=f"(d[b + 4]), "=f"(d[b + 5]), "=f"(d[b + 6]), "=f"(d[b + 7])
__device__ __forceinline__ void mma_n128_rs0(float* d, const uint32_t* a, uint64_t b) {
  asm volatile("wgmma.mma_async.sync.aligned.m64n128k16.f32.bf16.bf16 {" REGS64 "}, {%64,%65,%66,%67}, %68, 0, 1, 1, 0;\n"
               : W8(0), W8(8), W8(16), W8(24), W8(32), W8(40), W8(48), W8(56)
               : "r"(a[0]), "r"(a[1]), "r"(a[2]), "r"(a[3]), "l"(b));
}
__device__ __forceinline__ void mma_n64_rs0(float* d, const uint32_t* a, uint64_t b) {
  asm volatile("wgmma.mma_async.sync.aligned.m64n64k16.f32.bf16.bf16 {" REGS32 "}, {%32,%33,%34,%35}, %36, 0, 1, 1, 0;\n"
               : W8(0), W8(8), W8(16), W8(24)
               : "r"(a[0]), "r"(a[1]), "r"(a[2]), "r"(a[3]), "l"(b));
}
__device__ __forceinline__ uint32_t pack_bf16(float lo, float hi) {
  uint32_t r;
  asm("cvt.rn.bf16x2.f32 %0, %1, %2;" : "=r"(r) : "f"(hi), "f"(lo));
  return r;
}
__device__ __forceinline__ float bf_lo(uint32_t v) { return __uint_as_float(v << 16); }
__device__ __forceinline__ float bf_hi(uint32_t v) { return __uint_as_float(v & 0xFFFF0000u); }
__device__ __forceinline__ float bf_round(float v) { return bf_lo(pack_bf16(v, v)); }
__device__ __forceinline__ void stsm4(uint32_t addr, uint32_t r0, uint32_t r1, uint32_t r2, uint32_t r3) {
  asm volatile("stmatrix.sync.aligned.m8n8.x4.shared.b16 [%0], {%1,%2,%3,%4};" ::"r"(addr), "r"(r0), "r"(r1), "r"(r2), "r"(r3) : "memory");
}
__device__ __forceinline__ uint4 lds128(uint32_t addr) {
  uint4 v;
  asm volatile("ld.shared.v4.u32 {%0,%1,%2,%3}, [%4];" : "=r"(v.x), "=r"(v.y), "=r"(v.z), "=r"(v.w) : "r"(addr));
  return v;
}
__device__ __forceinline__ float ex2(float x) {
  float y;
  asm("ex2.approx.ftz.f32 %0, %1;" : "=f"(y) : "f"(x));
  return y;
}
__device__ __forceinline__ void pin_order(float v, uint32_t dummy) {
  asm volatile("{\n.reg .pred p;\nsetp.eq.b32 p, %0, 0xFFFFFFFF;\n@p st.shared.b32 [%1], %0;\n}" ::"r"(__float_as_uint(v)), "r"(dummy) : "memory");
}
__device__ __forceinline__ void sched_fence(uint32_t dummy) {
  asm volatile("{\n.reg .pred p;\n.reg .u32 c;\nsetp.eq.b32 p, %0, 0xFFFFFFFF;\nmov.u32 c, %%clock;\n@p st.shared.b32 [%0], c;\n}" ::"r"(dummy) : "memory");
}
__device__ __forceinline__ void stage_store_128(uint32_t base, int lane, const uint32_t* pk) {
  const int row = (lane & 7) + ((lane >> 3) & 1) * 8;
  const uint32_t rb = base + row * 128;
  const int hi = lane >> 4;
#pragma unroll
  for (int j = 0; j < 8; j++) {
    const int chunk = 2 * j + hi;
    const uint32_t a = rb + (j >> 2) * 8192 + (((chunk & 7) ^ (lane & 7)) << 4);
    stsm4(a, pk[4 * j + 0], pk[4 * j + 1], pk[4 * j + 2], pk[4 * j + 3]);
  }
}
__device__ __forceinline__ void ln_round(float mean, float var, float& m_bf, float& inv_s) {
  const uint32_t mv = pack_bf16(mean, var);
  m_bf = bf_lo(mv);
  float sq, rc;
  asm("sqrt.approx.f32 %0, %1;" : "=f"(sq) : "f"(bf_round(bf_hi(mv) + 1e-5f)));
  asm("rcp.approx.ftz.f32 %0, %1;" : "=f"(rc) : "f"(bf_round(sq)));
  inv_s = rc;
}
__device__ __forceinline__ uint32_t hadd2_bf(uint32_t a, uint32_t b) {
  uint32_t r;
  asm("add.rn.bf16x2 %0, %1, %2;" : "=r"(r) : "r"(a), "r"(b));
  return r;
}
__device__ __forceinline__ uint32_t ln_apply(uint32_t h, uint32_t nm2, float inv_s) {
  const uint32_t d = hadd2_bf(h, nm2);
  return pack_bf16(bf_lo(d) * inv_s, bf_hi(d) * inv_s);
}
__device__ __forceinline__ void ldsm4(uint32_t* r, uint32_t addr) {
  asm volatile("ldmatrix.sync.aligned.m8n8.x4.shared.b16 {%0,%1,%2,%3}, [%4];" : "=r"(r[0]), "=r"(r[1]), "=r"(r[2]), "=r"(r[3]) : "r"(addr) : "memory");
}
__device__ __forceinline__ void mma16816(float* d, uint32_t a0, uint32_t a1, uint32_t a2, uint32_t a3, uint32_t b0, uint32_t b1) {
  asm volatile("mma.sync.aligned.m16n8k16.row.col.f32.bf16.bf16.f32 {%0,%1,%2,%3}, {%4,%5,%6,%7}, {%8,%9}, {%0,%1,%2,%3};"
               : "+f"(d[0]), "+f"(d[1]), "+f"(d[2]), "+f"(d[3]) : "r"(a0), "r"(a1), "r"(a2), "r"(a3), "r"(b0), "r"(b1));
}

template <class F>
__device__ __forceinline__ void unroll8(F f) {
  f(std::integral_constant<int, 0>{}); f(std::integral_constant<int, 1>{}); f(std::integral_constant<int, 2>{}); f(std::integral_constant<int, 3>{});
  f(std::integral_constant<int, 4>{}); f(std::integral_constant<int, 5>{}); f(std::integral_constant<int, 6>{}); f(std::integral_constant<int, 7>{});
}

constexpr float AT_C = 0.08838834764831845f * 1.4426950408889634f;
#define AT_LO 0x1p-40f
#define AT_HI 0x1p40f
#define H_LATE 0
#define AT_R1 48
template <int I0, int I1>
__device__ __forceinline__ void at_exp(float* S) {
#pragma unroll
  for (int i = I0; i < I1; i++) asm volatile("ex2.approx.ftz.f32 %0, %0;" : "+f"(S[i]));
}
template <int I0, int I1>
__device__ __forceinline__ void at_fin(const float* S, uint32_t* P) {
#pragma unroll
  for (int i = I0; i < I1; i += 4) {
    P[i / 2] = pack_bf16(S[i], S[i + 1]); P[i / 2 + 1] = pack_bf16(S[i + 2], S[i + 3]);
  }
}
__device__ __forceinline__ void at_sum(const uint32_t* P, bool half, float& l0, float& l1) {
  uint32_t u[4];
#pragma unroll
  for (int r = 0; r < 4; r++) {
    const uint32_t* q = P + (r >> 1) * 16 + (r & 1);
    u[r] = hadd2_bf(hadd2_bf(hadd2_bf(q[0], q[2]), hadd2_bf(q[4], q[6])), hadd2_bf(hadd2_bf(q[8], q[10]), hadd2_bf(q[12], q[14])));
  }
  u[0] = hadd2_bf(u[0], half ? 0u : u[2]);
  u[1] = hadd2_bf(u[1], half ? 0u : u[3]);
  l0 += bf_lo(u[0]) + bf_hi(u[0]);
  l1 += bf_lo(u[1]) + bf_hi(u[1]);
}
__device__ __forceinline__ void at_mask(float* S, int r, int lane) {
  const int d = r + (lane >> 2) - (lane & 3) * 2;
#pragma unroll
  for (int j = 0; j < 8; j++) {
    float dummy0 = 0.f, dummy1 = 0.f;
    float& lo0 = j < 7 ? S[4 * (j < 7 ? j + 1 : j) + 2] : dummy0;
    float& lo1 = j < 7 ? S[4 * (j < 7 ? j + 1 : j) + 3] : dummy1;
    asm("{\n.reg .pred p, q;\nsetp.lt.s32 p, %4, %5;\nsetp.le.s32 q, %4, %5;\n"
        "@p add.f32 %0, %0, 0fFF800000;\n@q add.f32 %1, %1, 0fFF800000;\n@p add.f32 %2, %2, 0fFF800000;\n@q add.f32 %3, %3, 0fFF800000;\n}"
        : "+f"(S[4 * j]), "+f"(S[4 * j + 1]), "+f"(lo0), "+f"(lo1) : "r"(d), "r"(8 * j));
  }
}
__device__ __forceinline__ uint32_t ldg32(const __nv_bfloat16* p) { return __ldcg(reinterpret_cast<const uint32_t*>(p)); }
__device__ __forceinline__ uint32_t ldg16x2(const __nv_bfloat16* p, int stride) {
  return (uint32_t)__ldcg(reinterpret_cast<const unsigned short*>(p)) | ((uint32_t)__ldcg(reinterpret_cast<const unsigned short*>(p + stride)) << 16);
}
__device__ __forceinline__ void slow_tile(float* O, uint32_t* Q, float& l0, float& l1, const __nv_bfloat16* wq, int row0, int head, int lane, uint32_t dummy) {
  const int r = lane >> 2, q = lane & 3;
#pragma unroll
  for (int i = 0; i < 64; i++) O[i] = 0.f;
  {
    const __nv_bfloat16* xa = g_xn + (size_t)(row0 + r) * DM + 2 * q;
    const __nv_bfloat16* wb = wq + (size_t)(2 * q) * NQ + head * HD + (r >> 1) * 8 + (r & 1);
#pragma unroll 1
    for (int k = 0; k < DM; k += 16) {
      const uint32_t a0 = ldg32(xa + k), a1 = ldg32(xa + k + 8 * DM), a2 = ldg32(xa + k + 8), a3 = ldg32(xa + k + 8 * DM + 8);
#pragma unroll
      for (int j = 0; j < 16; j++) {
        const __nv_bfloat16* wp = wb + (size_t)k * NQ + (j >> 2) * 32 + (j & 3) * 2;
        mma16816(O + 4 * j, a0, a1, a2, a3, ldg16x2(wp, NQ), ldg16x2(wp + 8 * NQ, NQ));
        if (j == 7) sched_fence(dummy);
      }
    }
  }
#pragma unroll
  for (int i = 0; i < 32; i++) Q[i] = pack_bf16(O[2 * i], O[2 * i + 1]);
#pragma unroll
  for (int i = 0; i < 64; i++) O[i] = 0.f;
  float m0 = -INFINITY, m1 = -INFINITY;
  l0 = l1 = 0.f;
#pragma unroll 1
  for (int kv = 0; kv <= row0; kv += 16) {
    float s[8] = {0.f, 0.f, 0.f, 0.f, 0.f, 0.f, 0.f, 0.f};
    const __nv_bfloat16* kp = g_qkv + (size_t)(SEQ + kv + r) * NQ + head * HD + 2 * q;
#pragma unroll
    for (int k = 0; k < 8; k++) {
      mma16816(s, Q[4 * k], Q[4 * k + 1], Q[4 * k + 2], Q[4 * k + 3], ldg32(kp + 16 * k), ldg32(kp + 16 * k + 8));
      mma16816(s + 4, Q[4 * k], Q[4 * k + 1], Q[4 * k + 2], Q[4 * k + 3], ldg32(kp + 8 * NQ + 16 * k), ldg32(kp + 8 * NQ + 16 * k + 8));
    }
#pragma unroll
    for (int i = 0; i < 8; i++)
      if (kv + (i >> 2) * 8 + 2 * q + (i & 1) > row0 + r + (i & 2) * 4) s[i] = -INFINITY;
    float a = fmaxf(fmaxf(fmaxf(s[0], s[1]), fmaxf(s[4], s[5])), m0), b = fmaxf(fmaxf(fmaxf(s[2], s[3]), fmaxf(s[6], s[7])), m1);
    a = fmaxf(a, __shfl_xor_sync(~0u, a, 1)); b = fmaxf(b, __shfl_xor_sync(~0u, b, 1));
    a = fmaxf(a, __shfl_xor_sync(~0u, a, 2)); b = fmaxf(b, __shfl_xor_sync(~0u, b, 2));
    const float c0 = ex2(m0 - a), c1 = ex2(m1 - b);
    m0 = a; m1 = b;
#pragma unroll
    for (int i = 0; i < 8; i++) s[i] = ex2(s[i] - ((i & 2) ? b : a));
    l0 = l0 * c0 + (s[0] + s[1]) + (s[4] + s[5]);
    l1 = l1 * c1 + (s[2] + s[3]) + (s[6] + s[7]);
    sched_fence(dummy);
    const uint32_t p0 = pack_bf16(s[0], s[1]), p1 = pack_bf16(s[2], s[3]), p2 = pack_bf16(s[4], s[5]), p3 = pack_bf16(s[6], s[7]);
    const __nv_bfloat16* vp = g_qkv + (size_t)(2 * SEQ + kv + 2 * q) * NQ + head * HD + r;
#pragma unroll
    for (int j = 0; j < 16; j++) {
      O[4 * j] *= c0; O[4 * j + 1] *= c0; O[4 * j + 2] *= c1; O[4 * j + 3] *= c1;
      mma16816(O + 4 * j, p0, p1, p2, p3, ldg16x2(vp + 8 * j, NQ), ldg16x2(vp + 8 * NQ + 8 * j, NQ));
      if (j == 7) sched_fence(dummy);
    }
  }
}

constexpr int P1_STAGE = 49152;
constexpr int SLOT = 32768;
constexpr int OFF_LN = 6 * SLOT, OFF_R3 = 0;
constexpr int OFF_BAR = 229376;
constexpr int OFF_MISC = OFF_BAR + 8 * 58;
constexpr int SMEM_BYTES = OFF_MISC + 2080 + TL_BYTES;
enum : int {
  B_FULL1 = 0, B_KF = 4, B_VF = 6, B_FULL3 = 8, B_XF = 14, B_LN = 15, B_DEP = 16, B_OUT2 = 22, B_FIN = 23, B_SET = 24, B_SET2 = 25, B_QP = 26, B_WF2 = 29,
  B_WF = 30, B_WR = 31,
  B_LND = 32,
  B_XE = 33, B_PUB = 34, B_OUT = 40, B_OUT3 = 41,
  B_EMPTY1 = 42, B_KE = 46, B_VE = 48, B_EMPTY3 = 50, B_WE = 56, B_NUM = 57
};
#define PRE 3
#define LN_PF 4
#define LN_LD 9
constexpr int LN_PFN = 2;
constexpr int OFF_STG = SLOT, SL_SCR = 2;
#define SET_NS 50
#define ST_G 1
#define ST_NS 0
#define OBS 99
#define PFALL 0
#define WQ_D 4
#define WQ_0 18
#define SL_NS 600
#define X_KB 20
#define G_KB 35
#define WD_AT 8
#define OUT_P 0
#define W_G0 22
#define KVPF 1
struct Params {
  CUtensorMap xn, ckv, wq, wk, wv, kv, ctx_ld, ctx_st, wo, x, wd, wg, wu, out;
};

__global__ void __cluster_dims__(2, 1, 1) __launch_bounds__(384, 1)
fused_kernel(const __nv_bfloat16* __restrict__ x, const __nv_bfloat16* __restrict__ wq, const __nv_bfloat16* __restrict__ w_r,
             __nv_bfloat16* __restrict__ out, const __grid_constant__ Params p) {
  extern __shared__ __align__(1024) uint8_t sp[];
  const uint32_t sb = s2u(sp);
  const uint32_t bar = sb + OFF_BAR;
  auto B = [&](int i) { return bar + 8 * i; };
  const int tid = threadIdx.x, warp = __shfl_sync(~0u, tid >> 5, 0), wg = warp >> 2, lane = tid & 31;
  const int cta = blockIdx.x, rank = cta & 1, cl = cta >> 1;
  const int mp = cl < 4 ? 1 : (cl < 36 ? (cl & 7) : (0x3207654 >> (4 * ((cl - 36) % 7))) & 7);
  const int gq = cl < 4 ? 4 + cl : (cl < 36 ? (cl - 4) >> 3 : 4 + (cl - 36) / 7);
  const int mt = 2 * mp + rank;
  const int ti = (gq & 3) * 2 + rank, hh = mp * 2 + (gq >> 2);
  const int rid = mt * 8 + gq;
  const int fid = mt * 7 + gq;
  const bool ffn = gq < 7;
  uint4* const xr = g_xr + rid * XR_SIZE;
  TL_INIT();
  TL(0, 0, tid == 128);
  if (warp == 0) {
    if (elect_one()) {
#pragma unroll
      for (int kb = 0; kb < PRE; kb++) mbar_init(B(B_FULL1 + kb), 1);
      asm volatile("fence.mbarrier_init.release.cluster;" ::: "memory");
    }
    __syncwarp();
    cluster_arrive();
    if (elect_one()) {
#pragma unroll
      for (int kb = 0; kb < PRE; kb++) {
        mbar_expect(B(B_FULL1 + kb), P1_STAGE);
        tma_ld2(sb + kb * P1_STAGE, &p.ckv, B(B_FULL1 + kb), kb * 64, mt * 128);
        tma_ld3(sb + kb * P1_STAGE + 16384 + rank * 16384, &p.wk, B(B_FULL1 + kb), 0, kb * 64, gq * 4 + rank * 2);
        tma_ld3(sb + kb * P1_STAGE + 32768 - rank * 16384, &p.wk, B(B_FULL1 + kb), 0, kb * 64, gq * 4 + 2 - rank * 2);
      }
    }
  } else if (elect_one()) {
#pragma unroll 1
    for (int i = PRE + warp - 1; i < B_NUM; i += 11)
      mbar_init(B(i), i >= B_EMPTY1 ? 16 : (i >= B_XE ? 8 : (i == B_LND ? 3 : (i >= B_WF ? 2 : 1))));
    asm volatile("fence.mbarrier_init.release.cluster;" ::: "memory");
  }
  __syncwarp();
  if (warp) cluster_arrive();
  if (wg == 0) {
    reg_dealloc<40>();
    if (warp == 1 && elect_one()) {
      if (mt >= 2 * PRE) tma_pf3(&p.wk, 0, mp * 64, gq * 4 + rank * 2);
      if (gq >= PRE) asm volatile("cp.async.bulk.prefetch.tensor.2d.L2.global [%0, {%1,%2}];" ::"l"(&p.ckv), "r"(gq * 64), "r"(mt * 128) : "memory");
    } else if (warp == 2 && elect_one()) {
      prefetch_tm(&p.wv); prefetch_tm(&p.wq); prefetch_tm(&p.xn);
    }
    __syncwarp();
    cluster_wait();
    if (warp == 0) {
      int st = 0; uint32_t ph = 1;
#pragma unroll 1
      for (int t = 0; t < 6; t++) {
        const CUtensorMap* ma = t >= 4 ? &p.xn : &p.ckv;
        const CUtensorMap* mb = t >= 4 ? &p.wq : ((t & 1) ? &p.wv : &p.wk);
        const int nk = t >= 4 ? 16 : 8;
        const int row = (t < 4 ? mt : (t == 4 ? 15 - ti : ti)) * 128;
        const int col = t < 4 ? (gq + (t >> 1) * 8) * 4 + rank * 2 : (hh + rank * 16) * 2;
        if (t >= 4) mbar_wait(B(B_DEP + t - 4), 0);
#pragma unroll 1
        for (int kb = 0; kb < nk; kb++) {
          const uint32_t d = sb + st * P1_STAGE, fb = B(B_FULL1 + st);
          const int n = t * 8 + kb;
          if (n >= PRE) {
            mbar_wait_c(B(B_EMPTY1 + st), ph);
            if (elect_one()) {
              mbar_expect(fb, P1_STAGE);
              tma_ld2(d, ma, fb, kb * 64, row);
              tma_ld3_mc(d + 16384 + rank * 16384, mb, fb, 0, kb * 64, col, 3);
            }
          }
          if (t < 5 && elect_one()) {
            if (n >= LN_PF && n < LN_PF + LN_PFN) l2_prefetch(x + (size_t)cta * 16 * DM + (n - LN_PF) * (16 * DM / LN_PFN), 32768 / LN_PFN);
            if (n == LN_LD) {
              mbar_expect(B(B_LN), 32768);
              asm volatile("cp.async.bulk.shared::cluster.global.mbarrier::complete_tx::bytes [%0], [%1], %2, [%3];" ::"r"(sb + OFF_LN),
                           "l"(x + (size_t)cta * 16 * DM), "r"(32768), "r"(B(B_LN)) : "memory");
            }
            if (t < 3 && kb == 0) tma_pf3((t & 1) ? &p.wk : &p.wv, 0, mp * 64, (gq + ((t + 1) >> 1) * 8) * 4 + rank * 2);
            if (n >= WQ_0 && n < WQ_0 + 4 * WQ_D && (n - WQ_0) % WQ_D == 0) tma_pf3(&p.wq, 0, ((n - WQ_0) / WQ_D * 4 + (gq & 3)) * 64, (hh + rank * 16) * 2);
          }
          if (++st == 4) { st = 0; ph ^= 1; }
        }
      }
      if (elect_one()) { prefetch_tm(&p.kv); prefetch_tm(&p.ctx_ld); prefetch_tm(&p.wo); prefetch_tm(&p.wg); prefetch_tm(&p.wu); }
      auto load_kv = [&](int g, int isv) {
        const int h2 = g >= 17, sx = g - 17 * h2, n1 = h2 ? ti + 1 : 16 - ti;
        const int row = (1 + isv) * SEQ + (sx < n1 ? sx : 16 - sx) * 128, col = (hh + 16 * h2) * 2;
        const uint32_t d = sb + (isv ? 2 + 2 * (g & 1) : (g & 1)) * SLOT, fb = B(B_KF + 2 * isv + (g & 1));
        const bool shared = sx != (h2 ? (ti & 6) + 1 : 15 - (ti & 6));
        const int g2 = g + KVPF, h3 = g2 >= 17, s3 = g2 - 17 * h3;
        const int pb = PFALL ? (g2 < 34 ? (s3 < (h3 ? ti + 1 : 16 - ti) ? s3 : 16 - s3) : -1)
                             : (ti < 2 ? (h3 ? (s3 >= 1 && s3 <= 8 ? 16 - s3 : -1) : (s3 < 16 ? s3 : -1)) : (ti >= 6 && h3 && s3 < 8 ? s3 : -1));
        mbar_wait_c(g < 2 ? B(B_EMPTY1 + (isv ? 1 + 2 * g : g)) : B(B_KE + 2 * isv + (g & 1)), g < 2 ? 1 : ((g >> 1) & 1) ^ 1);
        if (elect_one()) {
          mbar_expect(fb, SLOT);
          if (shared) {
            tma_ld3_mc(d + rank * 16384, &p.kv, fb, 0, row, col + rank, 3);
          } else {
            tma_ld3(d, &p.kv, fb, 0, row, col);
            tma_ld3(d + 16384, &p.kv, fb, 0, row, col + 1);
          }
          if (KVPF && pb >= 0) tma_pf3(&p.kv, 0, (1 + isv) * SEQ + pb * 128, (hh + 16 * h3) * 2 + rank);
        }
      };
      int nw = ffn ? 0 : 12;
      auto load_w = [&]() {
        const int c = nw < 8 ? (nw >> 2) + (nw & 2) : nw >> 1;
        if (elect_one()) {
          if (!(nw & 3)) mbar_expect(B(B_WF - (nw >> 3)), 32768);
          tma_ld2(sb + (c < 2 ? 3 : 4) * SLOT + c * 16384 + (nw & 1) * 8192, (nw & 1) ? &p.wg : &p.wu, B(B_WF - (nw >> 3)), fid * 32, c * 128);
        }
        nw++;
      };
#pragma unroll 1
      for (int g = 0; g < 34; g++) {
        if (g == 0 || g == 17 - KVPF) mbar_wait(B(B_DEP + 2 + (g > 0)), 0);
        load_kv(g, 0);
        if (g > 0) load_kv(g - 1, 1);
        if (g >= W_G0 && nw < 12 && __any_sync(~0u, mbar_test(B(B_QP + (nw >> 2)), 0))) load_w();
      }
      load_kv(33, 1);
#pragma unroll 1
      while (nw < 12) { mbar_wait(B(B_QP + (nw >> 2)), 0); load_w(); }
      if (elect_one()) { prefetch_tm(&p.wd); prefetch_tm(&p.x); prefetch_tm(&p.out); }
      auto load3 = [&](int kb, int sl) {
        if (elect_one()) {
          mbar_expect(B(B_FULL3 + sl), SLOT);
          tma_ld2(sb + OFF_R3 + sl * SLOT, &p.ctx_ld, B(B_FULL3 + sl), kb * 64, mt * 128);
          tma_ld3_mc(sb + OFF_R3 + sl * SLOT + 16384 + rank * 8192, &p.wo, B(B_FULL3 + sl), 0, kb * 64, gq * 2 + rank, 3);
          if (kb >= OBS && kb < OBS + 11) TL(0, 32 + kb - OBS, true);
        }
      };
      mbar_wait(B(B_DEP + 4), 0);
#pragma unroll
      for (int kb = 0; kb < 5; kb++) {
        mbar_wait_c(B(kb == 3 ? B_WE : (kb == 4 ? B_VE + 1 : B_KE + kb)), 0);
        load3(kb, kb);
      }
      if (elect_one()) mbar_arrive(B(B_FULL3 + 5));
#pragma unroll 1
      for (int r = 1; r < 11; r++) {
#pragma unroll
        for (int j = 0; j < 6; j++) {
          if (j == 5 && r == 10) break;
          if (j == 3 && r == 5) mbar_wait(B(B_DEP + 5), 0);
          mbar_wait_c(B(B_EMPTY3 + j), ~r & 1);
          load3(r * 6 + j - 1, j);
          if (j == 5 && r == 9 && elect_one()) l2_prefetch(xr, XR_CAND * 16);
        }
      }
      if (ffn) {
#pragma unroll
        for (int j = 1; j >= 0; j--) {
          mbar_wait(B(B_EMPTY3 + 5 * j), j);
          if (elect_one()) {
            mbar_expect(B(B_FULL3 + 5 * j), SLOT);
            tma_ld3(sb + OFF_R3 + 5 * j * SLOT, &p.wd, B(B_FULL3 + 5 * j), 0, fid * 32, 8 * j);
          }
        }
      }
    } else {
      if (warp >= 2) {
#pragma unroll 1
        for (int i = tid - 64; i < XR_CAND; i += 64) xr[i] = make_uint4(~0u, ~0u, ~0u, ~0u);
        if (warp == 2) { __syncwarp(); if (lane == 0) mbar_arrive(B(B_WR)); }
      }
      if (warp == 3) {
        float ws = 0.f;
#pragma unroll
        for (int j = 0; j < 4; j++) {
          const uint4 q = __ldg(reinterpret_cast<const uint4*>(w_r) + j * 32 + lane);
          ws += bf_lo(q.x) + bf_hi(q.x) + bf_lo(q.y) + bf_hi(q.y) + bf_lo(q.z) + bf_hi(q.z) + bf_lo(q.w) + bf_hi(q.w);
        }
#pragma unroll
        for (int o = 16; o; o >>= 1) ws += __shfl_xor_sync(~0u, ws, o);
        uint2* tab = reinterpret_cast<uint2*>(sp + OFF_MISC + 512);
        tab[lane] = make_uint2(0x3F803F80u, 0x3F803F80u);
        tab[32 + lane] = __ldg(reinterpret_cast<const uint2*>(w_r + gq * 128) + lane);
        if (lane == 0) *reinterpret_cast<float*>(sp + OFF_MISC + 1024) = ws;
        __syncwarp();
        if (lane == 0) mbar_arrive(B(B_WR));
      }
      if (tid == 32) TS(0);
      mbar_wait(B(B_LN), 0);
#pragma unroll 1
      for (int r = warp - 1; r < 16; r += 3) {
        uint4 v[4];
        float a0 = 0.f, a1 = 0.f, b0 = 0.f, b1 = 0.f;
#pragma unroll
        for (int j = 0; j < 4; j++) {
          v[j] = lds128(sb + OFF_LN + r * 2048 + lane * 16 + j * 512);
          const uint32_t u[4] = {v[j].x, v[j].y, v[j].z, v[j].w};
#pragma unroll
          for (int i = 0; i < 4; i++) { const float a = bf_lo(u[i]), b = bf_hi(u[i]); a0 += a; a1 += b; b0 = fmaf(a, a, b0); b1 = fmaf(b, b, b1); }
        }
        a0 += a1; b0 += b1;
#pragma unroll
        for (int o = 16; o; o >>= 1) { a0 += __shfl_xor_sync(~0u, a0, o); b0 += __shfl_xor_sync(~0u, b0, o); }
        const float mean = a0 * (1.f / DM);
        float mb, inv;
        ln_round(mean, fmaxf(fmaf(b0, 1.f / DM, -mean * mean), 0.f), mb, inv);
        inv *= AT_C;
        const uint32_t nm2 = pack_bf16(-mb, -mb);
        uint4* dst = reinterpret_cast<uint4*>(g_xn + (size_t)(cta * 16 + r) * DM) + lane;
#pragma unroll
        for (int j = 0; j < 4; j++)
          dst[j * 32] = make_uint4(ln_apply(v[j].x, nm2, inv), ln_apply(v[j].y, nm2, inv), ln_apply(v[j].z, nm2, inv), ln_apply(v[j].w, nm2, inv));
      }
      __syncwarp();
      if (lane == 0) {
        mbar_arrive(B(B_LND));
        fence_gpu();
        red_add(&g_cnt[C_LN + (cta >> 3)], 1);
      }
      TL(3, warp, lane == 0);
      __syncwarp();
      if (warp == 3) {
        if (lane == 0) {
#pragma unroll 1
          for (int i = 0; i < 6; i++) {
            const int c = i < 2 ? C_LN + (i ? ti : 15 - ti) : (i < 4 ? C_QKV + (i - 2) * 8 + mp : C_CTX + (i - 4) * 16 + mt);
            spin_until_ge<true>(&g_cnt[c], i < 2 ? 24 : 16);
            fence_async_all();
            mbar_arrive(B(B_DEP + i));
            TL(3, 4 + i, true);
          }
        }
      } else if (warp == 1 && elect_one()) {
        mbar_wait(B(B_WR), 0);
#pragma unroll 1
        for (int i = 0; i < 6; i++) {
          const int c = i < 2 ? C_QKV + gq + i * 8 : C_CTX + (i >> 2) * 16 + ((i == 3 || i == 4) ? ti : 15 - ti);
          mbar_wait(B(B_PUB + i), 0);
          if (i >= 2 && i < 5) {
            asm volatile("fence.proxy.async.shared::cta;" ::: "memory");
#pragma unroll 1
            for (int n = 0; n < 8 / ST_G; n++) {
              const int h = n / (4 / ST_G), a = n % (4 / ST_G) * ST_G;
              asm volatile("cp.async.bulk.tensor.3d.global.shared::cta.bulk_group [%0, {%2,%3,%4}], [%1];" ::"l"(&p.ctx_st),
                           "r"(sb + (i == 4 ? 6 * SLOT + h * 16384 : (3 + 2 * h) * SLOT + (i - 2) * 16384) + a * 4096),
                           "r"(0), "r"((i == 2 ? 15 - ti : ti) * 128 + h * 64), "r"((hh + (i >> 2) * 16) * 4 + a) : "memory");
              asm volatile("cp.async.bulk.commit_group;\ncp.async.bulk.wait_group.read 0;" ::: "memory");
              if (ST_NS) __nanosleep(ST_NS);
            }
            mbar_arrive(B(B_QP + i - 2));
            asm volatile("cp.async.bulk.wait_group 0;" ::: "memory");
          }
          fence_gpu();
          red_add(&g_cnt[c], 1);
          TS(1 + i);
        }
      }
      if (warp == 2) {
#pragma unroll 1
        for (int n = 0; n < 8; n++) {
          if (!(n & 3)) mbar_wait(B(B_XE), n >> 2);
          if ((n < 4 || ffn) && elect_one()) {
            const uint32_t fb = B(n < 4 ? B_XF : B_WF2), d = sb + 6 * SLOT + (n & 3) * 8192;
            if (!(n & 3)) mbar_expect(fb, 32768);
            if (n < 4) tma_ld3(d, &p.x, fb, 0, mt * 128 + (n >> 1) * 64, gq * 2 + (n & 1));
            else tma_ld2(d, (n & 1) ? &p.wg : &p.wu, fb, fid * 32, (4 + (n >> 1)) * 128);
          }
          __nanosleep(SL_NS);
        }
#pragma unroll 1
        for (int i = XR_CAND + lane; i < XR_SIZE; i += 32) { xr[i] = make_uint4(~0u, ~0u, ~0u, ~0u); if (SET_NS) __nanosleep(SET_NS); }
        __syncwarp();
        if (lane == 0) { fence_gpu(); mbar_arrive(B(B_SET2)); }
        TL(2, 26, lane == 0);
        __syncwarp();
      }
      __syncwarp();
      if (warp == 3) {
        mbar_wait(B(B_OUT), 0);
        uint4 kv[2];
        poll_chunks(kv, g_xr + ((lane >> 1) * 8 + gq) * XR_SIZE + XR_KEY + (lane & 1) * 2, 1);
        const uint32_t a1 = max(kv[0].x, kv[0].z), a2 = max(min(kv[0].x, kv[0].z), max(kv[0].y, kv[0].w));
        const uint32_t b1 = max(kv[1].x, kv[1].z), b2 = max(min(kv[1].x, kv[1].z), max(kv[1].y, kv[1].w));
        const uint32_t k1 = max(a1, b1), k2 = max(min(a1, b1), max(a2, b2));
        const uint32_t m1 = __reduce_max_sync(~0u, k1);
        const uint32_t m2 = __reduce_max_sync(~0u, k1 == m1 ? k2 : k1);
        if (lane == 0) {
          *reinterpret_cast<uint2*>(sp + OFF_MISC) = make_uint2(m1, m2);
          mbar_arrive(B(B_OUT2));
        }
        const uint32_t key = (lane & 4) ? m2 : m1;
        const int tk = 0x7FFF - (key & 0x7FFF);
        const uint4* src = g_xr + ((tk >> 7) * 8 + (rid >> 4)) * XR_SIZE;
        poll_chunks(kv, src + XR_CAND + ((tk >> 4) & 7) * 64 + (((lane & 4) && !((m1 ^ m2) & 0x7FF0)) ? 16 : 0) + (rid & 12) + (lane & 3), 32);
        uint32_t u = key >> 16;
        u = (u & 0x8000u) ? (u & 0x7FFFu) : (~u & 0xFFFFu);
        const float rs = bf_round(__fdividef(1.f, 1.f + __expf(-__uint_as_float(u << 16))));
        if (lane < 8)
          *reinterpret_cast<uint4*>(sp + OFF_MISC + 128 + lane * 16) = make_uint4((rid & 2) ? ((rid & 1) ? kv[0].w : kv[0].z) : ((rid & 1) ? kv[0].y : kv[0].x),
              (rid & 2) ? ((rid & 1) ? kv[1].w : kv[1].z) : ((rid & 1) ? kv[1].y : kv[1].x), __float_as_uint(rs), 0);
        uint4 fl[1];
        poll_chunks(fl, src + XR_FLAG, 0);
        fence_gpu();
        __syncwarp();
        if (lane == 0) mbar_arrive(B(B_FIN));
      }
      if (warp == 1 && elect_one()) {
        mbar_wait(B(B_OUT3), 0);
#pragma unroll 1
        for (int n = 0; n < 4; n++) {
          asm volatile("cp.async.bulk.tensor.2d.global.shared::cta.bulk_group [%0, {%2,%3}], [%1];" ::"l"(&p.out), "r"(sb + OFF_STG + n * 8192),
                       "r"(gq * 128 + (n & 1) * 64), "r"(mt * 128 + (n >> 1) * 64) : "memory");
          asm volatile("cp.async.bulk.commit_group;" ::: "memory");
          if (OUT_P) asm volatile("cp.async.bulk.wait_group.read 0;" ::: "memory");
        }
        asm volatile("cp.async.bulk.wait_group 0;" ::: "memory");
        fence_async_all();
        fence_gpu();
        __stcg(xr + XR_FLAG, make_uint4(0, 0, 0, 0));
        TL(2, 25, true);
      }
    }
    __syncwarp();
    cluster_arrive();
    cluster_wait();
    TL_DUMP();
    if (tid == 32) TS(8);
  } else {
    reg_alloc<232>();
    cluster_wait();
    const int w = wg - 1, cw = warp - 4;
    int lane = lane_id();
    const uint32_t stg = sb + OFF_STG + w * 16384 + (cw & 3) * 2048;
    auto publish = [&](int i) { __syncwarp(); if (lane == 0) mbar_arrive(B(B_PUB + i)); };
    uint32_t rbar;
    asm("mapa.shared::cluster.u32 %0, %1, %2;" : "=r"(rbar) : "r"(bar), "r"(lane & 1));
    auto release2 = [&](int i) { if (lane < 2) asm volatile("mbarrier.arrive.shared::cluster.b64 _, [%0];" ::"r"(rbar + 8 * i) : "memory"); };
    float R[128];
    float O[64], acc[64];
    uint32_t pk[64];
    uint32_t* const Q = pk;
    uint32_t P[32];
    auto packed = [&](int i) {
      const float* v = R + 16 * (i >> 1) + 2 * (i & 1);
      return make_uint4(pack_bf16(v[0], v[1]), pack_bf16(v[4], v[5]), pack_bf16(v[8], v[9]), pack_bf16(v[12], v[13]));
    };
    const uint32_t q_st = sb + (cw & 3) * 1024 + (lane >> 2) * 64 + (((lane & 3) ^ (lane >> 3)) << 4);
    const uint32_t q_ld = sb + (cw & 3) * 1024 + (lane & 15) * 64 + (((lane >> 4) ^ ((lane >> 1) & 3)) << 4);
    auto park = [&](uint32_t off, int i, uint4 v) {
      asm volatile("st.shared.v4.u32 [%0], {%1,%2,%3,%4};" ::"r"(q_st + off + (i >> 1) * 4096 + (i & 1) * 512), "r"(v.x), "r"(v.y), "r"(v.z), "r"(v.w) : "memory");
    };
    auto load_q = [&](uint32_t off, int k) { ldsm4(Q + 4 * k, ((q_ld + off) ^ ((k & 1) << 5)) + (k >> 1) * 4096); };
    {
      TL(0, 1, tid == 128);
      __nv_bfloat16* pdst = g_qkv;
      auto put2 = [&](int j) {
#pragma unroll
        for (int i = (j >> 1) * 4 + (j & 1); i < (j >> 1) * 4 + 4; i += 2)
          __stcs(reinterpret_cast<uint4*>(pdst + (i & 1) * 8 * NQ + (i >> 1) * 32), make_uint4(pk[4 * i], pk[4 * i + 1], pk[4 * i + 2], pk[4 * i + 3]));
      };
      const uint64_t da0 = mk_desc(sb + w * 8192, 16, 1024, 1);
      const uint64_t db0 = mk_desc(sb + 16384, 8192, 1024, 1);
      int st = 0; uint32_t ph = 0;
      auto issue = [&](int accum, auto between) {
        mbar_wait_c(B(B_FULL1 + st), ph);
        const uint64_t da = desc_add(da0, st * P1_STAGE), db = desc_add(db0, st * P1_STAGE);
        between();
        wg_fence();
#pragma unroll
        for (int k = 0; k < 4; k++) mma_n256_ss<1>(R, desc_add(da, k * 32), desc_add(db, k * 2048), k == 0 ? accum : 1);
        wg_commit();
      };
      issue(0, []() {});
#pragma unroll 1
      for (int t = 0;; t++) {
        const int nk = t >= 4 ? 16 : 8;
        const bool tr = t > 0 && t < 5;
        TL(0, 2 + 2 * t + 16 * w, (tid & 127) == 0);
        int prev = st;
        if (++st == 4) { st = 0; ph ^= 1; }
#pragma unroll 1
        for (int kb = 1; kb < nk; kb++) {
          if (kb == nk - 1 && w == 1) bar_sync(5, 256);
          issue(1, []() {});
          if (kb == nk - 1 && w == 0) bar_arrive(5, 256);
          if (tr) {
#pragma unroll
            for (int i = 1; i < 8; i++) if (kb == i) put2(i);
            if (kb == 7 && !(t & 1)) publish((t >> 1) - 1);
          } else if (t == 5 && kb == 2) {
            mbar_wait_c(B(B_LND), 0);
#pragma unroll
            for (int i = 0; i < 8; i++) park(6 * SLOT + w * 16384, i, make_uint4(pk[4 * i], pk[4 * i + 1], pk[4 * i + 2], pk[4 * i + 3]));
            __syncwarp();
#pragma unroll
            for (int k = 0; k < 8; k++) load_q(6 * SLOT + w * 16384, k);
            __syncwarp();
#pragma unroll
            for (int i = 0; i < 8; i++) park(6 * SLOT + w * 16384, i, make_uint4(pk[32 + 4 * i], pk[33 + 4 * i], pk[34 + 4 * i], pk[35 + 4 * i]));
          }
          wg_wait<1>();
          release2(B_EMPTY1 + prev);
          prev = st;
          if (++st == 4) { st = 0; ph ^= 1; }
        }
        if (t == 5) break;
        issue(0, [&]() {
          sched_fence(q_st);
          wg_wait<0>();
          fence_regs<128>(R);
          TL(0, 3 + 2 * t + 16 * w, (tid & 127) == 0);
#pragma unroll
          for (int i = 0; i < 16; i++) { const uint4 v = packed(i); pk[4 * i] = v.x; pk[4 * i + 1] = v.y; pk[4 * i + 2] = v.z; pk[4 * i + 3] = v.w; }
          release2(B_EMPTY1 + prev);
          fence_regs<128>(R);
        });
        sched_fence(q_st);
        pdst = g_qkv + (size_t)(((t & 1) + 1) * SEQ + mt * 128 + cw * 16 + (lane >> 2)) * NQ + (gq + (t >> 1) * 8) * 256 + (lane & 3) * 8;
        if (t < 4) put2(0);
      }
      if (w == 1) bar_arrive(6, 256);
      mbar_wait_c(B(B_KF), 0);
      sched_fence(q_st);
      wg_wait<0>();
      fence_regs<128>(R);
      release2(B_EMPTY1 + 3);
      TL(0, 13 + 16 * w, (tid & 127) == 0);
    }
    auto issue3 = [&](int st, uint32_t ph, int accum) {
      mbar_wait_c(B(B_FULL3 + st), ph);
      const uint64_t da = mk_desc(sb + OFF_R3 + w * 8192 + st * SLOT, 16, 1024, 1), db = mk_desc(sb + OFF_R3 + 16384 + st * SLOT, 8192, 1024, 1);
      wg_fence();
#pragma unroll
      for (int k = 0; k < 4; k++) mma_n128_ss<1>(acc, desc_add(da, k * 32), desc_add(db, k * 2048), k == 0 ? accum : 1);
      wg_commit();
    };
    uint32_t wf[128];
    auto w_addr = [&](uint32_t off, int m) {
      const uint32_t w_ld = sb + ((lane >> 3) & 1) * 8192 + ((cw >> 1) * 32 + (lane & 7) + (lane >> 4) * 8) * 64 + ((((cw & 1) * 2) ^ ((lane >> 1) & 3)) << 4);
      return ((w_ld + off) ^ ((m & 1) << 4)) + (m >> 2) * 16384 + ((m >> 1) & 1) * 1024;
    };
    auto grab = [&](uint32_t* d, uint32_t off, int m0, int m1) {
#pragma unroll
      for (int m = m0; m < m1; m++)
        asm volatile("ldmatrix.sync.aligned.m8n8.x4.trans.shared.b16 {%0,%1,%2,%3}, [%4];"
                     : "=r"(d[4 * m]), "=r"(d[4 * m + 1]), "=r"(d[4 * m + 2]), "=r"(d[4 * m + 3]) : "r"(w_addr(off, m)) : "memory");
    };
    float inv[2] = {0.f, 0.f};
    auto scaled = [&](int i) {
      const float* o = O + 16 * (i >> 1) + 2 * (i & 1);
      const float c = inv[i & 1];
      return make_uint4(pack_bf16(o[0] * c, o[1] * c), pack_bf16(o[4] * c, o[5] * c), pack_bf16(o[8] * c, o[9] * c), pack_bf16(o[12] * c, o[13] * c));
    };
    {
      const int wrow = cw * 16;
      const uint64_t dk0 = mk_desc(sb, 16, 1024, 1);
      const uint64_t dv0 = mk_desc(sb + 2 * SLOT, 16384, 1024, 1);
      const uint32_t pin = sb + OFF_MISC + 1028;
      float l0 = 0.f, l1 = 0.f;
      int g = 0, t = 0;
      uint32_t fail = 0;
      auto piece = [&](int tt) { return (uint32_t)(tt == 3 ? 6 * SLOT + w * 16384 : (3 + 2 * w) * SLOT + (tt - 1) * 16384); };
      uint32_t par = 0;
      auto issue_s = [&](float* S) {
        const uint64_t dk = desc_add(dk0, par * 16);
        mma_n128_rs0(S, Q, dk);
#pragma unroll
        for (int k = 1; k < 8; k++) mma_n128_rs<0>(S, Q + 4 * k, desc_add(dk, (k >> 2) * 16384 + (k & 3) * 32), 1);
        wg_commit();
      };
      auto issue_pv = [&](bool half, int accum) {
        const uint64_t dv = desc_add(dv0, ((g - 1) & 1) * 2 * SLOT);
        wg_fence();
#pragma unroll
        for (int k = 0; k < 4; k++) mma_n128_rs<1>(O, P + 4 * k, desc_add(dv, k * 2048), k == 0 ? accum : 1);
        wg_commit();
        if (UNLIKELY(half)) {
          wg_fence();
          wg_commit();
        } else {
          wg_fence();
#pragma unroll
          for (int k = 4; k < 8; k++) mma_n128_rs<1>(O, P + 4 * k, desc_add(dv, k * 2048), 1);
          wg_commit();
        }
        bar_arrive(2 - w, 256);
        wg_wait<2>();
        fence_regs<32>(Q);
      };
      auto release_k = [&]() { release2(B_KE); rbar ^= 8; };
      auto pv_done = [&]() {
        TC(g, 3);
        sched_fence(q_st);
        wg_wait<0>();
        fence_regs<64>(O); fence_regs<32>(P);
        TC(g, 4);
        release2(B_VE);
      };
      auto row_inv = [&](bool go) {
        float a = l0 + __shfl_xor_sync(~0u, l0, 1), b = l1 + __shfl_xor_sync(~0u, l1, 1);
        a += __shfl_xor_sync(~0u, a, 2); b += __shfl_xor_sync(~0u, b, 2);
        const bool ok = __all_sync(~0u, a >= AT_LO && a <= AT_HI && b >= AT_LO && b <= AT_HI) != 0;
        asm("rcp.approx.ftz.f32 %0, %1;" : "=f"(inv[0]) : "f"(a));
        asm("rcp.approx.ftz.f32 %0, %1;" : "=f"(inv[1]) : "f"(b));
        fail |= (uint32_t)(go && !ok) << t;
        l0 = go ? 0.f : l0; l1 = go ? 0.f : l1;
        t += go;
      };
      const uint64_t m_first = 1ull | (1ull << (16 - ti)) | (1ull << 17) | (1ull << (18 + ti));
      const uint64_t m_diag = (3ull << (15 - ti)) | (3ull << (17 + ti));
      enum { F_FIRST = 1, F_DIAG = 2, F_LAST = 4, F_PFIRST = 8, F_PHALF = 16, F_STOP = 32 };
      auto kind = [&](int gn) {
        const uint32_t a = (uint32_t)((m_first << 1) >> gn), d = (uint32_t)((m_diag << 1) >> gn);
        return ((a >> 1) & 1) * F_FIRST | ((d >> 1) & 1) * F_DIAG | ((a >> 2) & 1) * F_LAST | (a & 1) * F_PFIRST |
               (w == 0 ? (d & 1) * F_PHALF | ((d >> 1) & 1) * F_STOP : 0) | (gn == 34 ? F_STOP : 0);
      };
      uint32_t kinds;
      {
        uint32_t qt[64];
#pragma unroll
        for (int i = 0; i < 16; i++) { const uint4 v = packed(i); qt[4 * i] = v.x; qt[4 * i + 1] = v.y; qt[4 * i + 2] = v.z; qt[4 * i + 3] = v.w; }
        fence_regs<64>(qt);
        sched_fence(q_st);
        float S[64];
        wg_fence();
        issue_s(S);
        bar_arrive(w ? 1 : 7, 256);
        bar_sync(6 + w, 256);
        sched_fence(q_st);
        TL(1, 0, tid == 128);
#pragma unroll
        for (int i = 0; i < 16; i++) park(piece(1), i, make_uint4(qt[4 * i], qt[4 * i + 1], qt[4 * i + 2], qt[4 * i + 3]));
        kinds = pinned(kind(lane + 3));
        sched_fence(q_st);
        wg_wait<0>();
        fence_regs<64>(S);
        release_k();
        TL(1, 1, tid == 128);
        const bool kok = mbar_try(B(B_KF + 1), 0);
        at_exp<0, 32>(S);
        sched_fence(q_st);
        at_exp<32, 64>(S); at_fin<0, 64>(S, P);
        if (UNLIKELY(!kok)) mbar_wait_c(B(B_KF + 1), 0);
        TL(1, 2, tid == 128);
      }
      uint32_t f = F_PFIRST, fn;
      auto shadow = [&]() {
        const bool vok = mbar_try(B(B_VF + ((g - 1) & 1)), ((g - 1) >> 1) & 1);
        at_sum(P, f & F_PHALF, l0, l1);
        fn = __shfl_sync(~0u, kinds, max(g - 2, 0));
        if (UNLIKELY(!vok)) mbar_wait_c(B(B_VF + ((g - 1) & 1)), ((g - 1) >> 1) & 1);
      };
      auto hand_over = [&]() { __syncwarp(); if (lane == 0 && !((fail >> (t - 1)) & 1)) mbar_arrive(B(B_PUB + 1 + t)); };
      auto exp_q = [&](float* S, auto kc, auto nc) {
        constexpr int k = decltype(kc)::value, n = decltype(nc)::value;
        asm volatile("{\n.reg .pred p;\nsetp.ne.b32 p, %5, 0;\n@p ldmatrix.sync.aligned.m8n8.x4.shared.b16 {%0,%1,%2,%3}, [%4];\n}"
                     : "+r"(Q[4 * k]), "+r"(Q[4 * k + 1]), "+r"(Q[4 * k + 2]), "+r"(Q[4 * k + 3])
                     : "r"(((q_ld + piece(t + 1)) ^ ((k & 1) << 5)) + (k >> 1) * 4096), "r"(f & F_LAST) : "memory");
        at_exp<n * k, n * k + n>(S);
      };
      g = 1; par = SLOT / 16;
#pragma unroll 1
      for (;;) {
        {
          TC(g, 0); TC(g - 1, 6);
          bar_sync(1 + w, 256);
          fence_regs<32>(Q);
          float S[64];
          wg_fence();
          issue_s(S);
          sched_fence(q_st);
          TC(g, 1);
          shadow();
          fence_regs<64>(O); fence_regs<32>(P);
          issue_pv(f & F_PHALF, ~f & F_PFIRST);
          fence_regs<64>(S);
          TC(g, 2);
          release_k();
          at_exp<0, 8>(S);
          const bool first = f & F_FIRST;
          if (UNLIKELY(f & (F_FIRST | F_LAST))) {
            row_inv(first);
            at_mask(S + 32, (f & F_DIAG) ? wrow - 64 : 64, lane);
            unroll8([&](auto kc) { exp_q(S + 8, kc, std::integral_constant<int, AT_R1 / 8 - 1>{}); });
          } else {
            at_exp<8, AT_R1>(S);
          }
          pv_done();
          g = pinned(g + 1); par = pinned(par ^ (SLOT / 16)); f = fn;
          const bool kok = mbar_try(B(B_KF + (g & 1)), g < 34 ? (g >> 1) & 1 : 0);
          if (UNLIKELY(first)) {
            unroll8([&](auto ic) {
              constexpr int i = decltype(ic)::value, n = (64 - AT_R1) / 8;
              at_exp<AT_R1 + n * i, AT_R1 + n * i + n>(S);
              park(piece(t), i, scaled(i));
            });
            at_fin<0, 64>(S, P);
            hand_over();
          } else {
            at_exp<AT_R1, 64>(S); at_fin<0, 64>(S, P);
          }
          TC(g - 1, 5);
          if (!TCLK) TL(1, 1 + g, tid == 128);
          if (kok && !(f & F_STOP)) continue;
          if (g == 34) break;
          mbar_wait_c(B(B_KF + (g & 1)), (g >> 1) & 1);
        }
#pragma unroll 1
        while (f & F_STOP) {
          TC(g, 0); TC(g - 1, 6);
          shadow();
          const bool first = f & F_FIRST;
          row_inv(first);
          bar_sync(1, 256);
          fence_regs<64>(O); fence_regs<32>(Q); fence_regs<32>(P);
          float S[32];
          const uint64_t dk = desc_add(dk0, par * 16);
          wg_fence();
          mma_n64_rs0(S, Q, dk);
#pragma unroll
          for (int k = 1; k < 8; k++) mma_n64_rs(S, Q + 4 * k, desc_add(dk, (k >> 2) * 16384 + (k & 3) * 32), 1);
          wg_commit();
          TC(g, 1);
          issue_pv(f & F_PHALF, ~f & F_PFIRST);
          fence_regs<32>(S);
          TC(g, 2);
          release_k();
          if (H_LATE) pv_done();
          sched_fence(q_st);
          at_mask(S, wrow, lane);
          unroll8([&](auto kc) { exp_q(S, kc, std::integral_constant<int, 4>{}); });
          if (!H_LATE) pv_done();
          g++; par ^= SLOT / 16; f = fn;
          at_fin<0, 32>(S, P);
          if (first) {
#pragma unroll
            for (int i = 0; i < 8; i++) park(piece(t), i, scaled(i));
            hand_over();
          }
          TC(g - 1, 5);
          if (!TCLK) TL(1, 1 + g, tid == 128);
          mbar_wait_c(B(B_KF + (g & 1)), (g >> 1) & 1);
        }
      }
      TCF();
      const bool wok = mbar_test(B(ffn ? B_WF : B_QP + 1), 0);
      grab(wf, 3 * SLOT, 0, 8);
      mbar_wait_c(B(B_VF + 1), 0);
      bar_sync(1 + w, 256);
      fence_regs<64>(O); fence_regs<32>(P);
      wg_fence();
#pragma unroll
      for (int k = 0; k < 8; k++) mma_n128_rs<1>(O, P + 4 * k, desc_add(dv0, 2 * SLOT + k * 2048), 1);
      wg_commit();
      if (w == 0) bar_arrive(2, 256);
      pin_order(__uint_as_float(wf[28] & wf[24]), pin);
      __syncwarp();
      if (wok) release2(B_WE);
      TL(3, 12 + 16 * w, (tid & 127) == 0);
      sched_fence(q_st);
      at_sum(P, false, l0, l1);
      row_inv(true);
      sched_fence(q_st);
      wg_wait<0>();
      fence_regs<64>(O); fence_regs<32>(P);
      release2(B_VE + 1);
      if (UNLIKELY(!wok || fail != 0)) {
#pragma unroll 1
        for (int tt = 0; tt < 4; tt++) {
          if (!((tt < 3 ? fail >> tt : fail != 0) & 1)) continue;
          slow_tile(O, P, l0, l1, wq, (((tt + 1) & 2) ? ti : 15 - ti) * 128 + wrow, hh + (tt & 2) * 8, lane, q_st);
          row_inv(false);
          if (tt < 3) {
#pragma unroll
            for (int i = 0; i < 8; i++) park(piece(tt + 1), i, scaled(i));
            publish(2 + tt);
          }
        }
        if (!wok) {
          mbar_wait_c(B(ffn ? B_WF : B_QP + 1), 0);
          grab(wf, 3 * SLOT, 0, 8);
          pin_order(__uint_as_float(wf[28] & wf[24]), pin);
          __syncwarp();
          release2(B_WE);
        }
      }
      TL(3, 13 + 16 * w, (tid & 127) == 0);
      issue3(0, 0, 0);
      TL(3, 14 + 16 * w, (tid & 127) == 0);
      TL(1, 36, tid == 128);
    }
    uint32_t hp[32];
    lane = lane_id();
    {
      int st = 1, prev = 0; uint32_t ph = 0;
      __nv_bfloat16* dst = g_qkv + (size_t)((15 - ti) * 128 + cw * 16 + (lane >> 2)) * NQ + (hh + 16) * 128 + (lane & 3) * 8;
      auto kblock = [&](auto between, int lim = 6) {
        issue3(st, ph, 1);
        between();
        wg_wait<1>();
        release2(B_EMPTY3 + prev);
        prev = st;
        if (++st == lim) { st = 0; ph ^= 1; }
      };
      kblock([&]() { TL(3, 15 + 16 * w, (tid & 127) == 0); });
      kblock([&]() { grab(wf + 32, 5 * SLOT, 0, 8); TL(3, 16 + 16 * w, (tid & 127) == 0); });
#pragma unroll 1
      for (int kb = 3; kb < 11; kb++) {
        kblock([&]() {
#pragma unroll
          for (int i = 0; i < 8; i++)
            if (kb == 3 + (i & 4) + (i & 1) * 2 + ((i >> 1) & 1)) *reinterpret_cast<uint4*>(dst + (i & 1) * 8 * NQ + (i >> 1) * 32) = scaled(i);
          TL(3, 14 + kb + 16 * w, (tid & 127) == 0);
          if (kb == 8) TL(2, 2, tid == 128);
        }, kb == 4 ? 5 : 6);
        if (kb == 4) release2(B_EMPTY3 + 5);
      }
      publish(5);
      kblock([&]() { mbar_wait_c(B(ffn ? B_WF2 : B_QP + 2), 0); grab(wf + 32, 5 * SLOT, 8, 16); });
#pragma unroll 1
      for (int kb = 12; kb < G_KB; kb++) {
        kblock([&]() { if ((kb & 7) == 0) TL(2, 1 + (kb >> 3), tid == 128); });
        if (kb == X_KB && lane == 0) mbar_arrive(B(B_XE));
      }
      kblock([&]() {
        mbar_wait_c(B(B_XF), 0);
#pragma unroll
        for (int i = 0; i < 8; i++)
          ldsm4(hp + 4 * i, sb + 6 * SLOT + w * 16384 + ((cw & 3) * 16 + (lane & 15)) * 128 + (i >> 2) * 8192 + ((((i & 3) * 2 + (lane >> 4)) ^ (lane & 7)) << 4));
      });
#pragma unroll 1
      for (int kb = G_KB + 1; kb < 64; kb++) {
        kblock([&]() { if ((kb & 7) == 0) TL(2, 1 + (kb >> 3), tid == 128); });
        if (kb == G_KB + 2 && lane == 0) mbar_arrive(B(B_XE));
      }
    }
    lane = lane_id();
    const int r0 = lane >> 2, q4 = lane & 3, ct = cw * 32 + lane;
    uint32_t tb[16];
    mbar_wait_c(B(B_WR), 0);
#pragma unroll
    for (int i = 0; i < 4; i++) ldsm4(tb + 4 * i, sb + OFF_MISC + 512 + (lane & 1) * 256 + (lane >> 3) * 16 + i * 64);
    mbar_wait_c(B(B_SET2), 0);
    float4* const psd = reinterpret_cast<float4*>(xr + XR_PS + cw * 16 + r0);
    const uint4* const pss = g_xr + (mt * 8 + (ct & 1) * 4) * XR_SIZE + XR_PS + (ct >> 1);
    sched_fence(stg);
    wg_wait<0>();
    fence_regs<64>(acc);
    TL(2, 10, tid == 128);
    {
      float d[2][4] = {}, qa[2][4] = {}, qb[2][4] = {};
#pragma unroll
      for (int j = 0; j < 16; j++) {
        hp[2 * j] = hadd2_bf(hp[2 * j], pack_bf16(acc[4 * j], acc[4 * j + 1]));
        hp[2 * j + 1] = hadd2_bf(hp[2 * j + 1], pack_bf16(acc[4 * j + 2], acc[4 * j + 3]));
        if (j & 1) {
          mma16816(d[(j >> 1) & 1], hp[2 * j - 2], hp[2 * j - 1], hp[2 * j], hp[2 * j + 1], tb[j - 1], tb[j]);
          mma16816(qa[(j >> 1) & 1], hp[2 * j - 2], hp[2 * j - 1], hp[2 * j], hp[2 * j + 1], hp[2 * j - 2], hp[2 * j]);
          mma16816(qb[(j >> 1) & 1], hp[2 * j - 2], hp[2 * j - 1], hp[2 * j], hp[2 * j + 1], hp[2 * j - 1], hp[2 * j + 1]);
        }
      }
      if (q4 == (r0 >> 1)) {
        __stcg(psd, make_float4(d[0][0] + d[1][0], (r0 & 1) ? qa[0][1] + qa[1][1] : qa[0][0] + qa[1][0], d[0][1] + d[1][1], 0.f));
        __stcg(psd + 8, make_float4(d[0][2] + d[1][2], (r0 & 1) ? qb[0][3] + qb[1][3] : qb[0][2] + qb[1][2], d[0][3] + d[1][3], 0.f));
      }
    }
    TL(2, 11, tid == 128);
    mbar_wait_c(B(B_EMPTY3 + 1), 0);
    stage_store_128(stg, lane, hp);
    if (ffn) mbar_wait_c(B(B_WF2), 1);
    grab(wf + 96, 6 * SLOT, 0, 8);
    const float wsum = *reinterpret_cast<const float*>(sp + OFF_MISC + 1024);
    __syncwarp();
    {
      uint4 ps[4];
      poll_chunks(ps, pss, XR_SIZE);
      TL(2, 12, tid == 128);
      auto F = [](uint32_t u) { return __uint_as_float(u); };
      float s1 = (F(ps[0].x) + F(ps[1].x)) + (F(ps[2].x) + F(ps[3].x)), s2 = (F(ps[0].y) + F(ps[1].y)) + (F(ps[2].y) + F(ps[3].y));
      float s3 = (F(ps[0].z) + F(ps[1].z)) + (F(ps[2].z) + F(ps[3].z));
      __syncwarp();
      s1 += __shfl_xor_sync(~0u, s1, 1); s2 += __shfl_xor_sync(~0u, s2, 1); s3 += __shfl_xor_sync(~0u, s3, 1);
      const float mean = s1 * (1.f / DM);
      float mb, inv;
      ln_round(mean, fmaxf(fmaf(s2, 1.f / DM, -mean * mean), 0.f), mb, inv);
      uint32_t u = pack_bf16((s3 - mb * wsum) * inv, 0.f);
      if (u == 0x8000u) u = 0;
      u = (u & 0x8000u) ? (~u & 0xFFFFu) : (u | 0x8000u);
      const uint32_t key = (u << 16) | (0x7FFFu - (mt * 128 + (ct >> 1)));
      const uint32_t nm2 = pack_bf16(-mb, -mb);
      const uint32_t c1 = __reduce_max_sync(~0u, key);
      const uint32_t c2 = __reduce_max_sync(~0u, key == c1 ? 0u : key);
      if (lane == 0) {
        __stcg(reinterpret_cast<uint2*>(xr + XR_KEY) + cw, make_uint2(c1, c2));
        mbar_arrive(B(B_OUT));
      }
      TL(2, 13, tid == 128);
      const int row = (0x7FFF - (((lane >> 4) ? c2 : c1) & 0x7FFF)) & 15;
      const uint32_t rn = __shfl_sync(~0u, nm2, row * 2);
      const float ri = __shfl_sync(~0u, inv, row * 2);
      uint32_t v[4];
#pragma unroll
      for (int i = 0; i < 4; i++)
        asm volatile("ld.shared.u32 %0, [%1];" : "=r"(v[i]) : "r"(stg + ((lane >> 3) & 1) * 8192 + row * 128 + ((((lane & 4) + i) ^ (row & 7)) << 4) + q4 * 4) : "memory");
      __stcg(xr + XR_CAND + cw * 64 + 32 + lane, make_uint4(ln_apply(v[0], rn, ri), ln_apply(v[1], rn, ri), ln_apply(v[2], rn, ri), ln_apply(v[3], rn, ri)));
      __stcg(xr + XR_CAND + cw * 64 + lane, make_uint4(v[0], v[1], v[2], v[3]));
      sched_fence(stg);
      const uint32_t na = __shfl_sync(~0u, nm2, r0 * 2), nb = __shfl_sync(~0u, nm2, r0 * 2 + 16);
      const float ia = __shfl_sync(~0u, inv, r0 * 2), ib = __shfl_sync(~0u, inv, r0 * 2 + 16);
#pragma unroll
      for (int i = 0; i < 32; i++) hp[i] = hadd2_bf(hp[i], ln_apply(hp[i], (i & 1) ? nb : na, (i & 1) ? ib : ia));
      __syncwarp();
      stage_store_128(stg, lane, hp);
      asm volatile("fence.proxy.async.shared::cta;" ::: "memory");
      publish(B_OUT3 - B_PUB);
    }
    uint32_t wd[16][4];
    sched_fence(stg);
    if (ffn) mbar_wait_c(B(B_FULL3 + 5 * w), 1 - w);
    auto load_wd = [&](int h) {
#pragma unroll
      for (int i = h; i < 16; i += 2)
        asm volatile("ldmatrix.sync.aligned.m8n8.x4.trans.shared.b16 {%0,%1,%2,%3}, [%4];"
                     : "=r"(wd[i][0]), "=r"(wd[i][1]), "=r"(wd[i][2]), "=r"(wd[i][3])
                     : "r"(sb + OFF_R3 + 5 * w * SLOT + (2 * (cw & 3) + (i >> 3)) * 4096 + (h * 16 + (lane & 7) + (lane >> 4) * 8) * 128 +
                           (((2 * ((i >> 1) & 3) + ((lane >> 3) & 1)) ^ (lane & 7)) << 4)) : "memory");
    };
    load_wd(0);
    __syncwarp();
    cluster_arrive();
    TL(2, 22, tid == 128);
    mbar_wait_c(B(B_OUT2), 0);
    const uint2 top = *reinterpret_cast<const uint2*>(sp + OFF_MISC);
    TL(2, 14, tid == 128);
    const int t0 = 0x7FFF - (top.x & 0x7FFF), t1 = 0x7FFF - (top.y & 0x7FFF);
    auto cand = [&](int second) {
      const int tk = second ? t1 : t0;
      return g_xr + (tk >> 7) * 8 * XR_SIZE + XR_CAND + ((tk >> 4) & 7) * 64 + ((second && (t0 >> 4) == (t1 >> 4)) ? 16 : 0);
    };
    if (ffn) {
      uint4 xb[2];
      poll_chunks(xb, cand(r0 & 1) + (r0 >> 1) * XR_SIZE + 32 + (cw >> 1) * 4 + q4, 4 * XR_SIZE);
      __syncwarp();
      TL(2, 15, tid == 128);
      float d[8][4] = {};
#pragma unroll
      for (int n = 0; n < 32; n++) {
        if (n == WD_AT) { sched_fence(stg); load_wd(1); }
        const int s = (n >> 4) * 4 + ((n >> 1) & 3), m = ((n >> 3) & 1) * 2 + (n & 1);
        const uint32_t* a = wf + 16 * s + 4 * m;
        mma16816(d[n & 7], a[0], a[1], a[2], a[3], (m & 2) ? xb[s >> 2].z : xb[s >> 2].x, (m & 2) ? xb[s >> 2].w : xb[s >> 2].y);
      }
      float v[8];
#pragma unroll
      for (int i = 0; i < 8; i++) {
        const float lo = (q4 & 1) ? d[2 + (i >> 2)][i & 3] : d[i >> 2][i & 3], hi = (q4 & 1) ? d[6 + (i >> 2)][i & 3] : d[4 + (i >> 2)][i & 3];
        v[i] = (q4 & 2) ? hi : lo;
      }
#pragma unroll
      for (int i = 0; i < 4; i++) v[i] = ((q4 & 2) ? v[i + 4] : v[i]) + __shfl_xor_sync(~0u, (q4 & 2) ? v[i] : v[i + 4], 2);
#pragma unroll
      for (int i = 0; i < 2; i++) v[i] = ((q4 & 1) ? v[i + 2] : v[i]) + __shfl_xor_sync(~0u, (q4 & 1) ? v[i] : v[i + 2], 1);
      float4* red = reinterpret_cast<float4*>(sp + SL_SCR * SLOT);
      reinterpret_cast<float2*>(red + cw * 16 + (q4 >> 1) * 8 + r0)[q4 & 1] = make_float2(v[0], v[1]);
      bar_sync(3, 256);
      TL(2, 16, tid == 128);
      const float4 z0 = red[lane], z1 = red[32 + lane], z2 = red[64 + lane], z3 = red[96 + lane];
      const uint32_t ub = pack_bf16((z0.x + z1.x) + (z2.x + z3.x), (z0.y + z1.y) + (z2.y + z3.y));
      const uint32_t gb = pack_bf16((z0.z + z1.z) + (z2.z + z3.z), (z0.w + z1.w) + (z2.w + z3.w));
      const float g0 = bf_lo(gb), g1 = bf_hi(gb);
      const uint32_t sg = pack_bf16(__fdividef(g0, 1.f + __expf(-g0)), __fdividef(g1, 1.f + __expf(-g1)));
      const uint32_t act = pack_bf16(bf_lo(sg) * bf_lo(ub), bf_hi(sg) * bf_hi(ub));
      const uint32_t pr = __byte_perm(act, __shfl_xor_sync(~0u, act, 1), (lane & 1) ? 0x3276 : 0x5410);
      const int src = q4 * 2 + (r0 & 1);
      const uint32_t a0 = __shfl_sync(~0u, pr, src), a1 = __shfl_sync(~0u, pr, src + 8), a2 = __shfl_sync(~0u, pr, src + 16), a3 = __shfl_sync(~0u, pr, src + 24);
      TL(2, 17, tid == 128);
      float y[8][4] = {};
#pragma unroll
      for (int i = 0; i < 8; i++) mma16816(y[i], wd[2 * i][0], wd[2 * i][1], wd[2 * i][2], wd[2 * i][3], a0, a1);
#pragma unroll
      for (int i = 0; i < 8; i++) mma16816(y[i], wd[2 * i + 1][0], wd[2 * i + 1][1], wd[2 * i + 1][2], wd[2 * i + 1][3], a2, a3);
      float2* yd = reinterpret_cast<float2*>(g_xr + (cw * 16 + 2 * q4) * XR_SIZE + XR_Y + fid * 4) + r0;
#pragma unroll
      for (int j = 0; j < 2; j++) {
        float v[4];
#pragma unroll
        for (int e = 0; e < 4; e++) {
          const float lo = (q4 & 1) ? y[4 * j + 1][e] : y[4 * j][e], hi = (q4 & 1) ? y[4 * j + 3][e] : y[4 * j + 2][e];
          v[e] = (q4 & 2) ? hi : lo;
        }
        __stcg(yd + j * 16 * XR_SIZE, make_float2(v[0], v[1]));
        __stcg(yd + j * 16 * XR_SIZE + 2 * XR_SIZE, make_float2(v[2], v[3]));
      }
    }
    TL(2, 18, tid == 128);
    if (rid == 127 && ct < C_NUM) g_cnt[ct] = 0;
    if (cw < 2) {
      const int tok = (lane >> 1) & 1, pair = cw * 2 + (lane & 1);
      uint4 z[7];
      poll_chunks(z, xr + XR_Y + (lane >> 1) * 4 + pair, 64);
      __syncwarp();
      TL(2, 19, tid == 128);
      mbar_wait_c(B(B_FIN), 0);
      const uint4 op = lds128(sb + OFF_MISC + 128 + (tok * 4 + pair) * 16);
      auto F = [](uint32_t u) { return __uint_as_float(u); };
      const float v0 = ((F(z[0].x) + F(z[1].x)) + (F(z[2].x) + F(z[3].x))) + ((F(z[4].x) + F(z[5].x)) + F(z[6].x));
      const float v1 = ((F(z[0].y) + F(z[1].y)) + (F(z[2].y) + F(z[3].y))) + ((F(z[4].y) + F(z[5].y)) + F(z[6].y));
      const float v2 = ((F(z[0].z) + F(z[1].z)) + (F(z[2].z) + F(z[3].z))) + ((F(z[4].z) + F(z[5].z)) + F(z[6].z));
      const float v3 = ((F(z[0].w) + F(z[1].w)) + (F(z[2].w) + F(z[3].w))) + ((F(z[4].w) + F(z[5].w)) + F(z[6].w));
      float ya = (tok ? v1 : v0) + __shfl_xor_sync(~0u, tok ? v0 : v1, 2), yb = (tok ? v3 : v2) + __shfl_xor_sync(~0u, tok ? v2 : v3, 2);
#pragma unroll
      for (int o = 4; o < 32; o <<= 1) { ya += __shfl_xor_sync(~0u, ya, o); yb += __shfl_xor_sync(~0u, yb, o); }
      const uint32_t yp = pack_bf16(ya, yb);
      if (lane < 4) reinterpret_cast<uint32_t*>(out + (size_t)(tok ? t1 : t0) * DM)[rid * 4 + pair] = hadd2_bf(op.x, hadd2_bf(op.y, pack_bf16(bf_lo(yp) * F(op.z), bf_hi(yp) * F(op.z))));
      TL(2, 21, tid == 128);
    }
    TL(2, 20, tid == 128);
    __syncwarp();
    cluster_wait();
    TL_DUMP();
  }
}

typedef CUresult (*EncodeFn)(CUtensorMap*, CUtensorMapDataType, cuuint32_t, void*, const cuuint64_t*, const cuuint64_t*, const cuuint32_t*,
                             const cuuint32_t*, CUtensorMapInterleave, CUtensorMapSwizzle, CUtensorMapL2promotion, CUtensorMapFloatOOBfill);
EncodeFn g_enc = nullptr;

void map2(CUtensorMap* m, const void* ptr, uint64_t rows, uint64_t cols, uint32_t bc, uint32_t br) {
  const CUtensorMapSwizzle sw = bc == 64 ? CU_TENSOR_MAP_SWIZZLE_128B : CU_TENSOR_MAP_SWIZZLE_64B;
  cuuint64_t gd[2] = {cols, rows}, gs[1] = {cols * 2};
  cuuint32_t bd[2] = {bc, br}, es[2] = {1, 1};
  g_enc(m, CU_TENSOR_MAP_DATA_TYPE_BFLOAT16, 2, (void*)ptr, gd, gs, bd, es, CU_TENSOR_MAP_INTERLEAVE_NONE, sw,
        CU_TENSOR_MAP_L2_PROMOTION_L2_128B, CU_TENSOR_MAP_FLOAT_OOB_FILL_NONE);
}
void map3(CUtensorMap* m, const void* ptr, uint64_t rows, uint64_t cols, uint32_t br, uint32_t bch, uint32_t bc = 64) {
  cuuint64_t gd[3] = {bc, rows, cols / bc}, gs[2] = {cols * 2, bc * 2};
  cuuint32_t bd[3] = {bc, br, bch}, es[3] = {1, 1, 1};
  g_enc(m, CU_TENSOR_MAP_DATA_TYPE_BFLOAT16, 3, (void*)ptr, gd, gs, bd, es, CU_TENSOR_MAP_INTERLEAVE_NONE, bc == 64 ? CU_TENSOR_MAP_SWIZZLE_128B : CU_TENSOR_MAP_SWIZZLE_64B,
        CU_TENSOR_MAP_L2_PROMOTION_L2_128B, CU_TENSOR_MAP_FLOAT_OOB_FILL_NONE);
}

}

extern "C" void kernel_launch(void* const* d_in, const int* in_sizes, int n_in, void* d_out, int out_size) {
  const __nv_bfloat16* x = (const __nv_bfloat16*)d_in[0];
  const __nv_bfloat16* ckv = (const __nv_bfloat16*)d_in[1];
  const __nv_bfloat16* wq = (const __nv_bfloat16*)d_in[2];
  const __nv_bfloat16* wk = (const __nv_bfloat16*)d_in[3];
  const __nv_bfloat16* wv = (const __nv_bfloat16*)d_in[4];
  const __nv_bfloat16* wo = (const __nv_bfloat16*)d_in[5];
  const __nv_bfloat16* w_r = (const __nv_bfloat16*)d_in[7];
  const __nv_bfloat16* wgate = (const __nv_bfloat16*)d_in[8];
  const __nv_bfloat16* wup = (const __nv_bfloat16*)d_in[9];
  const __nv_bfloat16* wdown = (const __nv_bfloat16*)d_in[10];
  __nv_bfloat16* out = (__nv_bfloat16*)d_out;

  if (!g_enc) {
    void* fn = nullptr;
    cudaDriverEntryPointQueryResult qr;
    cudaGetDriverEntryPoint("cuTensorMapEncodeTiled", &fn, cudaEnableDefault, &qr);
    g_enc = (EncodeFn)fn;
    cudaFuncSetAttribute(fused_kernel, cudaFuncAttributeMaxDynamicSharedMemorySize, SMEM_BYTES);
  }
  void *xn, *qkv;
  cudaGetSymbolAddress(&xn, g_xn);
  cudaGetSymbolAddress(&qkv, g_qkv);

  Params p;
  map2(&p.xn, xn, SEQ, DM, 64, 128);
  map2(&p.ckv, ckv, SEQ, DC, 64, 128);
  map3(&p.wq, wq, DM, NQ, 64, 2);
  map3(&p.wk, wk, DC, NQ, 64, 2);
  map3(&p.wv, wv, DC, NQ, 64, 2);
  map3(&p.kv, qkv, 3 * SEQ, NQ, 128, 1);
  map2(&p.ctx_ld, qkv, SEQ, NQ, 64, 128);
  map3(&p.ctx_st, qkv, SEQ, NQ, 64, ST_G, 32);
  map3(&p.wo, wo, NQ, DM, 64, 1);
  map3(&p.x, x, SEQ, DM, 64, 1);
  map3(&p.wd, wdown, FF, DM, 32, 8);
  map2(&p.out, out, SEQ, DM, 64, 64);
  map2(&p.wg, wgate, DM, FF, 32, 128);
  map2(&p.wu, wup, DM, FF, 32, 128);
  fused_kernel<<<128, 384, SMEM_BYTES, cudaStreamPerThread>>>(x, wq, w_r, out, p);
}
```

```cpp
#include <cuda_runtime.h>
#include <cuda_bf16.h>
#include <cuda.h>
#include <stdint.h>
#include <type_traits>

#pragma nv_diag_suppress 549
namespace {

constexpr int SEQ = 2048, DM = 1024, NH = 32, HD = 128, DC = 512, NQ = NH * HD, FF = 3584;

__device__ __align__(1024) __nv_bfloat16 g_xn[SEQ * DM];
__device__ __align__(1024) __nv_bfloat16 g_qkv[3 * SEQ * NQ];
constexpr int XR_PS = 0;
constexpr int XR_KEY = 128;
constexpr int XR_FLAG = 132;
constexpr int XR_CAND = 136;
constexpr int XR_Y = 648;
constexpr int XR_SIZE = 1104;
__device__ __align__(1024) uint4 g_xr[128 * XR_SIZE];
constexpr int C_LN = 0, C_QKV = 16, C_CTX = 32, C_NUM = 64;
__device__ unsigned g_cnt[C_NUM];

#define TL(k, i, cond) do {} while (0)
#define TL_BYTES 0
#define TL_INIT() do {} while (0)
#define TL_DUMP() do {} while (0)
#define TC(g, i) do {} while (0)
#define TCF() do {} while (0)
#define TS(i) do {} while (0)
#undef TCLK
#define TCLK 0

__device__ __forceinline__ uint32_t s2u(const void* p) { return (uint32_t)__cvta_generic_to_shared(p); }
__device__ __forceinline__ void mbar_init(uint32_t b, uint32_t c) { asm volatile("mbarrier.init.shared::cta.b64 [%0], %1;" ::"r"(b), "r"(c) : "memory"); }
__device__ __forceinline__ void mbar_expect(uint32_t b, uint32_t bytes) { asm volatile("mbarrier.arrive.expect_tx.shared::cta.b64 _, [%0], %1;" ::"r"(b), "r"(bytes) : "memory"); }
__device__ __forceinline__ void mbar_arrive(uint32_t b) { asm volatile("mbarrier.arrive.shared::cta.b64 _, [%0];" ::"r"(b) : "memory"); }
__device__ __forceinline__ bool mbar_test(uint32_t b, uint32_t ph) {
  uint32_t ok;
  asm volatile("{\n.reg .pred p;\nmbarrier.test_wait.parity.shared::cta.b64 p, [%1], %2;\nselp.u32 %0, 1, 0, p;\n}" : "=r"(ok) : "r"(b), "r"(ph) : "memory");
  return ok;
}
__device__ __forceinline__ void mbar_wait(uint32_t b, uint32_t ph) {
  asm volatile(
      "{\n.reg .pred p;\n.reg .u32 n;\nmov.u32 n, 0;\n"
      "LW:\nmbarrier.try_wait.parity.shared::cta.b64 p, [%0], %1, 20000;\n@p bra LD;\n"
      "add.u32 n, n, 1;\nsetp.lt.u32 p, n, 0x40000;\n@p bra LW;\ntrap;\nLD:\n}" ::"r"(b), "r"(ph) : "memory");
}
__device__ __forceinline__ void mbar_wait_c(uint32_t b, uint32_t ph) {
  asm volatile(
      "{\n.reg .pred p;\n.reg .u32 n;\nmov.u32 n, 0;\n"
      "LW:\nmbarrier.try_wait.parity.shared::cta.b64 p, [%0], %1;\n@p bra LD;\n"
      "add.u32 n, n, 1;\nsetp.lt.u32 p, n, 0x100000;\n@p bra LW;\ntrap;\nLD:\n}" ::"r"(b), "r"(ph) : "memory");
}
__device__ __forceinline__ bool mbar_try(uint32_t b, uint32_t ph) {
  uint32_t ok;
  asm volatile("{\n.reg .pred p;\nmbarrier.try_wait.parity.shared::cta.b64 p, [%1], %2;\nselp.u32 %0, 1, 0, p;\n}" : "=r"(ok) : "r"(b), "r"(ph) : "memory");
  return ok;
}
#define UNLIKELY(c) __builtin_expect(!!(c), 0)
__device__ __forceinline__ uint32_t pinned(uint32_t v) { uint32_t r; asm volatile("mov.b32 %0, %1;" : "=r"(r) : "r"(v)); return r; }
__device__ __forceinline__ bool elect_one() {
  uint32_t p;
  asm volatile("{\n.reg .pred p;\nelect.sync _|p, 0xFFFFFFFF;\nselp.u32 %0, 1, 0, p;\n}" : "=r"(p));
  return p;
}
__device__ __forceinline__ int lane_id() { int r; asm volatile("mov.u32 %0, %%laneid;" : "=r"(r)); return r; }
template <bool SLEEP = false>
__device__ __forceinline__ void spin_until_ge(const unsigned* p, unsigned target) {
  asm volatile(
      "{\n.reg .pred p, q;\n.reg .u32 n, v;\nmov.u32 n, 0;\nsetp.ne.u32 q, %2, 0;\n"
      "LW:\nld.acquire.gpu.global.u32 v, [%0];\nsetp.ge.u32 p, v, %1;\n@p bra LD;\n@q nanosleep.u32 200;\n"
      "add.u32 n, n, 1;\nsetp.lt.u32 p, n, 0x400000;\n@p bra LW;\ntrap;\nLD:\n}" ::"l"(p), "r"(target), "n"((int)SLEEP) : "memory");
}
#define REPOLL 1
template <int N>
__device__ __forceinline__ void poll_chunks(uint4 (&v)[N], const uint4* p, int stride) {
  uint32_t m[N];
#pragma unroll
  for (int i = 0; i < N; i++) { m[i] = ~0u; v[i] = make_uint4(0, 0, 0, 0); }
#pragma unroll 1
  for (int n = 0; n < 0x400000; n++) {
    uint32_t a = 0;
#pragma unroll
    for (int i = 0; i < N; i++)
      asm volatile("{\n.reg .pred p;\nsetp.eq.u32 p, %5, 0xFFFFFFFF;\n@p ld.relaxed.gpu.global.v4.u32 {%0,%1,%2,%3}, [%4];\n}"
                   : "+r"(v[i].x), "+r"(v[i].y), "+r"(v[i].z), "+r"(v[i].w) : "l"(p + i * stride), "r"(N >= REPOLL ? m[i] : ~0u) : "memory");
#pragma unroll
    for (int i = 0; i < N; i++) { m[i] = max(max(v[i].x, v[i].y), max(v[i].z, v[i].w)); a = max(a, m[i]); }
    if (__all_sync(~0u, a != 0xFFFFFFFFu)) break;
  }
}
__device__ __forceinline__ void fence_async_all() { asm volatile("fence.proxy.async;" ::: "memory"); }
__device__ __forceinline__ void bar_sync(int id, int n) { asm volatile("bar.sync %0, %1;" ::"r"(id), "r"(n) : "memory"); }
__device__ __forceinline__ void bar_arrive(int id, int n) { asm volatile("bar.arrive %0, %1;" ::"r"(id), "r"(n) : "memory"); }
__device__ __forceinline__ void cluster_arrive() { asm volatile("barrier.cluster.arrive.relaxed.aligned;" ::: "memory"); }
__device__ __forceinline__ void cluster_wait() { asm volatile("barrier.cluster.wait.acquire.aligned;" ::: "memory"); }
__device__ __forceinline__ void fence_gpu() { asm volatile("fence.acq_rel.gpu;" ::: "memory"); }
__device__ __forceinline__ void red_add(unsigned* p, unsigned v) { asm volatile("red.relaxed.gpu.global.add.u32 [%0], %1;" ::"l"(p), "r"(v) : "memory"); }
__device__ __forceinline__ void prefetch_tm(const CUtensorMap* m) { asm volatile("prefetch.tensormap [%0];" ::"l"(m) : "memory"); }

__device__ __forceinline__ void tma_ld2(uint32_t dst, const CUtensorMap* m, uint32_t bar, int c0, int c1) {
  asm volatile("cp.async.bulk.tensor.2d.shared::cta.global.mbarrier::complete_tx::bytes [%0], [%1, {%3,%4}], [%2];" ::"r"(dst), "l"(m), "r"(bar), "r"(c0), "r"(c1) : "memory");
}
__device__ __forceinline__ void tma_ld3(uint32_t dst, const CUtensorMap* m, uint32_t bar, int c0, int c1, int c2) {
  asm volatile("cp.async.bulk.tensor.3d.shared::cta.global.mbarrier::complete_tx::bytes [%0], [%1, {%3,%4,%5}], [%2];" ::"r"(dst), "l"(m), "r"(bar), "r"(c0), "r"(c1), "r"(c2) : "memory");
}
__device__ __forceinline__ void tma_ld3_mc(uint32_t dst, const CUtensorMap* m, uint32_t bar, int c0, int c1, int c2, uint16_t mask) {
  asm volatile("cp.async.bulk.tensor.3d.shared::cluster.global.mbarrier::complete_tx::bytes.multicast::cluster [%0], [%1, {%3,%4,%5}], [%2], %6;" ::"r"(dst), "l"(m), "r"(bar), "r"(c0), "r"(c1), "r"(c2), "h"(mask) : "memory");
}
__device__ __forceinline__ void tma_pf3(const CUtensorMap* m, int c0, int c1, int c2) {
  asm volatile("cp.async.bulk.prefetch.tensor.3d.L2.global [%0, {%1,%2,%3}];" ::"l"(m), "r"(c0), "r"(c1), "r"(c2) : "memory");
}
__device__ __forceinline__ void l2_prefetch(const void* p, uint32_t bytes) { asm volatile("cp.async.bulk.prefetch.L2.global [%0], %1;" ::"l"(p), "r"(bytes) : "memory"); }

__device__ __forceinline__ void wg_fence() { asm volatile("wgmma.fence.sync.aligned;" ::: "memory"); }
__device__ __forceinline__ void wg_commit() { asm volatile("wgmma.commit_group.sync.aligned;" ::: "memory"); }
template <int N> __device__ __forceinline__ void wg_wait() { asm volatile("wgmma.wait_group.sync.aligned %0;" ::"n"(N) : "memory"); }
template <int N> __device__ __forceinline__ void reg_alloc() { asm volatile("setmaxnreg.inc.sync.aligned.u32 %0;" ::"n"(N)); }
template <int N> __device__ __forceinline__ void reg_dealloc() { asm volatile("setmaxnreg.dec.sync.aligned.u32 %0;" ::"n"(N)); }
template <int N> __device__ __forceinline__ void fence_regs(float* d) {
#pragma unroll
  for (int i = 0; i < N; i++) asm volatile("" : "+f"(d[i])::"memory");
}
template <int N> __device__ __forceinline__ void fence_regs(uint32_t* d) {
#pragma unroll
  for (int i = 0; i < N; i++) asm volatile("" : "+r"(d[i])::"memory");
}

__device__ __forceinline__ uint64_t mk_desc(uint32_t addr, uint32_t lbo, uint32_t sbo, uint32_t swz) {
  uint32_t lo = ((addr & 0x3FFFF) >> 4) | ((lbo >> 4) << 16);
  uint32_t hi = (sbo >> 4) | (swz << 30);
  return ((uint64_t)hi << 32) | lo;
}
__device__ __forceinline__ uint64_t desc_add(uint64_t d, uint32_t bytes) {
  uint32_t lo = (uint32_t)d + (bytes >> 4);
  return (d & 0xFFFFFFFF00000000ull) | lo;
}

#define R8(b) "+f"(d[b + 0]), "+f"(d[b + 1]), "+f"(d[b + 2]), "+f"(d[b + 3]), "+f"(d[b + 4]), "+f"(d[b + 5]), "+f"(d[b + 6]), "+f"(d[b + 7])
#define REGS32 "%0,%1,%2,%3,%4,%5,%6,%7,%8,%9,%10,%11,%12,%13,%14,%15,%16,%17,%18,%19,%20,%21,%22,%23,%24,%25,%26,%27,%28,%29,%30,%31"
#define REGS64 REGS32 ",%32,%33,%34,%35,%36,%37,%38,%39,%40,%41,%42,%43,%44,%45,%46,%47,%48,%49,%50,%51,%52,%53,%54,%55,%56,%57,%58,%59,%60,%61,%62,%63"
#define REGS128 REGS64 ",%64,%65,%66,%67,%68,%69,%70,%71,%72,%73,%74,%75,%76,%77,%78,%79,%80,%81,%82,%83,%84,%85,%86,%87,%88,%89,%90,%91,%92,%93,%94,%95," \
               "%96,%97,%98,%99,%100,%101,%102,%103,%104,%105,%106,%107,%108,%109,%110,%111,%112,%113,%114,%115,%116,%117,%118,%119,%120,%121,%122,%123,%124,%125,%126,%127"

template <int TB>
__device__ __forceinline__ void mma_n256_ss(float (&d)[128], uint64_t a, uint64_t b, int acc) {
  asm volatile("{\n.reg .pred p;\nsetp.ne.b32 p, %130, 0;\n"
               "wgmma.mma_async.sync.aligned.m64n256k16.f32.bf16.bf16 {" REGS128 "}, %128, %129, p, 1, 1, 0, %131;\n}\n"
               : R8(0), R8(8), R8(16), R8(24), R8(32), R8(40), R8(48), R8(56), R8(64), R8(72), R8(80), R8(88), R8(96), R8(104), R8(112), R8(120)
               : "l"(a), "l"(b), "r"(acc), "n"(TB));
}
template <int TB>
__device__ __forceinline__ void mma_n128_ss(float* d, uint64_t a, uint64_t b, int acc) {
  asm volatile("{\n.reg .pred p;\nsetp.ne.b32 p, %66, 0;\n"
               "wgmma.mma_async.sync.aligned.m64n128k16.f32.bf16.bf16 {" REGS64 "}, %64, %65, p, 1, 1, 0, %67;\n}\n"
               : R8(0), R8(8), R8(16), R8(24), R8(32), R8(40), R8(48), R8(56)
               : "l"(a), "l"(b), "r"(acc), "n"(TB));
}
template <int TB>
__device__ __forceinline__ void mma_n128_rs(float* d, const uint32_t* a, uint64_t b, int acc) {
  asm volatile("{\n.reg .pred p;\nsetp.ne.b32 p, %69, 0;\n"
               "wgmma.mma_async.sync.aligned.m64n128k16.f32.bf16.bf16 {" REGS64 "}, {%64,%65,%66,%67}, %68, p, 1, 1, %70;\n}\n"
               : R8(0), R8(8), R8(16), R8(24), R8(32), R8(40), R8(48), R8(56)
               : "r"(a[0]), "r"(a[1]), "r"(a[2]), "r"(a[3]), "l"(b), "r"(acc), "n"(TB));
}
__device__ __forceinline__ void mma_n64_rs(float* d, const uint32_t* a, uint64_t b, int acc) {
  asm volatile("{\n.reg .pred p;\nsetp.ne.b32 p, %37, 0;\n"
               "wgmma.mma_async.sync.aligned.m64n64k16.f32.bf16.bf16 {" REGS32 "}, {%32,%33,%34,%35}, %36, p, 1, 1, 0;\n}\n"
               : R8(0), R8(8), R8(16), R8(24)
               : "r"(a[0]), "r"(a[1]), "r"(a[2]), "r"(a[3]), "l"(b), "r"(acc));
}
#define W8(b) "=f"(d[b + 0]), "=f"(d[b + 1]), "=f"(d[b + 2]), "=f"(d[b + 3]), "=f"(d[b + 4]), "=f"(d[b + 5]), "=f"(d[b + 6]), "=f"(d[b + 7])
__device__ __forceinline__ void mma_n128_rs0(float* d, const uint32_t* a, uint64_t b) {
  asm volatile("wgmma.mma_async.sync.aligned.m64n128k16.f32.bf16.bf16 {" REGS64 "}, {%64,%65,%66,%67}, %68, 0, 1, 1, 0;\n"
               : W8(0), W8(8), W8(16), W8(24), W8(32), W8(40), W8(48), W8(56)
               : "r"(a[0]), "r"(a[1]), "r"(a[2]), "r"(a[3]), "l"(b));
}
__device__ __forceinline__ void mma_n64_rs0(float* d, const uint32_t* a, uint64_t b) {
  asm volatile("wgmma.mma_async.sync.aligned.m64n64k16.f32.bf16.bf16 {" REGS32 "}, {%32,%33,%34,%35}, %36, 0, 1, 1, 0;\n"
               : W8(0), W8(8), W8(16), W8(24)
               : "r"(a[0]), "r"(a[1]), "r"(a[2]), "r"(a[3]), "l"(b));
}
__device__ __forceinline__ uint32_t pack_bf16(float lo, float hi) {
  uint32_t r;
  asm("cvt.rn.bf16x2.f32 %0, %1, %2;" : "=r"(r) : "f"(hi), "f"(lo));
  return r;
}
__device__ __forceinline__ float bf_lo(uint32_t v) { return __uint_as_float(v << 16); }
__device__ __forceinline__ float bf_hi(uint32_t v) { return __uint_as_float(v & 0xFFFF0000u); }
__device__ __forceinline__ float bf_round(float v) { return bf_lo(pack_bf16(v, v)); }
__device__ __forceinline__ void stsm4(uint32_t addr, uint32_t r0, uint32_t r1, uint32_t r2, uint32_t r3) {
  asm volatile("stmatrix.sync.aligned.m8n8.x4.shared.b16 [%0], {%1,%2,%3,%4};" ::"r"(addr), "r"(r0), "r"(r1), "r"(r2), "r"(r3) : "memory");
}
__device__ __forceinline__ uint4 lds128(uint32_t addr) {
  uint4 v;
  asm volatile("ld.shared.v4.u32 {%0,%1,%2,%3}, [%4];" : "=r"(v.x), "=r"(v.y), "=r"(v.z), "=r"(v.w) : "r"(addr));
  return v;
}
__device__ __forceinline__ float ex2(float x) {
  float y;
  asm("ex2.approx.ftz.f32 %0, %1;" : "=f"(y) : "f"(x));
  return y;
}
__device__ __forceinline__ void pin_order(float v, uint32_t dummy) {
  asm volatile("{\n.reg .pred p;\nsetp.eq.b32 p, %0, 0xFFFFFFFF;\n@p st.shared.b32 [%1], %0;\n}" ::"r"(__float_as_uint(v)), "r"(dummy) : "memory");
}
__device__ __forceinline__ void sched_fence(uint32_t dummy) {
  asm volatile("{\n.reg .pred p;\n.reg .u32 c;\nsetp.eq.b32 p, %0, 0xFFFFFFFF;\nmov.u32 c, %%clock;\n@p st.shared.b32 [%0], c;\n}" ::"r"(dummy) : "memory");
}
__device__ __forceinline__ void idle(int n) {
  asm volatile("{\n.reg .pred p;\n.reg .u32 a, b;\nmov.u32 a, %%clock;\nLI:\nmov.u32 b, %%clock;\nsub.u32 b, b, a;\nsetp.lt.u32 p, b, %0;\n@p bra LI;\n}" ::"r"(n) : "memory");
}
__device__ __forceinline__ void stage_store_128(uint32_t base, int lane, const uint32_t* pk) {
  const int row = (lane & 7) + ((lane >> 3) & 1) * 8;
  const uint32_t rb = base + row * 128;
  const int hi = lane >> 4;
#pragma unroll
  for (int j = 0; j < 8; j++) {
    const int chunk = 2 * j + hi;
    const uint32_t a = rb + (j >> 2) * 8192 + (((chunk & 7) ^ (lane & 7)) << 4);
    stsm4(a, pk[4 * j + 0], pk[4 * j + 1], pk[4 * j + 2], pk[4 * j + 3]);
  }
}
__device__ __forceinline__ void ln_round(float mean, float var, float& m_bf, float& inv_s) {
  const uint32_t mv = pack_bf16(mean, var);
  m_bf = bf_lo(mv);
  float sq, rc;
  asm("sqrt.approx.f32 %0, %1;" : "=f"(sq) : "f"(bf_round(bf_hi(mv) + 1e-5f)));
  asm("rcp.approx.ftz.f32 %0, %1;" : "=f"(rc) : "f"(bf_round(sq)));
  inv_s = rc;
}
__device__ __forceinline__ uint32_t hadd2_bf(uint32_t a, uint32_t b) {
  uint32_t r;
  asm("add.rn.bf16x2 %0, %1, %2;" : "=r"(r) : "r"(a), "r"(b));
  return r;
}
__device__ __forceinline__ uint32_t ln_apply(uint32_t h, uint32_t nm2, float inv_s) {
  const uint32_t d = hadd2_bf(h, nm2);
  return pack_bf16(bf_lo(d) * inv_s, bf_hi(d) * inv_s);
}
__device__ __forceinline__ void ldsm4(uint32_t* r, uint32_t addr) {
  asm volatile("ldmatrix.sync.aligned.m8n8.x4.shared.b16 {%0,%1,%2,%3}, [%4];" : "=r"(r[0]), "=r"(r[1]), "=r"(r[2]), "=r"(r[3]) : "r"(addr) : "memory");
}
__device__ __forceinline__ void mma16816(float* d, uint32_t a0, uint32_t a1, uint32_t a2, uint32_t a3, uint32_t b0, uint32_t b1) {
  asm volatile("mma.sync.aligned.m16n8k16.row.col.f32.bf16.bf16.f32 {%0,%1,%2,%3}, {%4,%5,%6,%7}, {%8,%9}, {%0,%1,%2,%3};"
               : "+f"(d[0]), "+f"(d[1]), "+f"(d[2]), "+f"(d[3]) : "r"(a0), "r"(a1), "r"(a2), "r"(a3), "r"(b0), "r"(b1));
}

template <class F>
__device__ __forceinline__ void unroll8(F f) {
  f(std::integral_constant<int, 0>{}); f(std::integral_constant<int, 1>{}); f(std::integral_constant<int, 2>{}); f(std::integral_constant<int, 3>{});
  f(std::integral_constant<int, 4>{}); f(std::integral_constant<int, 5>{}); f(std::integral_constant<int, 6>{}); f(std::integral_constant<int, 7>{});
}

constexpr float AT_C = 0.08838834764831845f * 1.4426950408889634f;
#define AT_LO 0x1p-40f
#define AT_HI 0x1p40f
#define H_LATE 1
#define AT_R1 48
template <int I0, int I1>
__device__ __forceinline__ void at_exp(float* S) {
#pragma unroll
  for (int i = I0; i < I1; i++) asm volatile("ex2.approx.ftz.f32 %0, %0;" : "+f"(S[i]));
}
template <int I0, int I1>
__device__ __forceinline__ void at_fin(const float* S, uint32_t* P) {
#pragma unroll
  for (int i = I0; i < I1; i += 4) {
    P[i / 2] = pack_bf16(S[i], S[i + 1]); P[i / 2 + 1] = pack_bf16(S[i + 2], S[i + 3]);
  }
}
__device__ __forceinline__ void at_sum(const uint32_t* P, bool half, float& l0, float& l1) {
  uint32_t u[4];
#pragma unroll
  for (int r = 0; r < 4; r++) {
    const uint32_t* q = P + (r >> 1) * 16 + (r & 1);
    u[r] = hadd2_bf(hadd2_bf(hadd2_bf(q[0], q[2]), hadd2_bf(q[4], q[6])), hadd2_bf(hadd2_bf(q[8], q[10]), hadd2_bf(q[12], q[14])));
  }
  u[0] = hadd2_bf(u[0], half ? 0u : u[2]);
  u[1] = hadd2_bf(u[1], half ? 0u : u[3]);
  l0 += bf_lo(u[0]) + bf_hi(u[0]);
  l1 += bf_lo(u[1]) + bf_hi(u[1]);
}
__device__ __forceinline__ void at_mask(float* S, int r, int lane) {
  const int d = r + (lane >> 2) - (lane & 3) * 2;
#pragma unroll
  for (int j = 0; j < 8; j++) {
    float dummy0 = 0.f, dummy1 = 0.f;
    float& lo0 = j < 7 ? S[4 * (j < 7 ? j + 1 : j) + 2] : dummy0;
    float& lo1 = j < 7 ? S[4 * (j < 7 ? j + 1 : j) + 3] : dummy1;
    asm("{\n.reg .pred p, q;\nsetp.lt.s32 p, %4, %5;\nsetp.le.s32 q, %4, %5;\n"
        "@p add.f32 %0, %0, 0fFF800000;\n@q add.f32 %1, %1, 0fFF800000;\n@p add.f32 %2, %2, 0fFF800000;\n@q add.f32 %3, %3, 0fFF800000;\n}"
        : "+f"(S[4 * j]), "+f"(S[4 * j + 1]), "+f"(lo0), "+f"(lo1) : "r"(d), "r"(8 * j));
  }
}
__device__ __forceinline__ uint32_t ldg32(const __nv_bfloat16* p) { return __ldcg(reinterpret_cast<const uint32_t*>(p)); }
__device__ __forceinline__ uint32_t ldg16x2(const __nv_bfloat16* p, int stride) {
  return (uint32_t)__ldcg(reinterpret_cast<const unsigned short*>(p)) | ((uint32_t)__ldcg(reinterpret_cast<const unsigned short*>(p + stride)) << 16);
}
__device__ __forceinline__ void slow_tile(float* O, uint32_t* Q, float& l0, float& l1, const __nv_bfloat16* wq, int row0, int head, int lane, uint32_t dummy) {
  const int r = lane >> 2, q = lane & 3;
#pragma unroll
  for (int i = 0; i < 64; i++) O[i] = 0.f;
  {
    const __nv_bfloat16* xa = g_xn + (size_t)(row0 + r) * DM + 2 * q;
    const __nv_bfloat16* wb = wq + (size_t)(2 * q) * NQ + head * HD + (r >> 1) * 8 + (r & 1);
#pragma unroll 1
    for (int k = 0; k < DM; k += 16) {
      const uint32_t a0 = ldg32(xa + k), a1 = ldg32(xa + k + 8 * DM), a2 = ldg32(xa + k + 8), a3 = ldg32(xa + k + 8 * DM + 8);
#pragma unroll
      for (int j = 0; j < 16; j++) {
        const __nv_bfloat16* wp = wb + (size_t)k * NQ + (j >> 2) * 32 + (j & 3) * 2;
        mma16816(O + 4 * j, a0, a1, a2, a3, ldg16x2(wp, NQ), ldg16x2(wp + 8 * NQ, NQ));
        if (j == 7) sched_fence(dummy);
      }
    }
  }
#pragma unroll
  for (int i = 0; i < 32; i++) Q[i] = pack_bf16(O[2 * i], O[2 * i + 1]);
#pragma unroll
  for (int i = 0; i < 64; i++) O[i] = 0.f;
  float m0 = -INFINITY, m1 = -INFINITY;
  l0 = l1 = 0.f;
#pragma unroll 1
  for (int kv = 0; kv <= row0; kv += 16) {
    float s[8] = {0.f, 0.f, 0.f, 0.f, 0.f, 0.f, 0.f, 0.f};
    const __nv_bfloat16* kp = g_qkv + (size_t)(SEQ + kv + r) * NQ + head * HD + 2 * q;
#pragma unroll
    for (int k = 0; k < 8; k++) {
      mma16816(s, Q[4 * k], Q[4 * k + 1], Q[4 * k + 2], Q[4 * k + 3], ldg32(kp + 16 * k), ldg32(kp + 16 * k + 8));
      mma16816(s + 4, Q[4 * k], Q[4 * k + 1], Q[4 * k + 2], Q[4 * k + 3], ldg32(kp + 8 * NQ + 16 * k), ldg32(kp + 8 * NQ + 16 * k + 8));
    }
#pragma unroll
    for (int i = 0; i < 8; i++)
      if (kv + (i >> 2) * 8 + 2 * q + (i & 1) > row0 + r + (i & 2) * 4) s[i] = -INFINITY;
    float a = fmaxf(fmaxf(fmaxf(s[0], s[1]), fmaxf(s[4], s[5])), m0), b = fmaxf(fmaxf(fmaxf(s[2], s[3]), fmaxf(s[6], s[7])), m1);
    a = fmaxf(a, __shfl_xor_sync(~0u, a, 1)); b = fmaxf(b, __shfl_xor_sync(~0u, b, 1));
    a = fmaxf(a, __shfl_xor_sync(~0u, a, 2)); b = fmaxf(b, __shfl_xor_sync(~0u, b, 2));
    const float c0 = ex2(m0 - a), c1 = ex2(m1 - b);
    m0 = a; m1 = b;
#pragma unroll
    for (int i = 0; i < 8; i++) s[i] = ex2(s[i] - ((i & 2) ? b : a));
    l0 = l0 * c0 + (s[0] + s[1]) + (s[4] + s[5]);
    l1 = l1 * c1 + (s[2] + s[3]) + (s[6] + s[7]);
    sched_fence(dummy);
    const uint32_t p0 = pack_bf16(s[0], s[1]), p1 = pack_bf16(s[2], s[3]), p2 = pack_bf16(s[4], s[5]), p3 = pack_bf16(s[6], s[7]);
    const __nv_bfloat16* vp = g_qkv + (size_t)(2 * SEQ + kv + 2 * q) * NQ + head * HD + r;
#pragma unroll
    for (int j = 0; j < 16; j++) {
      O[4 * j] *= c0; O[4 * j + 1] *= c0; O[4 * j + 2] *= c1; O[4 * j + 3] *= c1;
      mma16816(O + 4 * j, p0, p1, p2, p3, ldg16x2(vp + 8 * j, NQ), ldg16x2(vp + 8 * NQ + 8 * j, NQ));
      if (j == 7) sched_fence(dummy);
    }
  }
}

constexpr int P1_STAGE = 49152;
constexpr int SLOT = 32768;
constexpr int OFF_LN = 6 * SLOT, OFF_R3 = 0;
constexpr int OFF_BAR = 229376;
constexpr int OFF_MISC = OFF_BAR + 8 * 58;
constexpr int SMEM_BYTES = OFF_MISC + 2080 + TL_BYTES;
enum : int {
  B_FULL1 = 0, B_KF = 4, B_VF = 6, B_FULL3 = 8, B_XF = 14, B_LN = 15, B_DEP = 16, B_OUT2 = 22, B_FIN = 23, B_SET = 24, B_SET2 = 25, B_QP = 26, B_WF2 = 29,
  B_WF = 30, B_WR = 31,
  B_LND = 32,
  B_XE = 33, B_PUB = 34, B_OUT = 40, B_OUT3 = 41,
  B_EMPTY1 = 42, B_KE = 46, B_VE = 48, B_EMPTY3 = 50, B_WE = 56, B_NUM = 57
};
#define PRE 3
#define LN_PF 4
#define LN_LD 9
constexpr int LN_PFN = 2;
constexpr int OFF_STG = SLOT, SL_SCR = 2;
#define SET_NS 50
#define ST_G 1
#define ST_NS 0
#define OBS 99
#define PFALL 0
#define WQ_D 4
#define WQ_0 18
#define SL_NS 600
#define X_KB 20
#define G_KB 35
#define WD_AT 8
#define YD 700
#define OUT_R 64
#define OUT_CLK 500
#define W_G0 22
#define KVPF 1
struct Params {
  CUtensorMap xn, ckv, wq, wk, wv, kv, ctx_ld, ctx_st, wo, x, wd, wg, wu, out;
};

__global__ void __cluster_dims__(2, 1, 1) __launch_bounds__(384, 1)
fused_kernel(const __nv_bfloat16* __restrict__ x, const __nv_bfloat16* __restrict__ wq, const __nv_bfloat16* __restrict__ w_r,
             __nv_bfloat16* __restrict__ out, const __grid_constant__ Params p) {
  extern __shared__ __align__(1024) uint8_t sp[];
  const uint32_t sb = s2u(sp);
  const uint32_t bar = sb + OFF_BAR;
  auto B = [&](int i) { return bar + 8 * i; };
  const int tid = threadIdx.x, warp = __shfl_sync(~0u, tid >> 5, 0), wg = warp >> 2, lane = tid & 31;
  const int cta = blockIdx.x, rank = cta & 1, cl = cta >> 1;
  const int mp = cl < 4 ? 1 : (cl < 36 ? (cl & 7) : (0x3207654 >> (4 * ((cl - 36) % 7))) & 7);
  const int gq = cl < 4 ? 4 + cl : (cl < 36 ? (cl - 4) >> 3 : 4 + (cl - 36) / 7);
  const int mt = 2 * mp + rank;
  const int ti = (gq & 3) * 2 + rank, hh = mp * 2 + (gq >> 2);
  const int rid = mt * 8 + gq;
  const int fid = mt * 7 + gq;
  const bool ffn = gq < 7;
  uint4* const xr = g_xr + rid * XR_SIZE;
  TL_INIT();
  TL(0, 0, tid == 128);
  if (warp == 0) {
    if (elect_one()) {
#pragma unroll
      for (int kb = 0; kb < PRE; kb++) mbar_init(B(B_FULL1 + kb), 1);
      asm volatile("fence.mbarrier_init.release.cluster;" ::: "memory");
    }
    __syncwarp();
    cluster_arrive();
    if (elect_one()) {
#pragma unroll
      for (int kb = 0; kb < PRE; kb++) {
        mbar_expect(B(B_FULL1 + kb), P1_STAGE);
        tma_ld2(sb + kb * P1_STAGE, &p.ckv, B(B_FULL1 + kb), kb * 64, mt * 128);
        tma_ld3(sb + kb * P1_STAGE + 16384 + rank * 16384, &p.wk, B(B_FULL1 + kb), 0, kb * 64, gq * 4 + rank * 2);
        tma_ld3(sb + kb * P1_STAGE + 32768 - rank * 16384, &p.wk, B(B_FULL1 + kb), 0, kb * 64, gq * 4 + 2 - rank * 2);
      }
    }
  } else if (elect_one()) {
#pragma unroll 1
    for (int i = PRE + warp - 1; i < B_NUM; i += 11)
      mbar_init(B(i), i >= B_EMPTY1 ? 16 : (i >= B_XE ? 8 : (i == B_LND ? 3 : (i >= B_WF ? 2 : 1))));
    asm volatile("fence.mbarrier_init.release.cluster;" ::: "memory");
  }
  __syncwarp();
  if (warp) cluster_arrive();
  if (wg == 0) {
    reg_dealloc<40>();
    if (warp == 1 && elect_one()) {
      if (mt >= 2 * PRE) tma_pf3(&p.wk, 0, mp * 64, gq * 4 + rank * 2);
      if (gq >= PRE) asm volatile("cp.async.bulk.prefetch.tensor.2d.L2.global [%0, {%1,%2}];" ::"l"(&p.ckv), "r"(gq * 64), "r"(mt * 128) : "memory");
    } else if (warp == 2 && elect_one()) {
      prefetch_tm(&p.wv); prefetch_tm(&p.wq); prefetch_tm(&p.xn);
    }
    __syncwarp();
    cluster_wait();
    if (warp == 0) {
      int st = 0; uint32_t ph = 1;
#pragma unroll 1
      for (int t = 0; t < 6; t++) {
        const CUtensorMap* ma = t >= 4 ? &p.xn : &p.ckv;
        const CUtensorMap* mb = t >= 4 ? &p.wq : ((t & 1) ? &p.wv : &p.wk);
        const int nk = t >= 4 ? 16 : 8;
        const int row = (t < 4 ? mt : (t == 4 ? 15 - ti : ti)) * 128;
        const int col = t < 4 ? (gq + (t >> 1) * 8) * 4 + rank * 2 : (hh + rank * 16) * 2;
        if (t >= 4) mbar_wait(B(B_DEP + t - 4), 0);
#pragma unroll 1
        for (int kb = 0; kb < nk; kb++) {
          const uint32_t d = sb + st * P1_STAGE, fb = B(B_FULL1 + st);
          const int n = t * 8 + kb;
          if (n >= PRE) {
            mbar_wait_c(B(B_EMPTY1 + st), ph);
            if (elect_one()) {
              mbar_expect(fb, P1_STAGE);
              tma_ld2(d, ma, fb, kb * 64, row);
              tma_ld3_mc(d + 16384 + rank * 16384, mb, fb, 0, kb * 64, col, 3);
            }
          }
          if (t < 5 && elect_one()) {
            if (n >= LN_PF && n < LN_PF + LN_PFN) l2_prefetch(x + (size_t)cta * 16 * DM + (n - LN_PF) * (16 * DM / LN_PFN), 32768 / LN_PFN);
            if (n == LN_LD) {
              mbar_expect(B(B_LN), 32768);
              asm volatile("cp.async.bulk.shared::cluster.global.mbarrier::complete_tx::bytes [%0], [%1], %2, [%3];" ::"r"(sb + OFF_LN),
                           "l"(x + (size_t)cta * 16 * DM), "r"(32768), "r"(B(B_LN)) : "memory");
            }
            if (t < 3 && kb == 0) tma_pf3((t & 1) ? &p.wk : &p.wv, 0, mp * 64, (gq + ((t + 1) >> 1) * 8) * 4 + rank * 2);
            if (n >= WQ_0 && n < WQ_0 + 4 * WQ_D && (n - WQ_0) % WQ_D == 0) tma_pf3(&p.wq, 0, ((n - WQ_0) / WQ_D * 4 + (gq & 3)) * 64, (hh + rank * 16) * 2);
          }
          if (++st == 4) { st = 0; ph ^= 1; }
        }
      }
      if (elect_one()) { prefetch_tm(&p.kv); prefetch_tm(&p.ctx_ld); prefetch_tm(&p.wo); prefetch_tm(&p.wg); prefetch_tm(&p.wu); }
      auto load_kv = [&](int g, int isv) {
        const int h2 = g >= 17, sx = g - 17 * h2, n1 = h2 ? ti + 1 : 16 - ti;
        const int row = (1 + isv) * SEQ + (sx < n1 ? sx : 16 - sx) * 128, col = (hh + 16 * h2) * 2;
        const uint32_t d = sb + (isv ? 2 + 2 * (g & 1) : (g & 1)) * SLOT, fb = B(B_KF + 2 * isv + (g & 1));
        const bool shared = sx != (h2 ? (ti & 6) + 1 : 15 - (ti & 6));
        const int g2 = g + KVPF, h3 = g2 >= 17, s3 = g2 - 17 * h3;
        const int pb = PFALL ? (g2 < 34 ? (s3 < (h3 ? ti + 1 : 16 - ti) ? s3 : 16 - s3) : -1)
                             : (ti < 2 ? (h3 ? (s3 >= 1 && s3 <= 8 ? 16 - s3 : -1) : (s3 < 16 ? s3 : -1)) : (ti >= 6 && h3 && s3 < 8 ? s3 : -1));
        mbar_wait_c(g < 2 ? B(B_EMPTY1 + (isv ? 1 + 2 * g : g)) : B(B_KE + 2 * isv + (g & 1)), g < 2 ? 1 : ((g >> 1) & 1) ^ 1);
        if (elect_one()) {
          mbar_expect(fb, SLOT);
          if (shared) {
            tma_ld3_mc(d + rank * 16384, &p.kv, fb, 0, row, col + rank, 3);
          } else {
            tma_ld3(d, &p.kv, fb, 0, row, col);
            tma_ld3(d + 16384, &p.kv, fb, 0, row, col + 1);
          }
          if (KVPF && pb >= 0) tma_pf3(&p.kv, 0, (1 + isv) * SEQ + pb * 128, (hh + 16 * h3) * 2 + rank);
        }
      };
      int nw = ffn ? 0 : 12;
      auto load_w = [&]() {
        const int c = nw < 8 ? (nw >> 2) + (nw & 2) : nw >> 1;
        if (elect_one()) {
          if (!(nw & 3)) mbar_expect(B(B_WF - (nw >> 3)), 32768);
          tma_ld2(sb + (c < 2 ? 3 : 4) * SLOT + c * 16384 + (nw & 1) * 8192, (nw & 1) ? &p.wg : &p.wu, B(B_WF - (nw >> 3)), fid * 32, c * 128);
        }
        nw++;
      };
#pragma unroll 1
      for (int g = 0; g < 34; g++) {
        if (g == 0 || g == 17 - KVPF) mbar_wait(B(B_DEP + 2 + (g > 0)), 0);
        load_kv(g, 0);
        if (g > 0) load_kv(g - 1, 1);
        if (g >= W_G0 && nw < 12 && __any_sync(~0u, mbar_test(B(B_QP + (nw >> 2)), 0))) load_w();
      }
      load_kv(33, 1);
#pragma unroll 1
      while (nw < 12) { mbar_wait(B(B_QP + (nw >> 2)), 0); load_w(); }
      if (elect_one()) { prefetch_tm(&p.wd); prefetch_tm(&p.x); prefetch_tm(&p.out); }
      auto load3 = [&](int kb, int sl) {
        if (elect_one()) {
          mbar_expect(B(B_FULL3 + sl), SLOT);
          tma_ld2(sb + OFF_R3 + sl * SLOT, &p.ctx_ld, B(B_FULL3 + sl), kb * 64, mt * 128);
          tma_ld3_mc(sb + OFF_R3 + sl * SLOT + 16384 + rank * 8192, &p.wo, B(B_FULL3 + sl), 0, kb * 64, gq * 2 + rank, 3);
          if (kb >= OBS && kb < OBS + 11) TL(0, 32 + kb - OBS, true);
        }
      };
      mbar_wait(B(B_DEP + 4), 0);
#pragma unroll
      for (int kb = 0; kb < 5; kb++) {
        mbar_wait_c(B(kb == 3 ? B_WE : (kb == 4 ? B_VE + 1 : B_KE + kb)), 0);
        load3(kb, kb);
      }
      if (elect_one()) mbar_arrive(B(B_FULL3 + 5));
#pragma unroll 1
      for (int r = 1; r < 11; r++) {
#pragma unroll
        for (int j = 0; j < 6; j++) {
          if (j == 5 && r == 10) break;
          if (j == 3 && r == 5) mbar_wait(B(B_DEP + 5), 0);
          mbar_wait_c(B(B_EMPTY3 + j), ~r & 1);
          load3(r * 6 + j - 1, j);
          if (j == 5 && r == 9 && elect_one()) l2_prefetch(xr, XR_CAND * 16);
        }
      }
      if (ffn) {
#pragma unroll
        for (int j = 1; j >= 0; j--) {
          mbar_wait(B(B_EMPTY3 + 5 * j), j);
          if (elect_one()) {
            mbar_expect(B(B_FULL3 + 5 * j), SLOT);
            tma_ld3(sb + OFF_R3 + 5 * j * SLOT, &p.wd, B(B_FULL3 + 5 * j), 0, fid * 32, 8 * j);
          }
        }
      }
    } else {
      if (warp >= 2) {
#pragma unroll 1
        for (int i = tid - 64; i < XR_CAND; i += 64) xr[i] = make_uint4(~0u, ~0u, ~0u, ~0u);
        if (warp == 2) { __syncwarp(); if (lane == 0) mbar_arrive(B(B_WR)); }
      }
      if (warp == 3) {
        float ws = 0.f;
#pragma unroll
        for (int j = 0; j < 4; j++) {
          const uint4 q = __ldg(reinterpret_cast<const uint4*>(w_r) + j * 32 + lane);
          ws += bf_lo(q.x) + bf_hi(q.x) + bf_lo(q.y) + bf_hi(q.y) + bf_lo(q.z) + bf_hi(q.z) + bf_lo(q.w) + bf_hi(q.w);
        }
#pragma unroll
        for (int o = 16; o; o >>= 1) ws += __shfl_xor_sync(~0u, ws, o);
        uint2* tab = reinterpret_cast<uint2*>(sp + OFF_MISC + 512);
        tab[lane] = make_uint2(0x3F803F80u, 0x3F803F80u);
        tab[32 + lane] = __ldg(reinterpret_cast<const uint2*>(w_r + gq * 128) + lane);
        if (lane == 0) *reinterpret_cast<float*>(sp + OFF_MISC + 1024) = ws;
        __syncwarp();
        if (lane == 0) mbar_arrive(B(B_WR));
      }
      if (tid == 32) TS(0);
      mbar_wait(B(B_LN), 0);
#pragma unroll 1
      for (int r = warp - 1; r < 16; r += 3) {
        uint4 v[4];
        float a0 = 0.f, a1 = 0.f, b0 = 0.f, b1 = 0.f;
#pragma unroll
        for (int j = 0; j < 4; j++) {
          v[j] = lds128(sb + OFF_LN + r * 2048 + lane * 16 + j * 512);
          const uint32_t u[4] = {v[j].x, v[j].y, v[j].z, v[j].w};
#pragma unroll
          for (int i = 0; i < 4; i++) { const float a = bf_lo(u[i]), b = bf_hi(u[i]); a0 += a; a1 += b; b0 = fmaf(a, a, b0); b1 = fmaf(b, b, b1); }
        }
        a0 += a1; b0 += b1;
#pragma unroll
        for (int o = 16; o; o >>= 1) { a0 += __shfl_xor_sync(~0u, a0, o); b0 += __shfl_xor_sync(~0u, b0, o); }
        const float mean = a0 * (1.f / DM);
        float mb, inv;
        ln_round(mean, fmaxf(fmaf(b0, 1.f / DM, -mean * mean), 0.f), mb, inv);
        inv *= AT_C;
        const uint32_t nm2 = pack_bf16(-mb, -mb);
        uint4* dst = reinterpret_cast<uint4*>(g_xn + (size_t)(cta * 16 + r) * DM) + lane;
#pragma unroll
        for (int j = 0; j < 4; j++)
          dst[j * 32] = make_uint4(ln_apply(v[j].x, nm2, inv), ln_apply(v[j].y, nm2, inv), ln_apply(v[j].z, nm2, inv), ln_apply(v[j].w, nm2, inv));
      }
      __syncwarp();
      if (lane == 0) {
        mbar_arrive(B(B_LND));
        fence_gpu();
        red_add(&g_cnt[C_LN + (cta >> 3)], 1);
      }
      TL(3, warp, lane == 0);
      __syncwarp();
      if (warp == 3) {
        if (lane == 0) {
#pragma unroll 1
          for (int i = 0; i < 6; i++) {
            const int c = i < 2 ? C_LN + (i ? ti : 15 - ti) : (i < 4 ? C_QKV + (i - 2) * 8 + mp : C_CTX + (i - 4) * 16 + mt);
            spin_until_ge<true>(&g_cnt[c], i < 2 ? 24 : 16);
            fence_async_all();
            mbar_arrive(B(B_DEP + i));
            TL(3, 4 + i, true);
          }
        }
      } else if (warp == 1 && elect_one()) {
        mbar_wait(B(B_WR), 0);
#pragma unroll 1
        for (int i = 0; i < 6; i++) {
          const int c = i < 2 ? C_QKV + gq + i * 8 : C_CTX + (i >> 2) * 16 + ((i == 3 || i == 4) ? ti : 15 - ti);
          mbar_wait(B(B_PUB + i), 0);
          if (i >= 2 && i < 5) {
            asm volatile("fence.proxy.async.shared::cta;" ::: "memory");
#pragma unroll 1
            for (int n = 0; n < 8 / ST_G; n++) {
              const int h = n / (4 / ST_G), a = n % (4 / ST_G) * ST_G;
              asm volatile("cp.async.bulk.tensor.3d.global.shared::cta.bulk_group [%0, {%2,%3,%4}], [%1];" ::"l"(&p.ctx_st),
                           "r"(sb + (i == 4 ? 6 * SLOT + h * 16384 : (3 + 2 * h) * SLOT + (i - 2) * 16384) + a * 4096),
                           "r"(0), "r"((i == 2 ? 15 - ti : ti) * 128 + h * 64), "r"((hh + (i >> 2) * 16) * 4 + a) : "memory");
              asm volatile("cp.async.bulk.commit_group;\ncp.async.bulk.wait_group.read 0;" ::: "memory");
              if (ST_NS) __nanosleep(ST_NS);
            }
            mbar_arrive(B(B_QP + i - 2));
            asm volatile("cp.async.bulk.wait_group 0;" ::: "memory");
          }
          fence_gpu();
          red_add(&g_cnt[c], 1);
          TS(1 + i);
        }
      }
      if (warp == 2) {
#pragma unroll 1
        for (int n = 0; n < 8; n++) {
          if (!(n & 3)) mbar_wait(B(B_XE), n >> 2);
          if ((n < 4 || ffn) && elect_one()) {
            const uint32_t fb = B(n < 4 ? B_XF : B_WF2), d = sb + 6 * SLOT + (n & 3) * 8192;
            if (!(n & 3)) mbar_expect(fb, 32768);
            if (n < 4) tma_ld3(d, &p.x, fb, 0, mt * 128 + (n >> 1) * 64, gq * 2 + (n & 1));
            else tma_ld2(d, (n & 1) ? &p.wg : &p.wu, fb, fid * 32, (4 + (n >> 1)) * 128);
          }
          __nanosleep(SL_NS);
        }
#pragma unroll 1
        for (int i = XR_CAND + lane; i < XR_SIZE; i += 32) { xr[i] = make_uint4(~0u, ~0u, ~0u, ~0u); if (SET_NS) __nanosleep(SET_NS); }
        __syncwarp();
        if (lane == 0) { fence_gpu(); mbar_arrive(B(B_SET2)); }
        TL(2, 26, lane == 0);
        __syncwarp();
      }
      __syncwarp();
      if (warp == 3) {
        mbar_wait(B(B_OUT), 0);
        uint4 kv[2];
        poll_chunks(kv, g_xr + ((lane >> 1) * 8 + gq) * XR_SIZE + XR_KEY + (lane & 1) * 2, 1);
        const uint32_t a1 = max(kv[0].x, kv[0].z), a2 = max(min(kv[0].x, kv[0].z), max(kv[0].y, kv[0].w));
        const uint32_t b1 = max(kv[1].x, kv[1].z), b2 = max(min(kv[1].x, kv[1].z), max(kv[1].y, kv[1].w));
        const uint32_t k1 = max(a1, b1), k2 = max(min(a1, b1), max(a2, b2));
        const uint32_t m1 = __reduce_max_sync(~0u, k1);
        const uint32_t m2 = __reduce_max_sync(~0u, k1 == m1 ? k2 : k1);
        if (lane == 0) {
          *reinterpret_cast<uint2*>(sp + OFF_MISC) = make_uint2(m1, m2);
          mbar_arrive(B(B_OUT2));
        }
        const uint32_t key = (lane & 4) ? m2 : m1;
        const int tk = 0x7FFF - (key & 0x7FFF);
        const uint4* src = g_xr + ((tk >> 7) * 8 + (rid >> 4)) * XR_SIZE;
        poll_chunks(kv, src + XR_CAND + ((tk >> 4) & 7) * 64 + (((lane & 4) && !((m1 ^ m2) & 0x7FF0)) ? 16 : 0) + (rid & 12) + (lane & 3), 32);
        uint32_t u = key >> 16;
        u = (u & 0x8000u) ? (u & 0x7FFFu) : (~u & 0xFFFFu);
        const float rs = bf_round(__fdividef(1.f, 1.f + __expf(-__uint_as_float(u << 16))));
        if (lane < 8)
          *reinterpret_cast<uint4*>(sp + OFF_MISC + 128 + lane * 16) = make_uint4((rid & 2) ? ((rid & 1) ? kv[0].w : kv[0].z) : ((rid & 1) ? kv[0].y : kv[0].x),
              (rid & 2) ? ((rid & 1) ? kv[1].w : kv[1].z) : ((rid & 1) ? kv[1].y : kv[1].x), __float_as_uint(rs), 0);
#pragma unroll 1
        for (int n = 0; n < 0x400000; n++) {
          uint32_t v;
          asm volatile("ld.acquire.gpu.global.u32 %0, [%1];" : "=r"(v) : "l"(src + XR_FLAG) : "memory");
          if (__all_sync(~0u, v == 0)) break;
        }
        if (lane == 0) mbar_arrive(B(B_FIN));
      }
      if (warp == 1 && elect_one()) {
        mbar_wait(B(B_OUT3), 0);
        auto owner = [&]() {
          uint2 top;
          asm volatile("ld.shared.v2.u32 {%0,%1}, [%2];" : "=r"(top.x), "=r"(top.y) : "r"(sb + OFF_MISC) : "memory");
          return (0x7FFF - (top.x & 0x7FFF)) >> 7 == mt || (0x7FFF - (top.y & 0x7FFF)) >> 7 == mt;
        };
#pragma unroll 1
        for (int n = 0; n < 256 / OUT_R; n++) {
          if (n && !(mbar_test(B(B_OUT2), 0) && owner())) idle(OUT_CLK);
          asm volatile("cp.async.bulk.tensor.2d.global.shared::cta.bulk_group [%0, {%2,%3}], [%1];" ::"l"(&p.out), "r"(sb + OFF_STG + n * OUT_R * 128),
                       "r"(gq * 128 + (n * OUT_R & 64)), "r"(mt * 128 + (n * OUT_R >> 7) * 64 + (n * OUT_R & 63)) : "memory");
        }
        asm volatile("cp.async.bulk.commit_group;" ::: "memory");
        mbar_wait(B(B_OUT2), 0);
        if (owner()) {
          asm volatile("cp.async.bulk.wait_group 0;" ::: "memory");
          asm volatile("st.release.gpu.global.u32 [%0], 0;" ::"l"(xr + XR_FLAG) : "memory");
        } else {
          asm volatile("cp.async.bulk.wait_group.read 0;" ::: "memory");
        }
        TL(2, 25, true);
      }
    }
    __syncwarp();
    cluster_arrive();
    cluster_wait();
    TL_DUMP();
    if (tid == 32) TS(8);
  } else {
    reg_alloc<232>();
    cluster_wait();
    const int w = wg - 1, cw = warp - 4;
    int lane = lane_id();
    const uint32_t stg = sb + OFF_STG + w * 16384 + (cw & 3) * 2048;
    auto publish = [&](int i) { __syncwarp(); if (lane == 0) mbar_arrive(B(B_PUB + i)); };
    uint32_t rbar;
    asm("mapa.shared::cluster.u32 %0, %1, %2;" : "=r"(rbar) : "r"(bar), "r"(lane & 1));
    auto release2 = [&](int i) { if (lane < 2) asm volatile("mbarrier.arrive.shared::cluster.b64 _, [%0];" ::"r"(rbar + 8 * i) : "memory"); };
    float R[128];
    float O[64], acc[64];
    uint32_t pk[64];
    uint32_t* const Q = pk;
    uint32_t P[32];
    auto packed = [&](int i) {
      const float* v = R + 16 * (i >> 1) + 2 * (i & 1);
      return make_uint4(pack_bf16(v[0], v[1]), pack_bf16(v[4], v[5]), pack_bf16(v[8], v[9]), pack_bf16(v[12], v[13]));
    };
    const uint32_t q_st = sb + (cw & 3) * 1024 + (lane >> 2) * 64 + (((lane & 3) ^ (lane >> 3)) << 4);
    const uint32_t q_ld = sb + (cw & 3) * 1024 + (lane & 15) * 64 + (((lane >> 4) ^ ((lane >> 1) & 3)) << 4);
    auto park = [&](uint32_t off, int i, uint4 v) {
      asm volatile("st.shared.v4.u32 [%0], {%1,%2,%3,%4};" ::"r"(q_st + off + (i >> 1) * 4096 + (i & 1) * 512), "r"(v.x), "r"(v.y), "r"(v.z), "r"(v.w) : "memory");
    };
    auto load_q = [&](uint32_t off, int k) { ldsm4(Q + 4 * k, ((q_ld + off) ^ ((k & 1) << 5)) + (k >> 1) * 4096); };
    {
      TL(0, 1, tid == 128);
      __nv_bfloat16* pdst = g_qkv;
      auto put2 = [&](int j) {
#pragma unroll
        for (int i = (j >> 1) * 4 + (j & 1); i < (j >> 1) * 4 + 4; i += 2)
          __stcs(reinterpret_cast<uint4*>(pdst + (i & 1) * 8 * NQ + (i >> 1) * 32), make_uint4(pk[4 * i], pk[4 * i + 1], pk[4 * i + 2], pk[4 * i + 3]));
      };
      const uint64_t da0 = mk_desc(sb + w * 8192, 16, 1024, 1);
      const uint64_t db0 = mk_desc(sb + 16384, 8192, 1024, 1);
      int st = 0; uint32_t ph = 0;
      auto issue = [&](int accum, auto between) {
        mbar_wait_c(B(B_FULL1 + st), ph);
        const uint64_t da = desc_add(da0, st * P1_STAGE), db = desc_add(db0, st * P1_STAGE);
        between();
        wg_fence();
#pragma unroll
        for (int k = 0; k < 4; k++) mma_n256_ss<1>(R, desc_add(da, k * 32), desc_add(db, k * 2048), k == 0 ? accum : 1);
        wg_commit();
      };
      issue(0, []() {});
#pragma unroll 1
      for (int t = 0;; t++) {
        const int nk = t >= 4 ? 16 : 8;
        const bool tr = t > 0 && t < 5;
        TL(0, 2 + 2 * t + 16 * w, (tid & 127) == 0);
        int prev = st;
        if (++st == 4) { st = 0; ph ^= 1; }
#pragma unroll 1
        for (int kb = 1; kb < nk; kb++) {
          if (kb == nk - 1 && w == 1) bar_sync(5, 256);
          issue(1, []() {});
          if (kb == nk - 1 && w == 0) bar_arrive(5, 256);
          if (tr) {
#pragma unroll
            for (int i = 1; i < 8; i++) if (kb == i) put2(i);
            if (kb == 7 && !(t & 1)) publish((t >> 1) - 1);
          } else if (t == 5 && kb == 2) {
            mbar_wait_c(B(B_LND), 0);
#pragma unroll
            for (int i = 0; i < 8; i++) park(6 * SLOT + w * 16384, i, make_uint4(pk[4 * i], pk[4 * i + 1], pk[4 * i + 2], pk[4 * i + 3]));
            __syncwarp();
#pragma unroll
            for (int k = 0; k < 8; k++) load_q(6 * SLOT + w * 16384, k);
            __syncwarp();
#pragma unroll
            for (int i = 0; i < 8; i++) park(6 * SLOT + w * 16384, i, make_uint4(pk[32 + 4 * i], pk[33 + 4 * i], pk[34 + 4 * i], pk[35 + 4 * i]));
          }
          wg_wait<1>();
          release2(B_EMPTY1 + prev);
          prev = st;
          if (++st == 4) { st = 0; ph ^= 1; }
        }
        if (t == 5) break;
        issue(0, [&]() {
          sched_fence(q_st);
          wg_wait<0>();
          fence_regs<128>(R);
          TL(0, 3 + 2 * t + 16 * w, (tid & 127) == 0);
#pragma unroll
          for (int i = 0; i < 16; i++) { const uint4 v = packed(i); pk[4 * i] = v.x; pk[4 * i + 1] = v.y; pk[4 * i + 2] = v.z; pk[4 * i + 3] = v.w; }
          release2(B_EMPTY1 + prev);
          fence_regs<128>(R);
        });
        sched_fence(q_st);
        pdst = g_qkv + (size_t)(((t & 1) + 1) * SEQ + mt * 128 + cw * 16 + (lane >> 2)) * NQ + (gq + (t >> 1) * 8) * 256 + (lane & 3) * 8;
        if (t < 4) put2(0);
      }
      if (w == 1) bar_arrive(6, 256);
      mbar_wait_c(B(B_KF), 0);
      sched_fence(q_st);
      wg_wait<0>();
      fence_regs<128>(R);
      release2(B_EMPTY1 + 3);
      TL(0, 13 + 16 * w, (tid & 127) == 0);
    }
    auto issue3 = [&](int st, uint32_t ph, int accum) {
      mbar_wait_c(B(B_FULL3 + st), ph);
      const uint64_t da = mk_desc(sb + OFF_R3 + w * 8192 + st * SLOT, 16, 1024, 1), db = mk_desc(sb + OFF_R3 + 16384 + st * SLOT, 8192, 1024, 1);
      wg_fence();
#pragma unroll
      for (int k = 0; k < 4; k++) mma_n128_ss<1>(acc, desc_add(da, k * 32), desc_add(db, k * 2048), k == 0 ? accum : 1);
      wg_commit();
    };
    uint32_t wf[128];
    auto w_addr = [&](uint32_t off, int m) {
      const uint32_t w_ld = sb + ((lane >> 3) & 1) * 8192 + ((cw >> 1) * 32 + (lane & 7) + (lane >> 4) * 8) * 64 + ((((cw & 1) * 2) ^ ((lane >> 1) & 3)) << 4);
      return ((w_ld + off) ^ ((m & 1) << 4)) + (m >> 2) * 16384 + ((m >> 1) & 1) * 1024;
    };
    auto grab = [&](uint32_t* d, uint32_t off, int m0, int m1) {
#pragma unroll
      for (int m = m0; m < m1; m++)
        asm volatile("ldmatrix.sync.aligned.m8n8.x4.trans.shared.b16 {%0,%1,%2,%3}, [%4];"
                     : "=r"(d[4 * m]), "=r"(d[4 * m + 1]), "=r"(d[4 * m + 2]), "=r"(d[4 * m + 3]) : "r"(w_addr(off, m)) : "memory");
    };
    float inv[2] = {0.f, 0.f};
    auto scaled = [&](int i) {
      const float* o = O + 16 * (i >> 1) + 2 * (i & 1);
      const float c = inv[i & 1];
      return make_uint4(pack_bf16(o[0] * c, o[1] * c), pack_bf16(o[4] * c, o[5] * c), pack_bf16(o[8] * c, o[9] * c), pack_bf16(o[12] * c, o[13] * c));
    };
    {
      const int wrow = cw * 16;
      const uint64_t dk0 = mk_desc(sb, 16, 1024, 1);
      const uint64_t dv0 = mk_desc(sb + 2 * SLOT, 16384, 1024, 1);
      const uint32_t pin = sb + OFF_MISC + 1028;
      float l0 = 0.f, l1 = 0.f;
      int g = 0, t = 0;
      uint32_t fail = 0;
      auto piece = [&](int tt) { return (uint32_t)(tt == 3 ? 6 * SLOT + w * 16384 : (3 + 2 * w) * SLOT + (tt - 1) * 16384); };
      uint32_t par = 0;
      auto issue_s = [&](float* S) {
        const uint64_t dk = desc_add(dk0, par * 16);
        mma_n128_rs0(S, Q, dk);
#pragma unroll
        for (int k = 1; k < 8; k++) mma_n128_rs<0>(S, Q + 4 * k, desc_add(dk, (k >> 2) * 16384 + (k & 3) * 32), 1);
        wg_commit();
      };
      auto issue_pv = [&](bool half, int accum) {
        const uint64_t dv = desc_add(dv0, ((g - 1) & 1) * 2 * SLOT);
        wg_fence();
#pragma unroll
        for (int k = 0; k < 4; k++) mma_n128_rs<1>(O, P + 4 * k, desc_add(dv, k * 2048), k == 0 ? accum : 1);
        wg_commit();
        if (UNLIKELY(half)) {
          wg_fence();
          wg_commit();
        } else {
          wg_fence();
#pragma unroll
          for (int k = 4; k < 8; k++) mma_n128_rs<1>(O, P + 4 * k, desc_add(dv, k * 2048), 1);
          wg_commit();
        }
        bar_arrive(2 - w, 256);
        wg_wait<2>();
        fence_regs<32>(Q);
      };
      auto release_k = [&]() { release2(B_KE); rbar ^= 8; };
      auto pv_done = [&]() {
        TC(g, 3);
        sched_fence(q_st);
        wg_wait<0>();
        fence_regs<64>(O); fence_regs<32>(P);
        TC(g, 4);
        release2(B_VE);
      };
      auto row_inv = [&](bool go) {
        float a = l0 + __shfl_xor_sync(~0u, l0, 1), b = l1 + __shfl_xor_sync(~0u, l1, 1);
        a += __shfl_xor_sync(~0u, a, 2); b += __shfl_xor_sync(~0u, b, 2);
        const bool ok = __all_sync(~0u, a >= AT_LO && a <= AT_HI && b >= AT_LO && b <= AT_HI) != 0;
        asm("rcp.approx.ftz.f32 %0, %1;" : "=f"(inv[0]) : "f"(a));
        asm("rcp.approx.ftz.f32 %0, %1;" : "=f"(inv[1]) : "f"(b));
        fail |= (uint32_t)(go && !ok) << t;
        l0 = go ? 0.f : l0; l1 = go ? 0.f : l1;
        t += go;
      };
      const uint64_t m_first = 1ull | (1ull << (16 - ti)) | (1ull << 17) | (1ull << (18 + ti));
      const uint64_t m_diag = (3ull << (15 - ti)) | (3ull << (17 + ti));
      enum { F_FIRST = 1, F_DIAG = 2, F_LAST = 4, F_PFIRST = 8, F_PHALF = 16, F_STOP = 32 };
      auto kind = [&](int gn) {
        const uint32_t a = (uint32_t)((m_first << 1) >> gn), d = (uint32_t)((m_diag << 1) >> gn);
        return ((a >> 1) & 1) * F_FIRST | ((d >> 1) & 1) * F_DIAG | ((a >> 2) & 1) * F_LAST | (a & 1) * F_PFIRST |
               (w == 0 ? (d & 1) * F_PHALF | ((d >> 1) & 1) * F_STOP : 0) | (gn == 34 ? F_STOP : 0);
      };
      uint32_t kinds;
      {
        uint32_t qt[64];
#pragma unroll
        for (int i = 0; i < 16; i++) { const uint4 v = packed(i); qt[4 * i] = v.x; qt[4 * i + 1] = v.y; qt[4 * i + 2] = v.z; qt[4 * i + 3] = v.w; }
        fence_regs<64>(qt);
        sched_fence(q_st);
        float S[64];
        wg_fence();
        issue_s(S);
        bar_arrive(w ? 1 : 7, 256);
        bar_sync(6 + w, 256);
        sched_fence(q_st);
        TL(1, 0, tid == 128);
#pragma unroll
        for (int i = 0; i < 16; i++) park(piece(1), i, make_uint4(qt[4 * i], qt[4 * i + 1], qt[4 * i + 2], qt[4 * i + 3]));
        kinds = pinned(kind(lane + 3));
        sched_fence(q_st);
        wg_wait<0>();
        fence_regs<64>(S);
        release_k();
        TL(1, 1, tid == 128);
        const bool kok = mbar_try(B(B_KF + 1), 0);
        at_exp<0, 32>(S);
        sched_fence(q_st);
        at_exp<32, 64>(S); at_fin<0, 64>(S, P);
        if (UNLIKELY(!kok)) mbar_wait_c(B(B_KF + 1), 0);
        TL(1, 2, tid == 128);
      }
      uint32_t f = F_PFIRST, fn;
      auto shadow = [&]() {
        const bool vok = mbar_try(B(B_VF + ((g - 1) & 1)), ((g - 1) >> 1) & 1);
        at_sum(P, f & F_PHALF, l0, l1);
        fn = __shfl_sync(~0u, kinds, max(g - 2, 0));
        if (UNLIKELY(!vok)) mbar_wait_c(B(B_VF + ((g - 1) & 1)), ((g - 1) >> 1) & 1);
      };
      auto hand_over = [&]() { __syncwarp(); if (lane == 0 && !((fail >> (t - 1)) & 1)) mbar_arrive(B(B_PUB + 1 + t)); };
      auto exp_q = [&](float* S, auto kc, auto nc) {
        constexpr int k = decltype(kc)::value, n = decltype(nc)::value;
        asm volatile("{\n.reg .pred p;\nsetp.ne.b32 p, %5, 0;\n@p ldmatrix.sync.aligned.m8n8.x4.shared.b16 {%0,%1,%2,%3}, [%4];\n}"
                     : "+r"(Q[4 * k]), "+r"(Q[4 * k + 1]), "+r"(Q[4 * k + 2]), "+r"(Q[4 * k + 3])
                     : "r"(((q_ld + piece(t + 1)) ^ ((k & 1) << 5)) + (k >> 1) * 4096), "r"(f & F_LAST) : "memory");
        at_exp<n * k, n * k + n>(S);
      };
      g = 1; par = SLOT / 16;
#pragma unroll 1
      for (;;) {
        {
          TC(g, 0);
          bar_sync(1 + w, 256);
          fence_regs<32>(Q);
          float S[64];
          wg_fence();
          issue_s(S);
          sched_fence(q_st);
          TC(g, 1);
          shadow();
          fence_regs<64>(O); fence_regs<32>(P);
          issue_pv(f & F_PHALF, ~f & F_PFIRST);
          fence_regs<64>(S);
          TC(g, 2);
          release_k();
          at_exp<0, 8>(S);
          const bool first = f & F_FIRST;
          if (UNLIKELY(f & (F_FIRST | F_LAST))) {
            row_inv(first);
            at_mask(S + 32, (f & F_DIAG) ? wrow - 64 : 64, lane);
            unroll8([&](auto kc) { exp_q(S + 8, kc, std::integral_constant<int, AT_R1 / 8 - 1>{}); });
          } else {
            at_exp<8, AT_R1>(S);
          }
          pv_done();
          g = pinned(g + 1); par = pinned(par ^ (SLOT / 16)); f = fn;
          const bool kok = mbar_try(B(B_KF + (g & 1)), g < 34 ? (g >> 1) & 1 : 0);
          if (UNLIKELY(first)) {
            unroll8([&](auto ic) {
              constexpr int i = decltype(ic)::value, n = (64 - AT_R1) / 8;
              at_exp<AT_R1 + n * i, AT_R1 + n * i + n>(S);
              park(piece(t), i, scaled(i));
            });
            at_fin<0, 64>(S, P);
            hand_over();
          } else {
            at_exp<AT_R1, 64>(S); at_fin<0, 64>(S, P);
          }
          TC(g - 1, 5);
          if (!TCLK) TL(1, 1 + g, tid == 128);
          if (kok && !(f & F_STOP)) continue;
          if (UNLIKELY(!kok)) mbar_wait_c(B(B_KF + (g & 1)), (g >> 1) & 1);
          if (g == 34) break;
        }
#pragma unroll 1
        while (f & F_STOP) {
          TC(g, 0);
          bar_sync(1, 256);
          fence_regs<64>(O); fence_regs<32>(Q); fence_regs<32>(P);
          float S[32];
          const uint64_t dk = desc_add(dk0, par * 16);
          wg_fence();
          mma_n64_rs0(S, Q, dk);
#pragma unroll
          for (int k = 1; k < 8; k++) mma_n64_rs(S, Q + 4 * k, desc_add(dk, (k >> 2) * 16384 + (k & 3) * 32), 1);
          wg_commit();
          TC(g, 1);
          mbar_wait_c(B(B_VF + ((g - 1) & 1)), ((g - 1) >> 1) & 1);
          issue_pv(f & F_PHALF, ~f & F_PFIRST);
          fence_regs<32>(S);
          TC(g, 2);
          release_k();
          const bool first = f & F_FIRST;
          if (H_LATE == 2) pv_done();
          at_sum(P, f & F_PHALF, l0, l1);
          fn = __shfl_sync(~0u, kinds, g - 2);
          row_inv(first);
          if (H_LATE == 1) pv_done();
          if (H_LATE) sched_fence(q_st);
          at_mask(S, wrow, lane);
          unroll8([&](auto kc) { exp_q(S, kc, std::integral_constant<int, 4>{}); });
          if (!H_LATE) pv_done();
          g++; par ^= SLOT / 16; f = fn;
          at_fin<0, 32>(S, P);
          if (first) {
#pragma unroll
            for (int i = 0; i < 8; i++) park(piece(t), i, scaled(i));
            hand_over();
          }
          TC(g - 1, 5);
          if (!TCLK) TL(1, 1 + g, tid == 128);
          mbar_wait_c(B(B_KF + (g & 1)), (g >> 1) & 1);
        }
      }
      TCF();
      const bool wok = mbar_test(B(ffn ? B_WF : B_QP + 1), 0);
      grab(wf, 3 * SLOT, 0, 8);
      mbar_wait_c(B(B_VF + 1), 0);
      bar_sync(1 + w, 256);
      fence_regs<64>(O); fence_regs<32>(P);
      wg_fence();
#pragma unroll
      for (int k = 0; k < 8; k++) mma_n128_rs<1>(O, P + 4 * k, desc_add(dv0, 2 * SLOT + k * 2048), 1);
      wg_commit();
      if (w == 0) bar_arrive(2, 256);
      pin_order(__uint_as_float(wf[28] & wf[24]), pin);
      __syncwarp();
      if (wok) release2(B_WE);
      TL(3, 12 + 16 * w, (tid & 127) == 0);
      sched_fence(q_st);
      at_sum(P, false, l0, l1);
      row_inv(true);
      sched_fence(q_st);
      wg_wait<0>();
      fence_regs<64>(O); fence_regs<32>(P);
      release2(B_VE + 1);
      if (UNLIKELY(!wok || fail != 0)) {
#pragma unroll 1
        for (int tt = 0; tt < 4; tt++) {
          if (!((tt < 3 ? fail >> tt : fail != 0) & 1)) continue;
          slow_tile(O, P, l0, l1, wq, (((tt + 1) & 2) ? ti : 15 - ti) * 128 + wrow, hh + (tt & 2) * 8, lane, q_st);
          row_inv(false);
          if (tt < 3) {
#pragma unroll
            for (int i = 0; i < 8; i++) park(piece(tt + 1), i, scaled(i));
            publish(2 + tt);
          }
        }
        if (!wok) {
          mbar_wait_c(B(ffn ? B_WF : B_QP + 1), 0);
          grab(wf, 3 * SLOT, 0, 8);
          pin_order(__uint_as_float(wf[28] & wf[24]), pin);
          __syncwarp();
          release2(B_WE);
        }
      }
      TL(3, 13 + 16 * w, (tid & 127) == 0);
      issue3(0, 0, 0);
      TL(3, 14 + 16 * w, (tid & 127) == 0);
      TL(1, 36, tid == 128);
    }
    uint32_t hp[32];
    lane = lane_id();
    {
      int st = 1, prev = 0; uint32_t ph = 0;
      __nv_bfloat16* dst = g_qkv + (size_t)((15 - ti) * 128 + cw * 16 + (lane >> 2)) * NQ + (hh + 16) * 128 + (lane & 3) * 8;
      auto kblock = [&](auto between, int lim = 6) {
        issue3(st, ph, 1);
        between();
        wg_wait<1>();
        release2(B_EMPTY3 + prev);
        prev = st;
        if (++st == lim) { st = 0; ph ^= 1; }
      };
      kblock([&]() { TL(3, 15 + 16 * w, (tid & 127) == 0); });
      kblock([&]() { grab(wf + 32, 5 * SLOT, 0, 8); TL(3, 16 + 16 * w, (tid & 127) == 0); });
#pragma unroll 1
      for (int kb = 3; kb < 11; kb++) {
        kblock([&]() {
#pragma unroll
          for (int i = 0; i < 8; i++)
            if (kb == 3 + (i & 4) + (i & 1) * 2 + ((i >> 1) & 1)) *reinterpret_cast<uint4*>(dst + (i & 1) * 8 * NQ + (i >> 1) * 32) = scaled(i);
          TL(3, 14 + kb + 16 * w, (tid & 127) == 0);
          if (kb == 8) TL(2, 2, tid == 128);
        }, kb == 4 ? 5 : 6);
        if (kb == 4) release2(B_EMPTY3 + 5);
      }
      publish(5);
      kblock([&]() { mbar_wait_c(B(ffn ? B_WF2 : B_QP + 2), 0); grab(wf + 32, 5 * SLOT, 8, 16); });
#pragma unroll 1
      for (int kb = 12; kb < G_KB; kb++) {
        kblock([&]() { if ((kb & 7) == 0) TL(2, 1 + (kb >> 3), tid == 128); });
        if (kb == X_KB && lane == 0) mbar_arrive(B(B_XE));
      }
      kblock([&]() {
        mbar_wait_c(B(B_XF), 0);
#pragma unroll
        for (int i = 0; i < 8; i++)
          ldsm4(hp + 4 * i, sb + 6 * SLOT + w * 16384 + ((cw & 3) * 16 + (lane & 15)) * 128 + (i >> 2) * 8192 + ((((i & 3) * 2 + (lane >> 4)) ^ (lane & 7)) << 4));
      });
#pragma unroll 1
      for (int kb = G_KB + 1; kb < 64; kb++) {
        kblock([&]() { if ((kb & 7) == 0) TL(2, 1 + (kb >> 3), tid == 128); });
        if (kb == G_KB + 2 && lane == 0) mbar_arrive(B(B_XE));
      }
    }
    lane = lane_id();
    const int r0 = lane >> 2, q4 = lane & 3, ct = cw * 32 + lane;
    uint32_t tb[16];
    mbar_wait_c(B(B_WR), 0);
#pragma unroll
    for (int i = 0; i < 4; i++) ldsm4(tb + 4 * i, sb + OFF_MISC + 512 + (lane & 1) * 256 + (lane >> 3) * 16 + i * 64);
    mbar_wait_c(B(B_SET2), 0);
    float4* const psd = reinterpret_cast<float4*>(xr + XR_PS + cw * 16 + r0);
    const uint4* const pss = g_xr + (mt * 8 + (ct & 1) * 4) * XR_SIZE + XR_PS + (ct >> 1);
    sched_fence(stg);
    wg_wait<0>();
    fence_regs<64>(acc);
    TL(2, 10, tid == 128);
    {
      float d[2][4] = {}, qa[2][4] = {}, qb[2][4] = {};
#pragma unroll
      for (int j = 0; j < 16; j++) {
        hp[2 * j] = hadd2_bf(hp[2 * j], pack_bf16(acc[4 * j], acc[4 * j + 1]));
        hp[2 * j + 1] = hadd2_bf(hp[2 * j + 1], pack_bf16(acc[4 * j + 2], acc[4 * j + 3]));
        if (j & 1) {
          mma16816(d[(j >> 1) & 1], hp[2 * j - 2], hp[2 * j - 1], hp[2 * j], hp[2 * j + 1], tb[j - 1], tb[j]);
          mma16816(qa[(j >> 1) & 1], hp[2 * j - 2], hp[2 * j - 1], hp[2 * j], hp[2 * j + 1], hp[2 * j - 2], hp[2 * j]);
          mma16816(qb[(j >> 1) & 1], hp[2 * j - 2], hp[2 * j - 1], hp[2 * j], hp[2 * j + 1], hp[2 * j - 1], hp[2 * j + 1]);
        }
      }
      if (q4 == (r0 >> 1)) {
        __stcg(psd, make_float4(d[0][0] + d[1][0], (r0 & 1) ? qa[0][1] + qa[1][1] : qa[0][0] + qa[1][0], d[0][1] + d[1][1], 0.f));
        __stcg(psd + 8, make_float4(d[0][2] + d[1][2], (r0 & 1) ? qb[0][3] + qb[1][3] : qb[0][2] + qb[1][2], d[0][3] + d[1][3], 0.f));
      }
    }
    TL(2, 11, tid == 128);
    mbar_wait_c(B(B_EMPTY3 + 1), 0);
    stage_store_128(stg, lane, hp);
    if (ffn) mbar_wait_c(B(B_WF2), 1);
    grab(wf + 96, 6 * SLOT, 0, 8);
    const float wsum = *reinterpret_cast<const float*>(sp + OFF_MISC + 1024);
    __syncwarp();
    {
      uint4 ps[4];
      poll_chunks(ps, pss, XR_SIZE);
      TL(2, 12, tid == 128);
      auto F = [](uint32_t u) { return __uint_as_float(u); };
      float s1 = (F(ps[0].x) + F(ps[1].x)) + (F(ps[2].x) + F(ps[3].x)), s2 = (F(ps[0].y) + F(ps[1].y)) + (F(ps[2].y) + F(ps[3].y));
      float s3 = (F(ps[0].z) + F(ps[1].z)) + (F(ps[2].z) + F(ps[3].z));
      __syncwarp();
      s1 += __shfl_xor_sync(~0u, s1, 1); s2 += __shfl_xor_sync(~0u, s2, 1); s3 += __shfl_xor_sync(~0u, s3, 1);
      const float mean = s1 * (1.f / DM);
      float mb, inv;
      ln_round(mean, fmaxf(fmaf(s2, 1.f / DM, -mean * mean), 0.f), mb, inv);
      uint32_t u = pack_bf16((s3 - mb * wsum) * inv, 0.f);
      if (u == 0x8000u) u = 0;
      u = (u & 0x8000u) ? (~u & 0xFFFFu) : (u | 0x8000u);
      const uint32_t key = (u << 16) | (0x7FFFu - (mt * 128 + (ct >> 1)));
      const uint32_t nm2 = pack_bf16(-mb, -mb);
      const uint32_t c1 = __reduce_max_sync(~0u, key);
      const uint32_t c2 = __reduce_max_sync(~0u, key == c1 ? 0u : key);
      if (lane == 0) {
        __stcg(reinterpret_cast<uint2*>(xr + XR_KEY) + cw, make_uint2(c1, c2));
        mbar_arrive(B(B_OUT));
      }
      TL(2, 13, tid == 128);
      const int row = (0x7FFF - (((lane >> 4) ? c2 : c1) & 0x7FFF)) & 15;
      const uint32_t rn = __shfl_sync(~0u, nm2, row * 2);
      const float ri = __shfl_sync(~0u, inv, row * 2);
      uint32_t v[4];
#pragma unroll
      for (int i = 0; i < 4; i++)
        asm volatile("ld.shared.u32 %0, [%1];" : "=r"(v[i]) : "r"(stg + ((lane >> 3) & 1) * 8192 + row * 128 + ((((lane & 4) + i) ^ (row & 7)) << 4) + q4 * 4) : "memory");
      __stcg(xr + XR_CAND + cw * 64 + 32 + lane, make_uint4(ln_apply(v[0], rn, ri), ln_apply(v[1], rn, ri), ln_apply(v[2], rn, ri), ln_apply(v[3], rn, ri)));
      __stcg(xr + XR_CAND + cw * 64 + lane, make_uint4(v[0], v[1], v[2], v[3]));
      sched_fence(stg);
      const uint32_t na = __shfl_sync(~0u, nm2, r0 * 2), nb = __shfl_sync(~0u, nm2, r0 * 2 + 16);
      const float ia = __shfl_sync(~0u, inv, r0 * 2), ib = __shfl_sync(~0u, inv, r0 * 2 + 16);
#pragma unroll
      for (int i = 0; i < 32; i++) hp[i] = hadd2_bf(hp[i], ln_apply(hp[i], (i & 1) ? nb : na, (i & 1) ? ib : ia));
      __syncwarp();
      stage_store_128(stg, lane, hp);
      asm volatile("fence.proxy.async.shared::cta;" ::: "memory");
      publish(B_OUT3 - B_PUB);
    }
    uint32_t wd[16][4];
    sched_fence(stg);
    if (ffn) mbar_wait_c(B(B_FULL3 + 5 * w), 1 - w);
    auto load_wd = [&](int h) {
#pragma unroll
      for (int i = h; i < 16; i += 2)
        asm volatile("ldmatrix.sync.aligned.m8n8.x4.trans.shared.b16 {%0,%1,%2,%3}, [%4];"
                     : "=r"(wd[i][0]), "=r"(wd[i][1]), "=r"(wd[i][2]), "=r"(wd[i][3])
                     : "r"(sb + OFF_R3 + 5 * w * SLOT + (2 * (cw & 3) + (i >> 3)) * 4096 + (h * 16 + (lane & 7) + (lane >> 4) * 8) * 128 +
                           (((2 * ((i >> 1) & 3) + ((lane >> 3) & 1)) ^ (lane & 7)) << 4)) : "memory");
    };
    load_wd(0);
    __syncwarp();
    cluster_arrive();
    TL(2, 22, tid == 128);
    mbar_wait_c(B(B_OUT2), 0);
    const uint2 top = *reinterpret_cast<const uint2*>(sp + OFF_MISC);
    TL(2, 14, tid == 128);
    const int t0 = 0x7FFF - (top.x & 0x7FFF), t1 = 0x7FFF - (top.y & 0x7FFF);
    auto cand = [&](int second) {
      const int tk = second ? t1 : t0;
      return g_xr + (tk >> 7) * 8 * XR_SIZE + XR_CAND + ((tk >> 4) & 7) * 64 + ((second && (t0 >> 4) == (t1 >> 4)) ? 16 : 0);
    };
    if (ffn) {
      uint4 xb[2];
      poll_chunks(xb, cand(r0 & 1) + (r0 >> 1) * XR_SIZE + 32 + (cw >> 1) * 4 + q4, 4 * XR_SIZE);
      __syncwarp();
      TL(2, 15, tid == 128);
      float d[8][4] = {};
#pragma unroll
      for (int n = 0; n < 32; n++) {
        if (n == WD_AT) { sched_fence(stg); load_wd(1); }
        const int s = (n >> 4) * 4 + ((n >> 1) & 3), m = ((n >> 3) & 1) * 2 + (n & 1);
        const uint32_t* a = wf + 16 * s + 4 * m;
        mma16816(d[n & 7], a[0], a[1], a[2], a[3], (m & 2) ? xb[s >> 2].z : xb[s >> 2].x, (m & 2) ? xb[s >> 2].w : xb[s >> 2].y);
      }
      float v[8];
#pragma unroll
      for (int i = 0; i < 8; i++) {
        const float lo = (q4 & 1) ? d[2 + (i >> 2)][i & 3] : d[i >> 2][i & 3], hi = (q4 & 1) ? d[6 + (i >> 2)][i & 3] : d[4 + (i >> 2)][i & 3];
        v[i] = (q4 & 2) ? hi : lo;
      }
#pragma unroll
      for (int i = 0; i < 4; i++) v[i] = ((q4 & 2) ? v[i + 4] : v[i]) + __shfl_xor_sync(~0u, (q4 & 2) ? v[i] : v[i + 4], 2);
#pragma unroll
      for (int i = 0; i < 2; i++) v[i] = ((q4 & 1) ? v[i + 2] : v[i]) + __shfl_xor_sync(~0u, (q4 & 1) ? v[i] : v[i + 2], 1);
      float4* red = reinterpret_cast<float4*>(sp + SL_SCR * SLOT);
      reinterpret_cast<float2*>(red + cw * 16 + (q4 >> 1) * 8 + r0)[q4 & 1] = make_float2(v[0], v[1]);
      bar_sync(3, 256);
      TL(2, 16, tid == 128);
      const float4 z0 = red[lane], z1 = red[32 + lane], z2 = red[64 + lane], z3 = red[96 + lane];
      const uint32_t ub = pack_bf16((z0.x + z1.x) + (z2.x + z3.x), (z0.y + z1.y) + (z2.y + z3.y));
      const uint32_t gb = pack_bf16((z0.z + z1.z) + (z2.z + z3.z), (z0.w + z1.w) + (z2.w + z3.w));
      const float g0 = bf_lo(gb), g1 = bf_hi(gb);
      const uint32_t sg = pack_bf16(__fdividef(g0, 1.f + __expf(-g0)), __fdividef(g1, 1.f + __expf(-g1)));
      const uint32_t act = pack_bf16(bf_lo(sg) * bf_lo(ub), bf_hi(sg) * bf_hi(ub));
      const uint32_t pr = __byte_perm(act, __shfl_xor_sync(~0u, act, 1), (lane & 1) ? 0x3276 : 0x5410);
      const int src = q4 * 2 + (r0 & 1);
      const uint32_t a0 = __shfl_sync(~0u, pr, src), a1 = __shfl_sync(~0u, pr, src + 8), a2 = __shfl_sync(~0u, pr, src + 16), a3 = __shfl_sync(~0u, pr, src + 24);
      TL(2, 17, tid == 128);
      float y[8][4] = {};
#pragma unroll
      for (int i = 0; i < 8; i++) mma16816(y[i], wd[2 * i][0], wd[2 * i][1], wd[2 * i][2], wd[2 * i][3], a0, a1);
#pragma unroll
      for (int i = 0; i < 8; i++) mma16816(y[i], wd[2 * i + 1][0], wd[2 * i + 1][1], wd[2 * i + 1][2], wd[2 * i + 1][3], a2, a3);
      float2* yd = reinterpret_cast<float2*>(g_xr + (cw * 16 + 2 * q4) * XR_SIZE + XR_Y + fid * 4) + r0;
#pragma unroll
      for (int j = 0; j < 2; j++) {
        float v[4];
#pragma unroll
        for (int e = 0; e < 4; e++) {
          const float lo = (q4 & 1) ? y[4 * j + 1][e] : y[4 * j][e], hi = (q4 & 1) ? y[4 * j + 3][e] : y[4 * j + 2][e];
          v[e] = (q4 & 2) ? hi : lo;
        }
        __stcg(yd + j * 16 * XR_SIZE, make_float2(v[0], v[1]));
        __stcg(yd + j * 16 * XR_SIZE + 2 * XR_SIZE, make_float2(v[2], v[3]));
      }
    }
    TL(2, 18, tid == 128);
    if (rid == 127 && ct < C_NUM) g_cnt[ct] = 0;
    if (cw < 2) {
      const int tok = (lane >> 1) & 1, pair = cw * 2 + (lane & 1);
      idle(ffn ? YD : YD + 2000);
      uint4 z[7];
      poll_chunks(z, xr + XR_Y + (lane >> 1) * 4 + pair, 64);
      __syncwarp();
      TL(2, 19, tid == 128);
      mbar_wait_c(B(B_FIN), 0);
      const uint4 op = lds128(sb + OFF_MISC + 128 + (tok * 4 + pair) * 16);
      auto F = [](uint32_t u) { return __uint_as_float(u); };
      const float v0 = ((F(z[0].x) + F(z[1].x)) + (F(z[2].x) + F(z[3].x))) + ((F(z[4].x) + F(z[5].x)) + F(z[6].x));
      const float v1 = ((F(z[0].y) + F(z[1].y)) + (F(z[2].y) + F(z[3].y))) + ((F(z[4].y) + F(z[5].y)) + F(z[6].y));
      const float v2 = ((F(z[0].z) + F(z[1].z)) + (F(z[2].z) + F(z[3].z))) + ((F(z[4].z) + F(z[5].z)) + F(z[6].z));
      const float v3 = ((F(z[0].w) + F(z[1].w)) + (F(z[2].w) + F(z[3].w))) + ((F(z[4].w) + F(z[5].w)) + F(z[6].w));
      float ya = (tok ? v1 : v0) + __shfl_xor_sync(~0u, tok ? v0 : v1, 2), yb = (tok ? v3 : v2) + __shfl_xor_sync(~0u, tok ? v2 : v3, 2);
#pragma unroll
      for (int o = 4; o < 32; o <<= 1) { ya += __shfl_xor_sync(~0u, ya, o); yb += __shfl_xor_sync(~0u, yb, o); }
      const uint32_t yp = pack_bf16(ya, yb);
      if (lane < 4) reinterpret_cast<uint32_t*>(out + (size_t)(tok ? t1 : t0) * DM)[rid * 4 + pair] = hadd2_bf(op.x, hadd2_bf(op.y, pack_bf16(bf_lo(yp) * F(op.z), bf_hi(yp) * F(op.z))));
      TL(2, 21, tid == 128);
    }
    TL(2, 20, tid == 128);
    __syncwarp();
    cluster_wait();
    TL_DUMP();
  }
}

typedef CUresult (*EncodeFn)(CUtensorMap*, CUtensorMapDataType, cuuint32_t, void*, const cuuint64_t*, const cuuint64_t*, const cuuint32_t*,
                             const cuuint32_t*, CUtensorMapInterleave, CUtensorMapSwizzle, CUtensorMapL2promotion, CUtensorMapFloatOOBfill);
EncodeFn g_enc = nullptr;

void map2(CUtensorMap* m, const void* ptr, uint64_t rows, uint64_t cols, uint32_t bc, uint32_t br) {
  const CUtensorMapSwizzle sw = bc == 64 ? CU_TENSOR_MAP_SWIZZLE_128B : CU_TENSOR_MAP_SWIZZLE_64B;
  cuuint64_t gd[2] = {cols, rows}, gs[1] = {cols * 2};
  cuuint32_t bd[2] = {bc, br}, es[2] = {1, 1};
  g_enc(m, CU_TENSOR_MAP_DATA_TYPE_BFLOAT16, 2, (void*)ptr, gd, gs, bd, es, CU_TENSOR_MAP_INTERLEAVE_NONE, sw,
        CU_TENSOR_MAP_L2_PROMOTION_L2_128B, CU_TENSOR_MAP_FLOAT_OOB_FILL_NONE);
}
void map3(CUtensorMap* m, const void* ptr, uint64_t rows, uint64_t cols, uint32_t br, uint32_t bch, uint32_t bc = 64) {
  cuuint64_t gd[3] = {bc, rows, cols / bc}, gs[2] = {cols * 2, bc * 2};
  cuuint32_t bd[3] = {bc, br, bch}, es[3] = {1, 1, 1};
  g_enc(m, CU_TENSOR_MAP_DATA_TYPE_BFLOAT16, 3, (void*)ptr, gd, gs, bd, es, CU_TENSOR_MAP_INTERLEAVE_NONE, bc == 64 ? CU_TENSOR_MAP_SWIZZLE_128B : CU_TENSOR_MAP_SWIZZLE_64B,
        CU_TENSOR_MAP_L2_PROMOTION_L2_128B, CU_TENSOR_MAP_FLOAT_OOB_FILL_NONE);
}

}

extern "C" void kernel_launch(void* const* d_in, const int* in_sizes, int n_in, void* d_out, int out_size) {
  const __nv_bfloat16* x = (const __nv_bfloat16*)d_in[0];
  const __nv_bfloat16* ckv = (const __nv_bfloat16*)d_in[1];
  const __nv_bfloat16* wq = (const __nv_bfloat16*)d_in[2];
  const __nv_bfloat16* wk = (const __nv_bfloat16*)d_in[3];
  const __nv_bfloat16* wv = (const __nv_bfloat16*)d_in[4];
  const __nv_bfloat16* wo = (const __nv_bfloat16*)d_in[5];
  const __nv_bfloat16* w_r = (const __nv_bfloat16*)d_in[7];
  const __nv_bfloat16* wgate = (const __nv_bfloat16*)d_in[8];
  const __nv_bfloat16* wup = (const __nv_bfloat16*)d_in[9];
  const __nv_bfloat16* wdown = (const __nv_bfloat16*)d_in[10];
  __nv_bfloat16* out = (__nv_bfloat16*)d_out;

  if (!g_enc) {
    void* fn = nullptr;
    cudaDriverEntryPointQueryResult qr;
    cudaGetDriverEntryPoint("cuTensorMapEncodeTiled", &fn, cudaEnableDefault, &qr);
    g_enc = (EncodeFn)fn;
    cudaFuncSetAttribute(fused_kernel, cudaFuncAttributeMaxDynamicSharedMemorySize, SMEM_BYTES);
  }
  void *xn, *qkv;
  cudaGetSymbolAddress(&xn, g_xn);
  cudaGetSymbolAddress(&qkv, g_qkv);

  Params p;
  map2(&p.xn, xn, SEQ, DM, 64, 128);
  map2(&p.ckv, ckv, SEQ, DC, 64, 128);
  map3(&p.wq, wq, DM, NQ, 64, 2);
  map3(&p.wk, wk, DC, NQ, 64, 2);
  map3(&p.wv, wv, DC, NQ, 64, 2);
  map3(&p.kv, qkv, 3 * SEQ, NQ, 128, 1);
  map2(&p.ctx_ld, qkv, SEQ, NQ, 64, 128);
  map3(&p.ctx_st, qkv, SEQ, NQ, 64, ST_G, 32);
  map3(&p.wo, wo, NQ, DM, 64, 1);
  map3(&p.x, x, SEQ, DM, 64, 1);
  map3(&p.wd, wdown, FF, DM, 32, 8);
  map2(&p.out, out, SEQ, DM, 64, OUT_R);
  map2(&p.wg, wgate, DM, FF, 32, 128);
  map2(&p.wu, wup, DM, FF, 32, 128);
  fused_kernel<<<128, 384, SMEM_BYTES, cudaStreamPerThread>>>(x, wq, w_r, out, p);
}
```

```cpp
#include <cuda_runtime.h>
#include <cuda_bf16.h>
#include <cuda.h>
#include <stdint.h>
#include <type_traits>

#pragma nv_diag_suppress 549
namespace {

constexpr int SEQ = 2048, DM = 1024, NH = 32, HD = 128, DC = 512, NQ = NH * HD, FF = 3584;

__device__ __align__(1024) __nv_bfloat16 g_xn[SEQ * DM];
__device__ __align__(1024) __nv_bfloat16 g_qkv[3 * SEQ * NQ];
constexpr int XR_PS = 0;
constexpr int XR_KEY = 128;
constexpr int XR_FLAG = 132;
constexpr int XR_CAND = 136;
constexpr int XR_Y = 648;
constexpr int XR_SIZE = 1104;
__device__ __align__(1024) uint4 g_xr[128 * XR_SIZE];
constexpr int C_LN = 0, C_QKV = 16, C_CTX = 32, C_NUM = 64;
__device__ unsigned g_cnt[C_NUM];

#define TL(k, i, cond) do {} while (0)
#define TL_BYTES 0
#define TL_INIT() do {} while (0)
#define TL_DUMP() do {} while (0)
#define TC(g, i) do {} while (0)
#define TCF() do {} while (0)
#define TS(i) do {} while (0)
#undef TCLK
#define TCLK 0

__device__ __forceinline__ uint32_t s2u(const void* p) { return (uint32_t)__cvta_generic_to_shared(p); }
__device__ __forceinline__ void mbar_init(uint32_t b, uint32_t c) { asm volatile("mbarrier.init.shared::cta.b64 [%0], %1;" ::"r"(b), "r"(c) : "memory"); }
__device__ __forceinline__ void mbar_expect(uint32_t b, uint32_t bytes) { asm volatile("mbarrier.arrive.expect_tx.shared::cta.b64 _, [%0], %1;" ::"r"(b), "r"(bytes) : "memory"); }
__device__ __forceinline__ void mbar_arrive(uint32_t b) { asm volatile("mbarrier.arrive.shared::cta.b64 _, [%0];" ::"r"(b) : "memory"); }
__device__ __forceinline__ bool mbar_test(uint32_t b, uint32_t ph) {
  uint32_t ok;
  asm volatile("{\n.reg .pred p;\nmbarrier.test_wait.parity.shared::cta.b64 p, [%1], %2;\nselp.u32 %0, 1, 0, p;\n}" : "=r"(ok) : "r"(b), "r"(ph) : "memory");
  return ok;
}
__device__ __forceinline__ void mbar_wait(uint32_t b, uint32_t ph) {
  asm volatile(
      "{\n.reg .pred p;\n.reg .u32 n;\nmov.u32 n, 0;\n"
      "LW:\nmbarrier.try_wait.parity.shared::cta.b64 p, [%0], %1, 20000;\n@p bra LD;\n"
      "add.u32 n, n, 1;\nsetp.lt.u32 p, n, 0x40000;\n@p bra LW;\ntrap;\nLD:\n}" ::"r"(b), "r"(ph) : "memory");
}
__device__ __forceinline__ void mbar_wait_c(uint32_t b, uint32_t ph) {
  asm volatile(
      "{\n.reg .pred p;\n.reg .u32 n;\nmov.u32 n, 0;\n"
      "LW:\nmbarrier.try_wait.parity.shared::cta.b64 p, [%0], %1;\n@p bra LD;\n"
      "add.u32 n, n, 1;\nsetp.lt.u32 p, n, 0x100000;\n@p bra LW;\ntrap;\nLD:\n}" ::"r"(b), "r"(ph) : "memory");
}
__device__ __forceinline__ bool mbar_try(uint32_t b, uint32_t ph) {
  uint32_t ok;
  asm volatile("{\n.reg .pred p;\nmbarrier.try_wait.parity.shared::cta.b64 p, [%1], %2;\nselp.u32 %0, 1, 0, p;\n}" : "=r"(ok) : "r"(b), "r"(ph) : "memory");
  return ok;
}
#define UNLIKELY(c) __builtin_expect(!!(c), 0)
__device__ __forceinline__ uint32_t pinned(uint32_t v) { uint32_t r; asm volatile("mov.b32 %0, %1;" : "=r"(r) : "r"(v)); return r; }
__device__ __forceinline__ bool elect_one() {
  uint32_t p;
  asm volatile("{\n.reg .pred p;\nelect.sync _|p, 0xFFFFFFFF;\nselp.u32 %0, 1, 0, p;\n}" : "=r"(p));
  return p;
}
__device__ __forceinline__ int lane_id() { int r; asm volatile("mov.u32 %0, %%laneid;" : "=r"(r)); return r; }
template <bool SLEEP = false>
__device__ __forceinline__ void spin_until_ge(const unsigned* p, unsigned target) {
  asm volatile(
      "{\n.reg .pred p, q;\n.reg .u32 n, v;\nmov.u32 n, 0;\nsetp.ne.u32 q, %2, 0;\n"
      "LW:\nld.acquire.gpu.global.u32 v, [%0];\nsetp.ge.u32 p, v, %1;\n@p bra LD;\n@q nanosleep.u32 200;\n"
      "add.u32 n, n, 1;\nsetp.lt.u32 p, n, 0x400000;\n@p bra LW;\ntrap;\nLD:\n}" ::"l"(p), "r"(target), "n"((int)SLEEP) : "memory");
}
#define REPOLL 1
template <int N>
__device__ __forceinline__ void poll_chunks(uint4 (&v)[N], const uint4* p, int stride) {
  uint32_t m[N];
#pragma unroll
  for (int i = 0; i < N; i++) { m[i] = ~0u; v[i] = make_uint4(0, 0, 0, 0); }
#pragma unroll 1
  for (int n = 0; n < 0x400000; n++) {
    uint32_t a = 0;
#pragma unroll
    for (int i = 0; i < N; i++)
      asm volatile("{\n.reg .pred p;\nsetp.eq.u32 p, %5, 0xFFFFFFFF;\n@p ld.relaxed.gpu.global.v4.u32 {%0,%1,%2,%3}, [%4];\n}"
                   : "+r"(v[i].x), "+r"(v[i].y), "+r"(v[i].z), "+r"(v[i].w) : "l"(p + i * stride), "r"(N >= REPOLL ? m[i] : ~0u) : "memory");
#pragma unroll
    for (int i = 0; i < N; i++) { m[i] = max(max(v[i].x, v[i].y), max(v[i].z, v[i].w)); a = max(a, m[i]); }
    if (__all_sync(~0u, a != 0xFFFFFFFFu)) break;
  }
}
__device__ __forceinline__ void fence_async_all() { asm volatile("fence.proxy.async;" ::: "memory"); }
__device__ __forceinline__ void bar_sync(int id, int n) { asm volatile("bar.sync %0, %1;" ::"r"(id), "r"(n) : "memory"); }
__device__ __forceinline__ void bar_arrive(int id, int n) { asm volatile("bar.arrive %0, %1;" ::"r"(id), "r"(n) : "memory"); }
__device__ __forceinline__ void cluster_arrive() { asm volatile("barrier.cluster.arrive.relaxed.aligned;" ::: "memory"); }
__device__ __forceinline__ void cluster_wait() { asm volatile("barrier.cluster.wait.acquire.aligned;" ::: "memory"); }
__device__ __forceinline__ void fence_gpu() { asm volatile("fence.acq_rel.gpu;" ::: "memory"); }
__device__ __forceinline__ void red_add(unsigned* p, unsigned v) { asm volatile("red.relaxed.gpu.global.add.u32 [%0], %1;" ::"l"(p), "r"(v) : "memory"); }
__device__ __forceinline__ void prefetch_tm(const CUtensorMap* m) { asm volatile("prefetch.tensormap [%0];" ::"l"(m) : "memory"); }

constexpr uint64_t EV_N = 0x1000000000000000ull, EV_F = 0x12F0000000000000ull;
__device__ __forceinline__ void tma_ld2(uint32_t dst, const CUtensorMap* m, uint32_t bar, int c0, int c1, bool ef = false) {
  asm volatile("cp.async.bulk.tensor.2d.shared::cta.global.mbarrier::complete_tx::bytes.L2::cache_hint [%0], [%1, {%3,%4}], [%2], %5;" ::"r"(dst), "l"(m), "r"(bar), "r"(c0), "r"(c1), "l"(ef ? EV_F : EV_N) : "memory");
}
__device__ __forceinline__ void tma_ld3(uint32_t dst, const CUtensorMap* m, uint32_t bar, int c0, int c1, int c2, bool ef = false) {
  asm volatile("cp.async.bulk.tensor.3d.shared::cta.global.mbarrier::complete_tx::bytes.L2::cache_hint [%0], [%1, {%3,%4,%5}], [%2], %6;" ::"r"(dst), "l"(m), "r"(bar), "r"(c0), "r"(c1), "r"(c2), "l"(ef ? EV_F : EV_N) : "memory");
}
__device__ __forceinline__ void tma_ld3_mc(uint32_t dst, const CUtensorMap* m, uint32_t bar, int c0, int c1, int c2, uint16_t mask, bool ef = false) {
  asm volatile("cp.async.bulk.tensor.3d.shared::cluster.global.mbarrier::complete_tx::bytes.multicast::cluster.L2::cache_hint [%0], [%1, {%3,%4,%5}], [%2], %6, %7;" ::"r"(dst), "l"(m), "r"(bar), "r"(c0), "r"(c1), "r"(c2), "h"(mask), "l"(ef ? EV_F : EV_N) : "memory");
}
__device__ __forceinline__ void tma_pf3(const CUtensorMap* m, int c0, int c1, int c2) {
  asm volatile("cp.async.bulk.prefetch.tensor.3d.L2.global [%0, {%1,%2,%3}];" ::"l"(m), "r"(c0), "r"(c1), "r"(c2) : "memory");
}
__device__ __forceinline__ void l2_prefetch(const void* p, uint32_t bytes) { asm volatile("cp.async.bulk.prefetch.L2.global [%0], %1;" ::"l"(p), "r"(bytes) : "memory"); }

__device__ __forceinline__ void wg_fence() { asm volatile("wgmma.fence.sync.aligned;" ::: "memory"); }
__device__ __forceinline__ void wg_commit() { asm volatile("wgmma.commit_group.sync.aligned;" ::: "memory"); }
template <int N> __device__ __forceinline__ void wg_wait() { asm volatile("wgmma.wait_group.sync.aligned %0;" ::"n"(N) : "memory"); }
template <int N> __device__ __forceinline__ void reg_alloc() { asm volatile("setmaxnreg.inc.sync.aligned.u32 %0;" ::"n"(N)); }
template <int N> __device__ __forceinline__ void reg_dealloc() { asm volatile("setmaxnreg.dec.sync.aligned.u32 %0;" ::"n"(N)); }
template <int N> __device__ __forceinline__ void fence_regs(float* d) {
#pragma unroll
  for (int i = 0; i < N; i++) asm volatile("" : "+f"(d[i])::"memory");
}
template <int N> __device__ __forceinline__ void fence_regs(uint32_t* d) {
#pragma unroll
  for (int i = 0; i < N; i++) asm volatile("" : "+r"(d[i])::"memory");
}

__device__ __forceinline__ uint64_t mk_desc(uint32_t addr, uint32_t lbo, uint32_t sbo, uint32_t swz) {
  uint32_t lo = ((addr & 0x3FFFF) >> 4) | ((lbo >> 4) << 16);
  uint32_t hi = (sbo >> 4) | (swz << 30);
  return ((uint64_t)hi << 32) | lo;
}
__device__ __forceinline__ uint64_t desc_add(uint64_t d, uint32_t bytes) {
  uint32_t lo = (uint32_t)d + (bytes >> 4);
  return (d & 0xFFFFFFFF00000000ull) | lo;
}

#define R8(b) "+f"(d[b + 0]), "+f"(d[b + 1]), "+f"(d[b + 2]), "+f"(d[b + 3]), "+f"(d[b + 4]), "+f"(d[b + 5]), "+f"(d[b + 6]), "+f"(d[b + 7])
#define REGS32 "%0,%1,%2,%3,%4,%5,%6,%7,%8,%9,%10,%11,%12,%13,%14,%15,%16,%17,%18,%19,%20,%21,%22,%23,%24,%25,%26,%27,%28,%29,%30,%31"
#define REGS64 REGS32 ",%32,%33,%34,%35,%36,%37,%38,%39,%40,%41,%42,%43,%44,%45,%46,%47,%48,%49,%50,%51,%52,%53,%54,%55,%56,%57,%58,%59,%60,%61,%62,%63"
#define REGS128 REGS64 ",%64,%65,%66,%67,%68,%69,%70,%71,%72,%73,%74,%75,%76,%77,%78,%79,%80,%81,%82,%83,%84,%85,%86,%87,%88,%89,%90,%91,%92,%93,%94,%95," \
               "%96,%97,%98,%99,%100,%101,%102,%103,%104,%105,%106,%107,%108,%109,%110,%111,%112,%113,%114,%115,%116,%117,%118,%119,%120,%121,%122,%123,%124,%125,%126,%127"

template <int TB>
__device__ __forceinline__ void mma_n256_ss(float (&d)[128], uint64_t a, uint64_t b, int acc) {
  asm volatile("{\n.reg .pred p;\nsetp.ne.b32 p, %130, 0;\n"
               "wgmma.mma_async.sync.aligned.m64n256k16.f32.bf16.bf16 {" REGS128 "}, %128, %129, p, 1, 1, 0, %131;\n}\n"
               : R8(0), R8(8), R8(16), R8(24), R8(32), R8(40), R8(48), R8(56), R8(64), R8(72), R8(80), R8(88), R8(96), R8(104), R8(112), R8(120)
               : "l"(a), "l"(b), "r"(acc), "n"(TB));
}
template <int TB>
__device__ __forceinline__ void mma_n128_ss(float* d, uint64_t a, uint64_t b, int acc) {
  asm volatile("{\n.reg .pred p;\nsetp.ne.b32 p, %66, 0;\n"
               "wgmma.mma_async.sync.aligned.m64n128k16.f32.bf16.bf16 {" REGS64 "}, %64, %65, p, 1, 1, 0, %67;\n}\n"
               : R8(0), R8(8), R8(16), R8(24), R8(32), R8(40), R8(48), R8(56)
               : "l"(a), "l"(b), "r"(acc), "n"(TB));
}
template <int TB>
__device__ __forceinline__ void mma_n128_rs(float* d, const uint32_t* a, uint64_t b, int acc) {
  asm volatile("{\n.reg .pred p;\nsetp.ne.b32 p, %69, 0;\n"
               "wgmma.mma_async.sync.aligned.m64n128k16.f32.bf16.bf16 {" REGS64 "}, {%64,%65,%66,%67}, %68, p, 1, 1, %70;\n}\n"
               : R8(0), R8(8), R8(16), R8(24), R8(32), R8(40), R8(48), R8(56)
               : "r"(a[0]), "r"(a[1]), "r"(a[2]), "r"(a[3]), "l"(b), "r"(acc), "n"(TB));
}
__device__ __forceinline__ void mma_n64_rs(float* d, const uint32_t* a, uint64_t b, int acc) {
  asm volatile("{\n.reg .pred p;\nsetp.ne.b32 p, %37, 0;\n"
               "wgmma.mma_async.sync.aligned.m64n64k16.f32.bf16.bf16 {" REGS32 "}, {%32,%33,%34,%35}, %36, p, 1, 1, 0;\n}\n"
               : R8(0), R8(8), R8(16), R8(24)
               : "r"(a[0]), "r"(a[1]), "r"(a[2]), "r"(a[3]), "l"(b), "r"(acc));
}
#define W8(b) "=f"(d[b + 0]), "=f"(d[b + 1]), "=f"(d[b + 2]), "=f"(d[b + 3]), "=f"(d[b + 4]), "=f"(d[b + 5]), "=f"(d[b + 6]), "=f"(d[b + 7])
__device__ __forceinline__ void mma_n128_rs0(float* d, const uint32_t* a, uint64_t b) {
  asm volatile("wgmma.mma_async.sync.aligned.m64n128k16.f32.bf16.bf16 {" REGS64 "}, {%64,%65,%66,%67}, %68, 0, 1, 1, 0;\n"
               : W8(0), W8(8), W8(16), W8(24), W8(32), W8(40), W8(48), W8(56)
               : "r"(a[0]), "r"(a[1]), "r"(a[2]), "r"(a[3]), "l"(b));
}
__device__ __forceinline__ void mma_n64_rs0(float* d, const uint32_t* a, uint64_t b) {
  asm volatile("wgmma.mma_async.sync.aligned.m64n64k16.f32.bf16.bf16 {" REGS32 "}, {%32,%33,%34,%35}, %36, 0, 1, 1, 0;\n"
               : W8(0), W8(8), W8(16), W8(24)
               : "r"(a[0]), "r"(a[1]), "r"(a[2]), "r"(a[3]), "l"(b));
}
__device__ __forceinline__ uint32_t pack_bf16(float lo, float hi) {
  uint32_t r;
  asm("cvt.rn.bf16x2.f32 %0, %1, %2;" : "=r"(r) : "f"(hi), "f"(lo));
  return r;
}
__device__ __forceinline__ float bf_lo(uint32_t v) { return __uint_as_float(v << 16); }
__device__ __forceinline__ float bf_hi(uint32_t v) { return __uint_as_float(v & 0xFFFF0000u); }
__device__ __forceinline__ float bf_round(float v) { return bf_lo(pack_bf16(v, v)); }
__device__ __forceinline__ void stsm4(uint32_t addr, uint32_t r0, uint32_t r1, uint32_t r2, uint32_t r3) {
  asm volatile("stmatrix.sync.aligned.m8n8.x4.shared.b16 [%0], {%1,%2,%3,%4};" ::"r"(addr), "r"(r0), "r"(r1), "r"(r2), "r"(r3) : "memory");
}
__device__ __forceinline__ uint4 lds128(uint32_t addr) {
  uint4 v;
  asm volatile("ld.shared.v4.u32 {%0,%1,%2,%3}, [%4];" : "=r"(v.x), "=r"(v.y), "=r"(v.z), "=r"(v.w) : "r"(addr));
  return v;
}
__device__ __forceinline__ float ex2(float x) {
  float y;
  asm("ex2.approx.ftz.f32 %0, %1;" : "=f"(y) : "f"(x));
  return y;
}
__device__ __forceinline__ void pin_order(float v, uint32_t dummy) {
  asm volatile("{\n.reg .pred p;\nsetp.eq.b32 p, %0, 0xFFFFFFFF;\n@p st.shared.b32 [%1], %0;\n}" ::"r"(__float_as_uint(v)), "r"(dummy) : "memory");
}
__device__ __forceinline__ void sched_fence(uint32_t dummy) {
  asm volatile("{\n.reg .pred p;\n.reg .u32 c;\nsetp.eq.b32 p, %0, 0xFFFFFFFF;\nmov.u32 c, %%clock;\n@p st.shared.b32 [%0], c;\n}" ::"r"(dummy) : "memory");
}
__device__ __forceinline__ void idle(int n) {
  asm volatile("{\n.reg .pred p;\n.reg .u32 a, b;\nmov.u32 a, %%clock;\nLI:\nmov.u32 b, %%clock;\nsub.u32 b, b, a;\nsetp.lt.u32 p, b, %0;\n@p bra LI;\n}" ::"r"(n) : "memory");
}
__device__ __forceinline__ void stage_store_128(uint32_t base, int lane, const uint32_t* pk) {
  const int row = (lane & 7) + ((lane >> 3) & 1) * 8;
  const uint32_t rb = base + row * 128;
  const int hi = lane >> 4;
#pragma unroll
  for (int j = 0; j < 8; j++) {
    const int chunk = 2 * j + hi;
    const uint32_t a = rb + (j >> 2) * 8192 + (((chunk & 7) ^ (lane & 7)) << 4);
    stsm4(a, pk[4 * j + 0], pk[4 * j + 1], pk[4 * j + 2], pk[4 * j + 3]);
  }
}
__device__ __forceinline__ void ln_round(float mean, float var, float& m_bf, float& inv_s) {
  const uint32_t mv = pack_bf16(mean, var);
  m_bf = bf_lo(mv);
  float sq, rc;
  asm("sqrt.approx.f32 %0, %1;" : "=f"(sq) : "f"(bf_round(bf_hi(mv) + 1e-5f)));
  asm("rcp.approx.ftz.f32 %0, %1;" : "=f"(rc) : "f"(bf_round(sq)));
  inv_s = rc;
}
__device__ __forceinline__ uint32_t hadd2_bf(uint32_t a, uint32_t b) {
  uint32_t r;
  asm("add.rn.bf16x2 %0, %1, %2;" : "=r"(r) : "r"(a), "r"(b));
  return r;
}
__device__ __forceinline__ uint32_t ln_apply(uint32_t h, uint32_t nm2, float inv_s) {
  const uint32_t d = hadd2_bf(h, nm2);
  return pack_bf16(bf_lo(d) * inv_s, bf_hi(d) * inv_s);
}
__device__ __forceinline__ void ldsm4(uint32_t* r, uint32_t addr) {
  asm volatile("ldmatrix.sync.aligned.m8n8.x4.shared.b16 {%0,%1,%2,%3}, [%4];" : "=r"(r[0]), "=r"(r[1]), "=r"(r[2]), "=r"(r[3]) : "r"(addr) : "memory");
}
__device__ __forceinline__ void mma16816(float* d, uint32_t a0, uint32_t a1, uint32_t a2, uint32_t a3, uint32_t b0, uint32_t b1) {
  asm volatile("mma.sync.aligned.m16n8k16.row.col.f32.bf16.bf16.f32 {%0,%1,%2,%3}, {%4,%5,%6,%7}, {%8,%9}, {%0,%1,%2,%3};"
               : "+f"(d[0]), "+f"(d[1]), "+f"(d[2]), "+f"(d[3]) : "r"(a0), "r"(a1), "r"(a2), "r"(a3), "r"(b0), "r"(b1));
}

template <class F>
__device__ __forceinline__ void unroll8(F f) {
  f(std::integral_constant<int, 0>{}); f(std::integral_constant<int, 1>{}); f(std::integral_constant<int, 2>{}); f(std::integral_constant<int, 3>{});
  f(std::integral_constant<int, 4>{}); f(std::integral_constant<int, 5>{}); f(std::integral_constant<int, 6>{}); f(std::integral_constant<int, 7>{});
}

constexpr float AT_C = 0.08838834764831845f * 1.4426950408889634f;
#define AT_LO 0x1p-40f
#define AT_HI 0x1p40f
#define BNC 2
#define H_LATE 1
#define AT_R1 48
template <int I0, int I1>
__device__ __forceinline__ void at_exp(float* S) {
#pragma unroll
  for (int i = I0; i < I1; i++) asm volatile("ex2.approx.ftz.f32 %0, %0;" : "+f"(S[i]));
}
template <int I0, int I1>
__device__ __forceinline__ void at_fin(const float* S, uint32_t* P) {
#pragma unroll
  for (int i = I0; i < I1; i += 4) {
    P[i / 2] = pack_bf16(S[i], S[i + 1]); P[i / 2 + 1] = pack_bf16(S[i + 2], S[i + 3]);
  }
}
__device__ __forceinline__ void at_sum(const uint32_t* P, bool half, float& l0, float& l1) {
  uint32_t u[4];
#pragma unroll
  for (int r = 0; r < 4; r++) {
    const uint32_t* q = P + (r >> 1) * 16 + (r & 1);
    u[r] = hadd2_bf(hadd2_bf(hadd2_bf(q[0], q[2]), hadd2_bf(q[4], q[6])), hadd2_bf(hadd2_bf(q[8], q[10]), hadd2_bf(q[12], q[14])));
  }
  u[0] = hadd2_bf(u[0], half ? 0u : u[2]);
  u[1] = hadd2_bf(u[1], half ? 0u : u[3]);
  l0 += bf_lo(u[0]) + bf_hi(u[0]);
  l1 += bf_lo(u[1]) + bf_hi(u[1]);
}
template <int j>
__device__ __forceinline__ void at_mask1(float* S, int d) {
  float dummy0 = 0.f, dummy1 = 0.f;
  float& lo0 = j < 7 ? S[4 * (j < 7 ? j + 1 : j) + 2] : dummy0;
  float& lo1 = j < 7 ? S[4 * (j < 7 ? j + 1 : j) + 3] : dummy1;
  asm("{\n.reg .pred p, q;\nsetp.lt.s32 p, %4, %5;\nsetp.le.s32 q, %4, %5;\n"
      "@p add.f32 %0, %0, 0fFF800000;\n@q add.f32 %1, %1, 0fFF800000;\n@p add.f32 %2, %2, 0fFF800000;\n@q add.f32 %3, %3, 0fFF800000;\n}"
      : "+f"(S[4 * j]), "+f"(S[4 * j + 1]), "+f"(lo0), "+f"(lo1) : "r"(d), "r"(8 * j));
}
__device__ __forceinline__ void at_mask(float* S, int r, int lane) {
  unroll8([&](auto jc) { at_mask1<decltype(jc)::value>(S, r + (lane >> 2) - (lane & 3) * 2); });
}
__device__ __forceinline__ uint32_t ldg32(const __nv_bfloat16* p) { return __ldcg(reinterpret_cast<const uint32_t*>(p)); }
__device__ __forceinline__ uint32_t ldg16x2(const __nv_bfloat16* p, int stride) {
  return (uint32_t)__ldcg(reinterpret_cast<const unsigned short*>(p)) | ((uint32_t)__ldcg(reinterpret_cast<const unsigned short*>(p + stride)) << 16);
}
__device__ __forceinline__ void slow_tile(float* O, uint32_t* Q, float& l0, float& l1, const __nv_bfloat16* wq, int row0, int head, int lane, uint32_t dummy) {
  const int r = lane >> 2, q = lane & 3;
#pragma unroll
  for (int i = 0; i < 64; i++) O[i] = 0.f;
  {
    const __nv_bfloat16* xa = g_xn + (size_t)(row0 + r) * DM + 2 * q;
    const __nv_bfloat16* wb = wq + (size_t)(2 * q) * NQ + head * HD + (r >> 1) * 8 + (r & 1);
#pragma unroll 1
    for (int k = 0; k < DM; k += 16) {
      const uint32_t a0 = ldg32(xa + k), a1 = ldg32(xa + k + 8 * DM), a2 = ldg32(xa + k + 8), a3 = ldg32(xa + k + 8 * DM + 8);
#pragma unroll
      for (int j = 0; j < 16; j++) {
        const __nv_bfloat16* wp = wb + (size_t)k * NQ + (j >> 2) * 32 + (j & 3) * 2;
        mma16816(O + 4 * j, a0, a1, a2, a3, ldg16x2(wp, NQ), ldg16x2(wp + 8 * NQ, NQ));
        if (j == 7) sched_fence(dummy);
      }
    }
  }
#pragma unroll
  for (int i = 0; i < 32; i++) Q[i] = pack_bf16(O[2 * i], O[2 * i + 1]);
#pragma unroll
  for (int i = 0; i < 64; i++) O[i] = 0.f;
  float m0 = -INFINITY, m1 = -INFINITY;
  l0 = l1 = 0.f;
#pragma unroll 1
  for (int kv = 0; kv <= row0; kv += 16) {
    float s[8] = {0.f, 0.f, 0.f, 0.f, 0.f, 0.f, 0.f, 0.f};
    const __nv_bfloat16* kp = g_qkv + (size_t)(SEQ + kv + r) * NQ + head * HD + 2 * q;
#pragma unroll
    for (int k = 0; k < 8; k++) {
      mma16816(s, Q[4 * k], Q[4 * k + 1], Q[4 * k + 2], Q[4 * k + 3], ldg32(kp + 16 * k), ldg32(kp + 16 * k + 8));
      mma16816(s + 4, Q[4 * k], Q[4 * k + 1], Q[4 * k + 2], Q[4 * k + 3], ldg32(kp + 8 * NQ + 16 * k), ldg32(kp + 8 * NQ + 16 * k + 8));
    }
#pragma unroll
    for (int i = 0; i < 8; i++)
      if (kv + (i >> 2) * 8 + 2 * q + (i & 1) > row0 + r + (i & 2) * 4) s[i] = -INFINITY;
    float a = fmaxf(fmaxf(fmaxf(s[0], s[1]), fmaxf(s[4], s[5])), m0), b = fmaxf(fmaxf(fmaxf(s[2], s[3]), fmaxf(s[6], s[7])), m1);
    a = fmaxf(a, __shfl_xor_sync(~0u, a, 1)); b = fmaxf(b, __shfl_xor_sync(~0u, b, 1));
    a = fmaxf(a, __shfl_xor_sync(~0u, a, 2)); b = fmaxf(b, __shfl_xor_sync(~0u, b, 2));
    const float c0 = ex2(m0 - a), c1 = ex2(m1 - b);
    m0 = a; m1 = b;
#pragma unroll
    for (int i = 0; i < 8; i++) s[i] = ex2(s[i] - ((i & 2) ? b : a));
    l0 = l0 * c0 + (s[0] + s[1]) + (s[4] + s[5]);
    l1 = l1 * c1 + (s[2] + s[3]) + (s[6] + s[7]);
    sched_fence(dummy);
    const uint32_t p0 = pack_bf16(s[0], s[1]), p1 = pack_bf16(s[2], s[3]), p2 = pack_bf16(s[4], s[5]), p3 = pack_bf16(s[6], s[7]);
    const __nv_bfloat16* vp = g_qkv + (size_t)(2 * SEQ + kv + 2 * q) * NQ + head * HD + r;
#pragma unroll
    for (int j = 0; j < 16; j++) {
      O[4 * j] *= c0; O[4 * j + 1] *= c0; O[4 * j + 2] *= c1; O[4 * j + 3] *= c1;
      mma16816(O + 4 * j, p0, p1, p2, p3, ldg16x2(vp + 8 * j, NQ), ldg16x2(vp + 8 * NQ + 8 * j, NQ));
      if (j == 7) sched_fence(dummy);
    }
  }
}

constexpr int P1_STAGE = 49152;
constexpr int SLOT = 32768;
constexpr int OFF_LN = 6 * SLOT, OFF_R3 = 0;
constexpr int OFF_BAR = 229376;
constexpr int OFF_MISC = OFF_BAR + 8 * 58;
constexpr int SMEM_BYTES = OFF_MISC + 2080 + TL_BYTES;
enum : int {
  B_FULL1 = 0, B_KF = 4, B_VF = 6, B_FULL3 = 8, B_XF = 14, B_LN = 15, B_DEP = 16, B_OUT2 = 22, B_FIN = 23, B_SET = 24, B_SET2 = 25, B_QP = 26, B_WF2 = 29,
  B_WF = 30, B_WR = 31,
  B_LND = 32,
  B_XE = 33, B_PUB = 34, B_OUT = 40, B_OUT3 = 41,
  B_EMPTY1 = 42, B_KE = 46, B_VE = 48, B_EMPTY3 = 50, B_WE = 56, B_NUM = 57
};
#define PRE 3
#define LN_PF 4
#define LN_LD 9
constexpr int LN_PFN = 2;
constexpr int OFF_STG = SLOT, SL_SCR = 2;
#define SET_NS 50
#define ST_G 1
#define ST_NS 0
#define OBS 99
#define PFALL 0
#define WQ_D 4
#define WQ_0 18
#define SL_NS 600
#define X_KB 20
#define G_KB 35
#define WD_AT 8
#define YD 700
#define OUT_R 64
#define OUT_CLK 500
#define W_G0 22
#define KVPF 1
struct Params {
  CUtensorMap xn, ckv, wq, wk, wv, kv, ctx_ld, ctx_st, wo, x, wd, wg, wu, out;
};

__global__ void __cluster_dims__(2, 1, 1) __launch_bounds__(384, 1)
fused_kernel(const __nv_bfloat16* __restrict__ x, const __nv_bfloat16* __restrict__ wq, const __nv_bfloat16* __restrict__ w_r,
             __nv_bfloat16* __restrict__ out, const __grid_constant__ Params p) {
  extern __shared__ __align__(1024) uint8_t sp[];
  const uint32_t sb = s2u(sp);
  const uint32_t bar = sb + OFF_BAR;
  auto B = [&](int i) { return bar + 8 * i; };
  const int tid = threadIdx.x, warp = __shfl_sync(~0u, tid >> 5, 0), wg = warp >> 2, lane = tid & 31;
  const int cta = blockIdx.x, rank = cta & 1, cl = cta >> 1;
  const int mp = cl < 4 ? 1 : (cl < 36 ? (cl & 7) : (0x3207654 >> (4 * ((cl - 36) % 7))) & 7);
  const int gq = cl < 4 ? 4 + cl : (cl < 36 ? (cl - 4) >> 3 : 4 + (cl - 36) / 7);
  const int mt = 2 * mp + rank;
  const int ti = (gq & 3) * 2 + rank, hh = mp * 2 + (gq >> 2);
  const int rid = mt * 8 + gq;
  const int fid = mt * 7 + gq;
  const bool ffn = gq < 7;
  uint4* const xr = g_xr + rid * XR_SIZE;
  TL_INIT();
  TL(0, 0, tid == 128);
  if (warp == 0) {
    if (elect_one()) {
#pragma unroll
      for (int kb = 0; kb < PRE; kb++) mbar_init(B(B_FULL1 + kb), 1);
      asm volatile("fence.mbarrier_init.release.cluster;" ::: "memory");
    }
    __syncwarp();
    cluster_arrive();
    if (elect_one()) {
#pragma unroll
      for (int kb = 0; kb < PRE; kb++) {
        mbar_expect(B(B_FULL1 + kb), P1_STAGE);
        tma_ld2(sb + kb * P1_STAGE, &p.ckv, B(B_FULL1 + kb), kb * 64, mt * 128);
        tma_ld3(sb + kb * P1_STAGE + 16384 + rank * 16384, &p.wk, B(B_FULL1 + kb), 0, kb * 64, gq * 4 + rank * 2);
        tma_ld3(sb + kb * P1_STAGE + 32768 - rank * 16384, &p.wk, B(B_FULL1 + kb), 0, kb * 64, gq * 4 + 2 - rank * 2);
      }
    }
  } else if (elect_one()) {
#pragma unroll 1
    for (int i = PRE + warp - 1; i < B_NUM; i += 11)
      mbar_init(B(i), i >= B_EMPTY1 ? 16 : (i >= B_XE ? 8 : (i == B_LND ? 3 : (i >= B_WF ? 2 : 1))));
    asm volatile("fence.mbarrier_init.release.cluster;" ::: "memory");
  }
  __syncwarp();
  if (warp) cluster_arrive();
  if (wg == 0) {
    reg_dealloc<40>();
    if (warp == 1 && elect_one()) {
      if (mt >= 2 * PRE) tma_pf3(&p.wk, 0, mp * 64, gq * 4 + rank * 2);
      if (gq >= PRE) asm volatile("cp.async.bulk.prefetch.tensor.2d.L2.global [%0, {%1,%2}];" ::"l"(&p.ckv), "r"(gq * 64), "r"(mt * 128) : "memory");
    } else if (warp == 2 && elect_one()) {
      prefetch_tm(&p.wv); prefetch_tm(&p.wq); prefetch_tm(&p.xn);
    }
    __syncwarp();
    cluster_wait();
    if (warp == 0) {
      int st = 0; uint32_t ph = 1;
#pragma unroll 1
      for (int t = 0; t < 6; t++) {
        const CUtensorMap* ma = t >= 4 ? &p.xn : &p.ckv;
        const CUtensorMap* mb = t >= 4 ? &p.wq : ((t & 1) ? &p.wv : &p.wk);
        const int nk = t >= 4 ? 16 : 8;
        const int row = (t < 4 ? mt : (t == 4 ? 15 - ti : ti)) * 128;
        const int col = t < 4 ? (gq + (t >> 1) * 8) * 4 + rank * 2 : (hh + rank * 16) * 2;
        if (t >= 4) mbar_wait(B(B_DEP + t - 4), 0);
#pragma unroll 1
        for (int kb = 0; kb < nk; kb++) {
          const uint32_t d = sb + st * P1_STAGE, fb = B(B_FULL1 + st);
          const int n = t * 8 + kb;
          if (n >= PRE) {
            mbar_wait_c(B(B_EMPTY1 + st), ph);
            if (elect_one()) {
              mbar_expect(fb, P1_STAGE);
              tma_ld2(d, ma, fb, kb * 64, row);
              tma_ld3_mc(d + 16384 + rank * 16384, mb, fb, 0, kb * 64, col, 3);
            }
          }
          if (t < 5 && elect_one()) {
            if (n >= LN_PF && n < LN_PF + LN_PFN) l2_prefetch(x + (size_t)cta * 16 * DM + (n - LN_PF) * (16 * DM / LN_PFN), 32768 / LN_PFN);
            if (n == LN_LD) {
              mbar_expect(B(B_LN), 32768);
              asm volatile("cp.async.bulk.shared::cluster.global.mbarrier::complete_tx::bytes [%0], [%1], %2, [%3];" ::"r"(sb + OFF_LN),
                           "l"(x + (size_t)cta * 16 * DM), "r"(32768), "r"(B(B_LN)) : "memory");
            }
            if (t < 3 && kb == 0) tma_pf3((t & 1) ? &p.wk : &p.wv, 0, mp * 64, (gq + ((t + 1) >> 1) * 8) * 4 + rank * 2);
            if (n >= WQ_0 && n < WQ_0 + 4 * WQ_D && (n - WQ_0) % WQ_D == 0) tma_pf3(&p.wq, 0, ((n - WQ_0) / WQ_D * 4 + (gq & 3)) * 64, (hh + rank * 16) * 2);
          }
          if (++st == 4) { st = 0; ph ^= 1; }
        }
      }
      if (elect_one()) { prefetch_tm(&p.kv); prefetch_tm(&p.ctx_ld); prefetch_tm(&p.wo); prefetch_tm(&p.wg); prefetch_tm(&p.wu); }
      auto load_kv = [&](int g, int isv) {
        const int h2 = g >= 17, sx = g - 17 * h2, n1 = h2 ? ti + 1 : 16 - ti;
        const int row = (1 + isv) * SEQ + (sx < n1 ? sx : 16 - sx) * 128, col = (hh + 16 * h2) * 2;
        const uint32_t d = sb + (isv ? 2 + 2 * (g & 1) : (g & 1)) * SLOT, fb = B(B_KF + 2 * isv + (g & 1));
        const bool ef = sx >= n1 || sx >= 8;
        const bool shared = sx != (h2 ? (ti & 6) + 1 : 15 - (ti & 6));
        const int g2 = g + KVPF, h3 = g2 >= 17, s3 = g2 - 17 * h3;
        const int pb = PFALL ? (g2 < 34 ? (s3 < (h3 ? ti + 1 : 16 - ti) ? s3 : 16 - s3) : -1)
                             : (ti < 2 ? (h3 ? (s3 >= 1 && s3 <= 8 ? 16 - s3 : -1) : (s3 < 16 ? s3 : -1)) : (ti >= 6 && h3 && s3 < 8 ? s3 : -1));
        mbar_wait_c(g < 2 ? B(B_EMPTY1 + (isv ? 1 + 2 * g : g)) : B(B_KE + 2 * isv + (g & 1)), g < 2 ? 1 : ((g >> 1) & 1) ^ 1);
        if (elect_one()) {
          mbar_expect(fb, SLOT);
          if (shared) {
            tma_ld3_mc(d + rank * 16384, &p.kv, fb, 0, row, col + rank, 3, ef);
          } else {
            tma_ld3(d, &p.kv, fb, 0, row, col, ef);
            tma_ld3(d + 16384, &p.kv, fb, 0, row, col + 1, ef);
          }
          if (KVPF && pb >= 0) tma_pf3(&p.kv, 0, (1 + isv) * SEQ + pb * 128, (hh + 16 * h3) * 2 + rank);
        }
      };
      int nw = ffn ? 0 : 12;
      auto load_w = [&]() {
        const int c = nw < 8 ? (nw >> 2) + (nw & 2) : nw >> 1;
        if (elect_one()) {
          if (!(nw & 3)) mbar_expect(B(B_WF - (nw >> 3)), 32768);
          tma_ld2(sb + (c < 2 ? 3 : 4) * SLOT + c * 16384 + (nw & 1) * 8192, (nw & 1) ? &p.wg : &p.wu, B(B_WF - (nw >> 3)), fid * 32, c * 128, true);
        }
        nw++;
      };
#pragma unroll 1
      for (int g = 0; g < 34; g++) {
        if (g == 0 || g == 17 - KVPF) mbar_wait(B(B_DEP + 2 + (g > 0)), 0);
        load_kv(g, 0);
        if (g > 0) load_kv(g - 1, 1);
        if (g >= W_G0 && nw < 12 && __any_sync(~0u, mbar_test(B(B_QP + (nw >> 2)), 0))) load_w();
      }
      load_kv(33, 1);
#pragma unroll 1
      while (nw < 12) { mbar_wait(B(B_QP + (nw >> 2)), 0); load_w(); }
      if (elect_one()) { prefetch_tm(&p.wd); prefetch_tm(&p.x); prefetch_tm(&p.out); }
      auto load3 = [&](int kb, int sl) {
        if (elect_one()) {
          mbar_expect(B(B_FULL3 + sl), SLOT);
          tma_ld2(sb + OFF_R3 + sl * SLOT, &p.ctx_ld, B(B_FULL3 + sl), kb * 64, mt * 128);
          tma_ld3_mc(sb + OFF_R3 + sl * SLOT + 16384 + rank * 8192, &p.wo, B(B_FULL3 + sl), 0, kb * 64, gq * 2 + rank, 3);
          if (kb >= OBS && kb < OBS + 11) TL(0, 32 + kb - OBS, true);
        }
      };
      mbar_wait(B(B_DEP + 4), 0);
#pragma unroll
      for (int kb = 0; kb < 5; kb++) {
        mbar_wait_c(B(kb == 3 ? B_WE : (kb == 4 ? B_VE + 1 : B_KE + kb)), 0);
        load3(kb, kb);
      }
      if (elect_one()) mbar_arrive(B(B_FULL3 + 5));
#pragma unroll 1
      for (int r = 1; r < 11; r++) {
#pragma unroll
        for (int j = 0; j < 6; j++) {
          if (j == 5 && r == 10) break;
          if (j == 3 && r == 5) mbar_wait(B(B_DEP + 5), 0);
          mbar_wait_c(B(B_EMPTY3 + j), ~r & 1);
          load3(r * 6 + j - 1, j);
          if (j == 5 && r == 9 && elect_one()) l2_prefetch(xr, XR_CAND * 16);
        }
      }
      if (ffn) {
#pragma unroll
        for (int j = 1; j >= 0; j--) {
          mbar_wait(B(B_EMPTY3 + 5 * j), j);
          if (elect_one()) {
            mbar_expect(B(B_FULL3 + 5 * j), SLOT);
            tma_ld3(sb + OFF_R3 + 5 * j * SLOT, &p.wd, B(B_FULL3 + 5 * j), 0, fid * 32, 8 * j, true);
          }
        }
      }
    } else {
      if (warp >= 2) {
#pragma unroll 1
        for (int i = tid - 64; i < XR_CAND; i += 64) xr[i] = make_uint4(~0u, ~0u, ~0u, ~0u);
        if (warp == 2) { __syncwarp(); if (lane == 0) mbar_arrive(B(B_WR)); }
      }
      if (warp == 3) {
        float ws = 0.f;
#pragma unroll
        for (int j = 0; j < 4; j++) {
          const uint4 q = __ldg(reinterpret_cast<const uint4*>(w_r) + j * 32 + lane);
          ws += bf_lo(q.x) + bf_hi(q.x) + bf_lo(q.y) + bf_hi(q.y) + bf_lo(q.z) + bf_hi(q.z) + bf_lo(q.w) + bf_hi(q.w);
        }
#pragma unroll
        for (int o = 16; o; o >>= 1) ws += __shfl_xor_sync(~0u, ws, o);
        uint2* tab = reinterpret_cast<uint2*>(sp + OFF_MISC + 512);
        tab[lane] = make_uint2(0x3F803F80u, 0x3F803F80u);
        tab[32 + lane] = __ldg(reinterpret_cast<const uint2*>(w_r + gq * 128) + lane);
        if (lane == 0) *reinterpret_cast<float*>(sp + OFF_MISC + 1024) = ws;
        __syncwarp();
        if (lane == 0) mbar_arrive(B(B_WR));
      }
      if (tid == 32) TS(0);
      mbar_wait(B(B_LN), 0);
#pragma unroll 1
      for (int r = warp - 1; r < 16; r += 3) {
        uint4 v[4];
        float a0 = 0.f, a1 = 0.f, b0 = 0.f, b1 = 0.f;
#pragma unroll
        for (int j = 0; j < 4; j++) {
          v[j] = lds128(sb + OFF_LN + r * 2048 + lane * 16 + j * 512);
          const uint32_t u[4] = {v[j].x, v[j].y, v[j].z, v[j].w};
#pragma unroll
          for (int i = 0; i < 4; i++) { const float a = bf_lo(u[i]), b = bf_hi(u[i]); a0 += a; a1 += b; b0 = fmaf(a, a, b0); b1 = fmaf(b, b, b1); }
        }
        a0 += a1; b0 += b1;
#pragma unroll
        for (int o = 16; o; o >>= 1) { a0 += __shfl_xor_sync(~0u, a0, o); b0 += __shfl_xor_sync(~0u, b0, o); }
        const float mean = a0 * (1.f / DM);
        float mb, inv;
        ln_round(mean, fmaxf(fmaf(b0, 1.f / DM, -mean * mean), 0.f), mb, inv);
        inv *= AT_C;
        const uint32_t nm2 = pack_bf16(-mb, -mb);
        uint4* dst = reinterpret_cast<uint4*>(g_xn + (size_t)(cta * 16 + r) * DM) + lane;
#pragma unroll
        for (int j = 0; j < 4; j++)
          dst[j * 32] = make_uint4(ln_apply(v[j].x, nm2, inv), ln_apply(v[j].y, nm2, inv), ln_apply(v[j].z, nm2, inv), ln_apply(v[j].w, nm2, inv));
      }
      __syncwarp();
      if (lane == 0) {
        mbar_arrive(B(B_LND));
        fence_gpu();
        red_add(&g_cnt[C_LN + (cta >> 3)], 1);
      }
      TL(3, warp, lane == 0);
      __syncwarp();
      if (warp == 3) {
        if (lane == 0) {
#pragma unroll 1
          for (int i = 0; i < 6; i++) {
            const int c = i < 2 ? C_LN + (i ? ti : 15 - ti) : (i < 4 ? C_QKV + (i - 2) * 8 + mp : C_CTX + (i - 4) * 16 + mt);
            spin_until_ge<true>(&g_cnt[c], i < 2 ? 24 : 16);
            fence_async_all();
            mbar_arrive(B(B_DEP + i));
            TL(3, 4 + i, true);
          }
        }
      } else if (warp == 1 && elect_one()) {
        mbar_wait(B(B_WR), 0);
#pragma unroll 1
        for (int i = 0; i < 6; i++) {
          const int c = i < 2 ? C_QKV + gq + i * 8 : C_CTX + (i >> 2) * 16 + ((i == 3 || i == 4) ? ti : 15 - ti);
          mbar_wait(B(B_PUB + i), 0);
          if (i >= 2 && i < 5) {
            asm volatile("fence.proxy.async.shared::cta;" ::: "memory");
#pragma unroll 1
            for (int n = 0; n < 8 / ST_G; n++) {
              const int h = n / (4 / ST_G), a = n % (4 / ST_G) * ST_G;
              asm volatile("cp.async.bulk.tensor.3d.global.shared::cta.bulk_group [%0, {%2,%3,%4}], [%1];" ::"l"(&p.ctx_st),
                           "r"(sb + (i == 4 ? 6 * SLOT + h * 16384 : (3 + 2 * h) * SLOT + (i - 2) * 16384) + a * 4096),
                           "r"(0), "r"((i == 2 ? 15 - ti : ti) * 128 + h * 64), "r"((hh + (i >> 2) * 16) * 4 + a) : "memory");
              asm volatile("cp.async.bulk.commit_group;\ncp.async.bulk.wait_group.read 0;" ::: "memory");
              if (ST_NS) __nanosleep(ST_NS);
            }
            mbar_arrive(B(B_QP + i - 2));
            asm volatile("cp.async.bulk.wait_group 0;" ::: "memory");
          }
          fence_gpu();
          red_add(&g_cnt[c], 1);
          TS(1 + i);
        }
      }
      if (warp == 2) {
#pragma unroll 1
        for (int n = 0; n < 8; n++) {
          if (!(n & 3)) mbar_wait(B(B_XE), n >> 2);
          if ((n < 4 || ffn) && elect_one()) {
            const uint32_t fb = B(n < 4 ? B_XF : B_WF2), d = sb + 6 * SLOT + (n & 3) * 8192;
            if (!(n & 3)) mbar_expect(fb, 32768);
            if (n < 4) tma_ld3(d, &p.x, fb, 0, mt * 128 + (n >> 1) * 64, gq * 2 + (n & 1), true);
            else tma_ld2(d, (n & 1) ? &p.wg : &p.wu, fb, fid * 32, (4 + (n >> 1)) * 128, true);
          }
          __nanosleep(SL_NS);
        }
#pragma unroll 1
        for (int i = XR_CAND + lane; i < XR_SIZE; i += 32) { xr[i] = make_uint4(~0u, ~0u, ~0u, ~0u); if (SET_NS) __nanosleep(SET_NS); }
        __syncwarp();
        if (lane == 0) { fence_gpu(); mbar_arrive(B(B_SET2)); }
        TL(2, 26, lane == 0);
        __syncwarp();
      }
      __syncwarp();
      if (warp == 3) {
        mbar_wait(B(B_OUT), 0);
        uint4 kv[2];
        poll_chunks(kv, g_xr + ((lane >> 1) * 8 + gq) * XR_SIZE + XR_KEY + (lane & 1) * 2, 1);
        const uint32_t a1 = max(kv[0].x, kv[0].z), a2 = max(min(kv[0].x, kv[0].z), max(kv[0].y, kv[0].w));
        const uint32_t b1 = max(kv[1].x, kv[1].z), b2 = max(min(kv[1].x, kv[1].z), max(kv[1].y, kv[1].w));
        const uint32_t k1 = max(a1, b1), k2 = max(min(a1, b1), max(a2, b2));
        const uint32_t m1 = __reduce_max_sync(~0u, k1);
        const uint32_t m2 = __reduce_max_sync(~0u, k1 == m1 ? k2 : k1);
        if (lane == 0) {
          *reinterpret_cast<uint2*>(sp + OFF_MISC) = make_uint2(m1, m2);
          mbar_arrive(B(B_OUT2));
        }
        const uint32_t key = (lane & 4) ? m2 : m1;
        const int tk = 0x7FFF - (key & 0x7FFF);
        const uint4* src = g_xr + ((tk >> 7) * 8 + (rid >> 4)) * XR_SIZE;
        poll_chunks(kv, src + XR_CAND + ((tk >> 4) & 7) * 64 + (((lane & 4) && !((m1 ^ m2) & 0x7FF0)) ? 16 : 0) + (rid & 12) + (lane & 3), 32);
        uint32_t u = key >> 16;
        u = (u & 0x8000u) ? (u & 0x7FFFu) : (~u & 0xFFFFu);
        const float rs = bf_round(__fdividef(1.f, 1.f + __expf(-__uint_as_float(u << 16))));
        if (lane < 8)
          *reinterpret_cast<uint4*>(sp + OFF_MISC + 128 + lane * 16) = make_uint4((rid & 2) ? ((rid & 1) ? kv[0].w : kv[0].z) : ((rid & 1) ? kv[0].y : kv[0].x),
              (rid & 2) ? ((rid & 1) ? kv[1].w : kv[1].z) : ((rid & 1) ? kv[1].y : kv[1].x), __float_as_uint(rs), 0);
#pragma unroll 1
        for (int n = 0; n < 0x400000; n++) {
          uint32_t v;
          asm volatile("ld.acquire.gpu.global.u32 %0, [%1];" : "=r"(v) : "l"(src + XR_FLAG) : "memory");
          if (__all_sync(~0u, v == 0)) break;
        }
        if (lane == 0) mbar_arrive(B(B_FIN));
      }
      if (warp == 1 && elect_one()) {
        mbar_wait(B(B_OUT3), 0);
        auto owner = [&]() {
          uint2 top;
          asm volatile("ld.shared.v2.u32 {%0,%1}, [%2];" : "=r"(top.x), "=r"(top.y) : "r"(sb + OFF_MISC) : "memory");
          return (0x7FFF - (top.x & 0x7FFF)) >> 7 == mt || (0x7FFF - (top.y & 0x7FFF)) >> 7 == mt;
        };
#pragma unroll 1
        for (int n = 0; n < 256 / OUT_R; n++) {
          if (n && !(mbar_test(B(B_OUT2), 0) && owner())) idle(OUT_CLK);
          asm volatile("cp.async.bulk.tensor.2d.global.shared::cta.bulk_group [%0, {%2,%3}], [%1];" ::"l"(&p.out), "r"(sb + OFF_STG + n * OUT_R * 128),
                       "r"(gq * 128 + (n * OUT_R & 64)), "r"(mt * 128 + (n * OUT_R >> 7) * 64 + (n * OUT_R & 63)) : "memory");
        }
        asm volatile("cp.async.bulk.commit_group;" ::: "memory");
        mbar_wait(B(B_OUT2), 0);
        if (owner()) {
          asm volatile("cp.async.bulk.wait_group 0;" ::: "memory");
          asm volatile("st.release.gpu.global.u32 [%0], 0;" ::"l"(xr + XR_FLAG) : "memory");
        } else {
          asm volatile("cp.async.bulk.wait_group.read 0;" ::: "memory");
        }
        TL(2, 25, true);
      }
    }
    __syncwarp();
    cluster_arrive();
    cluster_wait();
    TL_DUMP();
    if (tid == 32) TS(8);
  } else {
    reg_alloc<232>();
    cluster_wait();
    const int w = wg - 1, cw = warp - 4;
    int lane = lane_id();
    const uint32_t stg = sb + OFF_STG + w * 16384 + (cw & 3) * 2048;
    auto publish = [&](int i) { __syncwarp(); if (lane == 0) mbar_arrive(B(B_PUB + i)); };
    uint32_t rbar;
    asm("mapa.shared::cluster.u32 %0, %1, %2;" : "=r"(rbar) : "r"(bar), "r"(lane & 1));
    auto release2 = [&](int i) { if (lane < 2) asm volatile("mbarrier.arrive.shared::cluster.b64 _, [%0];" ::"r"(rbar + 8 * i) : "memory"); };
    float R[128];
    float O[64], acc[64];
    uint32_t pk[64];
    uint32_t* const Q = pk;
    uint32_t P[32];
    auto packed = [&](int i) {
      const float* v = R + 16 * (i >> 1) + 2 * (i & 1);
      return make_uint4(pack_bf16(v[0], v[1]), pack_bf16(v[4], v[5]), pack_bf16(v[8], v[9]), pack_bf16(v[12], v[13]));
    };
    const uint32_t q_st = sb + (cw & 3) * 1024 + (lane >> 2) * 64 + (((lane & 3) ^ (lane >> 3)) << 4);
    const uint32_t q_ld = sb + (cw & 3) * 1024 + (lane & 15) * 64 + (((lane >> 4) ^ ((lane >> 1) & 3)) << 4);
    auto park = [&](uint32_t off, int i, uint4 v) {
      asm volatile("st.shared.v4.u32 [%0], {%1,%2,%3,%4};" ::"r"(q_st + off + (i >> 1) * 4096 + (i & 1) * 512), "r"(v.x), "r"(v.y), "r"(v.z), "r"(v.w) : "memory");
    };
    auto load_q = [&](uint32_t off, int k) { ldsm4(Q + 4 * k, ((q_ld + off) ^ ((k & 1) << 5)) + (k >> 1) * 4096); };
    {
      TL(0, 1, tid == 128);
      __nv_bfloat16* pdst = g_qkv;
      auto put2 = [&](int j) {
#pragma unroll
        for (int i = (j >> 1) * 4 + (j & 1); i < (j >> 1) * 4 + 4; i += 2)
          __stcs(reinterpret_cast<uint4*>(pdst + (i & 1) * 8 * NQ + (i >> 1) * 32), make_uint4(pk[4 * i], pk[4 * i + 1], pk[4 * i + 2], pk[4 * i + 3]));
      };
      const uint64_t da0 = mk_desc(sb + w * 8192, 16, 1024, 1);
      const uint64_t db0 = mk_desc(sb + 16384, 8192, 1024, 1);
      int st = 0; uint32_t ph = 0;
      auto issue = [&](int accum, auto between) {
        mbar_wait_c(B(B_FULL1 + st), ph);
        const uint64_t da = desc_add(da0, st * P1_STAGE), db = desc_add(db0, st * P1_STAGE);
        between();
        wg_fence();
#pragma unroll
        for (int k = 0; k < 4; k++) mma_n256_ss<1>(R, desc_add(da, k * 32), desc_add(db, k * 2048), k == 0 ? accum : 1);
        wg_commit();
      };
      issue(0, []() {});
#pragma unroll 1
      for (int t = 0;; t++) {
        const int nk = t >= 4 ? 16 : 8;
        const bool tr = t > 0 && t < 5;
        TL(0, 2 + 2 * t + 16 * w, (tid & 127) == 0);
        int prev = st;
        if (++st == 4) { st = 0; ph ^= 1; }
#pragma unroll 1
        for (int kb = 1; kb < nk; kb++) {
          if (kb == nk - 1 && w == 1) bar_sync(5, 256);
          issue(1, []() {});
          if (kb == nk - 1 && w == 0) bar_arrive(5, 256);
          if (tr) {
#pragma unroll
            for (int i = 1; i < 8; i++) if (kb == i) put2(i);
            if (kb == 7 && !(t & 1)) publish((t >> 1) - 1);
          } else if (t == 5) {
            if (kb == 2) {
              mbar_wait_c(B(B_LND), 0);
#pragma unroll
              for (int i = 0; i < 8; i++) park(6 * SLOT + w * 16384, i, make_uint4(pk[4 * i], pk[4 * i + 1], pk[4 * i + 2], pk[4 * i + 3]));
              __syncwarp();
            }
            if (kb == 2 + BNC) {
#pragma unroll
              for (int k = 0; k < 8; k++) load_q(6 * SLOT + w * 16384, k);
              __syncwarp();
            }
            if (kb == 2 + 2 * BNC) {
#pragma unroll
              for (int i = 0; i < 8; i++) park(6 * SLOT + w * 16384, i, make_uint4(pk[32 + 4 * i], pk[33 + 4 * i], pk[34 + 4 * i], pk[35 + 4 * i]));
            }
          }
          wg_wait<1>();
          release2(B_EMPTY1 + prev);
          prev = st;
          if (++st == 4) { st = 0; ph ^= 1; }
        }
        if (t == 5) break;
        issue(0, [&]() {
          sched_fence(q_st);
          wg_wait<0>();
          fence_regs<128>(R);
          TL(0, 3 + 2 * t + 16 * w, (tid & 127) == 0);
#pragma unroll
          for (int i = 0; i < 16; i++) { const uint4 v = packed(i); pk[4 * i] = v.x; pk[4 * i + 1] = v.y; pk[4 * i + 2] = v.z; pk[4 * i + 3] = v.w; }
          release2(B_EMPTY1 + prev);
          fence_regs<128>(R);
        });
        sched_fence(q_st);
        pdst = g_qkv + (size_t)(((t & 1) + 1) * SEQ + mt * 128 + cw * 16 + (lane >> 2)) * NQ + (gq + (t >> 1) * 8) * 256 + (lane & 3) * 8;
        if (t < 4) put2(0);
      }
      if (w == 1) bar_arrive(6, 256);
      mbar_wait_c(B(B_KF), 0);
      sched_fence(q_st);
      wg_wait<0>();
      fence_regs<128>(R);
      release2(B_EMPTY1 + 3);
      TL(0, 13 + 16 * w, (tid & 127) == 0);
    }
    auto issue3 = [&](int st, uint32_t ph, int accum) {
      mbar_wait_c(B(B_FULL3 + st), ph);
      const uint64_t da = mk_desc(sb + OFF_R3 + w * 8192 + st * SLOT, 16, 1024, 1), db = mk_desc(sb + OFF_R3 + 16384 + st * SLOT, 8192, 1024, 1);
      wg_fence();
#pragma unroll
      for (int k = 0; k < 4; k++) mma_n128_ss<1>(acc, desc_add(da, k * 32), desc_add(db, k * 2048), k == 0 ? accum : 1);
      wg_commit();
    };
    uint32_t wf[128];
    auto w_addr = [&](uint32_t off, int m) {
      const uint32_t w_ld = sb + ((lane >> 3) & 1) * 8192 + ((cw >> 1) * 32 + (lane & 7) + (lane >> 4) * 8) * 64 + ((((cw & 1) * 2) ^ ((lane >> 1) & 3)) << 4);
      return ((w_ld + off) ^ ((m & 1) << 4)) + (m >> 2) * 16384 + ((m >> 1) & 1) * 1024;
    };
    auto grab = [&](uint32_t* d, uint32_t off, int m0, int m1) {
#pragma unroll
      for (int m = m0; m < m1; m++)
        asm volatile("ldmatrix.sync.aligned.m8n8.x4.trans.shared.b16 {%0,%1,%2,%3}, [%4];"
                     : "=r"(d[4 * m]), "=r"(d[4 * m + 1]), "=r"(d[4 * m + 2]), "=r"(d[4 * m + 3]) : "r"(w_addr(off, m)) : "memory");
    };
    float inv[2] = {0.f, 0.f};
    auto scaled = [&](int i) {
      const float* o = O + 16 * (i >> 1) + 2 * (i & 1);
      const float c = inv[i & 1];
      return make_uint4(pack_bf16(o[0] * c, o[1] * c), pack_bf16(o[4] * c, o[5] * c), pack_bf16(o[8] * c, o[9] * c), pack_bf16(o[12] * c, o[13] * c));
    };
    {
      const int wrow = cw * 16;
      const uint64_t dk0 = mk_desc(sb, 16, 1024, 1);
      const uint64_t dv0 = mk_desc(sb + 2 * SLOT, 16384, 1024, 1);
      const uint32_t pin = sb + OFF_MISC + 1028;
      float l0 = 0.f, l1 = 0.f;
      int g = 0, t = 0;
      uint32_t fail = 0;
      auto piece = [&](int tt) { return (uint32_t)(tt == 3 ? 6 * SLOT + w * 16384 : (3 + 2 * w) * SLOT + (tt - 1) * 16384); };
      uint32_t par = 0;
      auto issue_s = [&](float* S) {
        const uint64_t dk = desc_add(dk0, par * 16);
        mma_n128_rs0(S, Q, dk);
#pragma unroll
        for (int k = 1; k < 8; k++) mma_n128_rs<0>(S, Q + 4 * k, desc_add(dk, (k >> 2) * 16384 + (k & 3) * 32), 1);
        wg_commit();
      };
      auto issue_pv = [&](bool half, int accum) {
        const uint64_t dv = desc_add(dv0, ((g - 1) & 1) * 2 * SLOT);
        wg_fence();
#pragma unroll
        for (int k = 0; k < 4; k++) mma_n128_rs<1>(O, P + 4 * k, desc_add(dv, k * 2048), k == 0 ? accum : 1);
        wg_commit();
        if (UNLIKELY(half)) {
          wg_fence();
          wg_commit();
        } else {
          wg_fence();
#pragma unroll
          for (int k = 4; k < 8; k++) mma_n128_rs<1>(O, P + 4 * k, desc_add(dv, k * 2048), 1);
          wg_commit();
        }
        bar_arrive(2 - w, 256);
        wg_wait<2>();
        fence_regs<32>(Q);
      };
      auto release_k = [&]() { release2(B_KE); rbar ^= 8; };
      auto pv_done = [&]() {
        TC(g, 3);
        sched_fence(q_st);
        wg_wait<0>();
        fence_regs<64>(O); fence_regs<32>(P);
        TC(g, 4);
        release2(B_VE);
      };
      auto row_inv = [&](bool go) {
        float a = l0 + __shfl_xor_sync(~0u, l0, 1), b = l1 + __shfl_xor_sync(~0u, l1, 1);
        a += __shfl_xor_sync(~0u, a, 2); b += __shfl_xor_sync(~0u, b, 2);
        const bool ok = __all_sync(~0u, a >= AT_LO && a <= AT_HI && b >= AT_LO && b <= AT_HI) != 0;
        asm("rcp.approx.ftz.f32 %0, %1;" : "=f"(inv[0]) : "f"(a));
        asm("rcp.approx.ftz.f32 %0, %1;" : "=f"(inv[1]) : "f"(b));
        fail |= (uint32_t)(go && !ok) << t;
        l0 = go ? 0.f : l0; l1 = go ? 0.f : l1;
        t += go;
      };
      const uint64_t m_first = 1ull | (1ull << (16 - ti)) | (1ull << 17) | (1ull << (18 + ti));
      const uint64_t m_diag = (3ull << (15 - ti)) | (3ull << (17 + ti));
      enum { F_FIRST = 1, F_DIAG = 2, F_LAST = 4, F_PFIRST = 8, F_PHALF = 16, F_STOP = 32 };
      auto kind = [&](int gn) {
        const uint32_t a = (uint32_t)((m_first << 1) >> gn), d = (uint32_t)((m_diag << 1) >> gn);
        return ((a >> 1) & 1) * F_FIRST | ((d >> 1) & 1) * F_DIAG | ((a >> 2) & 1) * F_LAST | (a & 1) * F_PFIRST |
               (w == 0 ? (d & 1) * F_PHALF | ((d >> 1) & 1) * F_STOP : 0) | (gn == 34 ? F_STOP : 0);
      };
      uint32_t kinds;
      {
        uint32_t qt[64];
#pragma unroll
        for (int i = 0; i < 16; i++) { const uint4 v = packed(i); qt[4 * i] = v.x; qt[4 * i + 1] = v.y; qt[4 * i + 2] = v.z; qt[4 * i + 3] = v.w; }
        fence_regs<64>(qt);
        sched_fence(q_st);
        float S[64];
        wg_fence();
        issue_s(S);
        bar_arrive(w ? 1 : 7, 256);
        bar_sync(6 + w, 256);
        sched_fence(q_st);
        TL(1, 0, tid == 128);
#pragma unroll
        for (int i = 0; i < 16; i++) park(piece(1), i, make_uint4(qt[4 * i], qt[4 * i + 1], qt[4 * i + 2], qt[4 * i + 3]));
        kinds = pinned(kind(lane + 3));
        sched_fence(q_st);
        wg_wait<0>();
        fence_regs<64>(S);
        release_k();
        TL(1, 1, tid == 128);
        const bool kok = mbar_try(B(B_KF + 1), 0);
        at_exp<0, 32>(S);
        sched_fence(q_st);
        at_exp<32, 64>(S); at_fin<0, 64>(S, P);
        if (UNLIKELY(!kok)) mbar_wait_c(B(B_KF + 1), 0);
        TL(1, 2, tid == 128);
      }
      uint32_t f = F_PFIRST, fn;
      auto shadow = [&]() {
        const bool vok = mbar_try(B(B_VF + ((g - 1) & 1)), ((g - 1) >> 1) & 1);
        at_sum(P, f & F_PHALF, l0, l1);
        fn = __shfl_sync(~0u, kinds, max(g - 2, 0));
        if (UNLIKELY(!vok)) mbar_wait_c(B(B_VF + ((g - 1) & 1)), ((g - 1) >> 1) & 1);
      };
      auto hand_over = [&]() { __syncwarp(); if (lane == 0 && !((fail >> (t - 1)) & 1)) mbar_arrive(B(B_PUB + 1 + t)); };
      auto exp_q = [&](float* S, auto kc, auto nc) {
        constexpr int k = decltype(kc)::value, n = decltype(nc)::value;
        asm volatile("{\n.reg .pred p;\nsetp.ne.b32 p, %5, 0;\n@p ldmatrix.sync.aligned.m8n8.x4.shared.b16 {%0,%1,%2,%3}, [%4];\n}"
                     : "+r"(Q[4 * k]), "+r"(Q[4 * k + 1]), "+r"(Q[4 * k + 2]), "+r"(Q[4 * k + 3])
                     : "r"(((q_ld + piece(t + 1)) ^ ((k & 1) << 5)) + (k >> 1) * 4096), "r"(f & F_LAST) : "memory");
        at_exp<n * k, n * k + n>(S);
      };
      g = 1; par = SLOT / 16;
#pragma unroll 1
      for (;;) {
        {
          TC(g, 0);
          bar_sync(1 + w, 256);
          fence_regs<32>(Q);
          float S[64];
          wg_fence();
          issue_s(S);
          sched_fence(q_st);
          TC(g, 1);
          shadow();
          fence_regs<64>(O); fence_regs<32>(P);
          issue_pv(f & F_PHALF, ~f & F_PFIRST);
          fence_regs<64>(S);
          TC(g, 2);
          release_k();
          at_exp<0, 8>(S);
          const bool first = f & F_FIRST;
          if (UNLIKELY(f & (F_FIRST | F_LAST))) {
            row_inv(first);
            at_mask(S + 32, (f & F_DIAG) ? wrow - 64 : 64, lane);
            unroll8([&](auto kc) { exp_q(S + 8, kc, std::integral_constant<int, AT_R1 / 8 - 1>{}); });
          } else {
            at_exp<8, AT_R1>(S);
          }
          pv_done();
          g = pinned(g + 1); par = pinned(par ^ (SLOT / 16)); f = fn;
          const bool kok = mbar_try(B(B_KF + (g & 1)), g < 34 ? (g >> 1) & 1 : 0);
          if (UNLIKELY(first)) {
            unroll8([&](auto ic) {
              constexpr int i = decltype(ic)::value, n = (64 - AT_R1) / 8;
              at_exp<AT_R1 + n * i, AT_R1 + n * i + n>(S);
              park(piece(t), i, scaled(i));
            });
            at_fin<0, 64>(S, P);
            hand_over();
          } else {
            at_exp<AT_R1, 64>(S); at_fin<0, 64>(S, P);
          }
          TC(g - 1, 5);
          if (!TCLK) TL(1, 1 + g, tid == 128);
          if (kok && !(f & F_STOP)) continue;
          if (UNLIKELY(!kok)) mbar_wait_c(B(B_KF + (g & 1)), (g >> 1) & 1);
          if (g == 34) break;
        }
#pragma unroll 1
        while (f & F_STOP) {
          TC(g, 0);
          bar_sync(1, 256);
          fence_regs<64>(O); fence_regs<32>(Q); fence_regs<32>(P);
          float S[32];
          const uint64_t dk = desc_add(dk0, par * 16);
          wg_fence();
          mma_n64_rs0(S, Q, dk);
#pragma unroll
          for (int k = 1; k < 8; k++) mma_n64_rs(S, Q + 4 * k, desc_add(dk, (k >> 2) * 16384 + (k & 3) * 32), 1);
          wg_commit();
          TC(g, 1);
          mbar_wait_c(B(B_VF + ((g - 1) & 1)), ((g - 1) >> 1) & 1);
          issue_pv(f & F_PHALF, ~f & F_PFIRST);
          fence_regs<32>(S);
          TC(g, 2);
          release_k();
          const bool first = f & F_FIRST;
          if (H_LATE == 2) pv_done();
          at_sum(P, f & F_PHALF, l0, l1);
          fn = __shfl_sync(~0u, kinds, g - 2);
          row_inv(first);
          if (H_LATE == 1) pv_done();
          if (H_LATE) sched_fence(q_st);
          at_mask(S, wrow, lane);
          unroll8([&](auto kc) { exp_q(S, kc, std::integral_constant<int, 4>{}); });
          if (!H_LATE) pv_done();
          g++; par ^= SLOT / 16; f = fn;
          at_fin<0, 32>(S, P);
          if (first) {
#pragma unroll
            for (int i = 0; i < 8; i++) park(piece(t), i, scaled(i));
            hand_over();
          }
          TC(g - 1, 5);
          if (!TCLK) TL(1, 1 + g, tid == 128);
          mbar_wait_c(B(B_KF + (g & 1)), (g >> 1) & 1);
        }
      }
      TCF();
      const bool wok = mbar_test(B(ffn ? B_WF : B_QP + 1), 0);
      grab(wf, 3 * SLOT, 0, 8);
      mbar_wait_c(B(B_VF + 1), 0);
      bar_sync(1 + w, 256);
      fence_regs<64>(O); fence_regs<32>(P);
      wg_fence();
#pragma unroll
      for (int k = 0; k < 8; k++) mma_n128_rs<1>(O, P + 4 * k, desc_add(dv0, 2 * SLOT + k * 2048), 1);
      wg_commit();
      if (w == 0) bar_arrive(2, 256);
      pin_order(__uint_as_float(wf[28] & wf[24]), pin);
      __syncwarp();
      if (wok) release2(B_WE);
      TL(3, 12 + 16 * w, (tid & 127) == 0);
      sched_fence(q_st);
      at_sum(P, false, l0, l1);
      row_inv(true);
      sched_fence(q_st);
      wg_wait<0>();
      fence_regs<64>(O); fence_regs<32>(P);
      release2(B_VE + 1);
      if (UNLIKELY(!wok || fail != 0)) {
#pragma unroll 1
        for (int tt = 0; tt < 4; tt++) {
          if (!((tt < 3 ? fail >> tt : fail != 0) & 1)) continue;
          slow_tile(O, P, l0, l1, wq, (((tt + 1) & 2) ? ti : 15 - ti) * 128 + wrow, hh + (tt & 2) * 8, lane, q_st);
          row_inv(false);
          if (tt < 3) {
#pragma unroll
            for (int i = 0; i < 8; i++) park(piece(tt + 1), i, scaled(i));
            publish(2 + tt);
          }
        }
        if (!wok) {
          mbar_wait_c(B(ffn ? B_WF : B_QP + 1), 0);
          grab(wf, 3 * SLOT, 0, 8);
          pin_order(__uint_as_float(wf[28] & wf[24]), pin);
          __syncwarp();
          release2(B_WE);
        }
      }
      TL(3, 13 + 16 * w, (tid & 127) == 0);
      issue3(0, 0, 0);
      TL(3, 14 + 16 * w, (tid & 127) == 0);
      TL(1, 36, tid == 128);
    }
    uint32_t hp[32];
    lane = lane_id();
    {
      int st = 1, prev = 0; uint32_t ph = 0;
      __nv_bfloat16* dst = g_qkv + (size_t)((15 - ti) * 128 + cw * 16 + (lane >> 2)) * NQ + (hh + 16) * 128 + (lane & 3) * 8;
      auto kblock = [&](auto between, int lim = 6) {
        issue3(st, ph, 1);
        between();
        wg_wait<1>();
        release2(B_EMPTY3 + prev);
        prev = st;
        if (++st == lim) { st = 0; ph ^= 1; }
      };
      kblock([&]() { TL(3, 15 + 16 * w, (tid & 127) == 0); });
      kblock([&]() { grab(wf + 32, 5 * SLOT, 0, 8); TL(3, 16 + 16 * w, (tid & 127) == 0); });
#pragma unroll 1
      for (int kb = 3; kb < 11; kb++) {
        kblock([&]() {
#pragma unroll
          for (int i = 0; i < 8; i++)
            if (kb == 3 + (i & 4) + (i & 1) * 2 + ((i >> 1) & 1)) *reinterpret_cast<uint4*>(dst + (i & 1) * 8 * NQ + (i >> 1) * 32) = scaled(i);
          TL(3, 14 + kb + 16 * w, (tid & 127) == 0);
          if (kb == 8) TL(2, 2, tid == 128);
        }, kb == 4 ? 5 : 6);
        if (kb == 4) release2(B_EMPTY3 + 5);
      }
      publish(5);
      kblock([&]() { mbar_wait_c(B(ffn ? B_WF2 : B_QP + 2), 0); grab(wf + 32, 5 * SLOT, 8, 16); });
#pragma unroll 1
      for (int kb = 12; kb < G_KB; kb++) {
        kblock([&]() { if ((kb & 7) == 0) TL(2, 1 + (kb >> 3), tid == 128); });
        if (kb == X_KB && lane == 0) mbar_arrive(B(B_XE));
      }
      kblock([&]() {
        mbar_wait_c(B(B_XF), 0);
#pragma unroll
        for (int i = 0; i < 8; i++)
          ldsm4(hp + 4 * i, sb + 6 * SLOT + w * 16384 + ((cw & 3) * 16 + (lane & 15)) * 128 + (i >> 2) * 8192 + ((((i & 3) * 2 + (lane >> 4)) ^ (lane & 7)) << 4));
      });
#pragma unroll 1
      for (int kb = G_KB + 1; kb < 64; kb++) {
        kblock([&]() { if ((kb & 7) == 0) TL(2, 1 + (kb >> 3), tid == 128); });
        if (kb == G_KB + 2 && lane == 0) mbar_arrive(B(B_XE));
      }
    }
    lane = lane_id();
    const int r0 = lane >> 2, q4 = lane & 3, ct = cw * 32 + lane;
    uint32_t tb[16];
    mbar_wait_c(B(B_WR), 0);
#pragma unroll
    for (int i = 0; i < 4; i++) ldsm4(tb + 4 * i, sb + OFF_MISC + 512 + (lane & 1) * 256 + (lane >> 3) * 16 + i * 64);
    mbar_wait_c(B(B_SET2), 0);
    float4* const psd = reinterpret_cast<float4*>(xr + XR_PS + cw * 16 + r0);
    const uint4* const pss = g_xr + (mt * 8 + (ct & 1) * 4) * XR_SIZE + XR_PS + (ct >> 1);
    sched_fence(stg);
    wg_wait<0>();
    fence_regs<64>(acc);
    TL(2, 10, tid == 128);
    {
      float d[2][4] = {}, qa[2][4] = {}, qb[2][4] = {};
#pragma unroll
      for (int j = 0; j < 16; j++) {
        hp[2 * j] = hadd2_bf(hp[2 * j], pack_bf16(acc[4 * j], acc[4 * j + 1]));
        hp[2 * j + 1] = hadd2_bf(hp[2 * j + 1], pack_bf16(acc[4 * j + 2], acc[4 * j + 3]));
        if (j & 1) {
          mma16816(d[(j >> 1) & 1], hp[2 * j - 2], hp[2 * j - 1], hp[2 * j], hp[2 * j + 1], tb[j - 1], tb[j]);
          mma16816(qa[(j >> 1) & 1], hp[2 * j - 2], hp[2 * j - 1], hp[2 * j], hp[2 * j + 1], hp[2 * j - 2], hp[2 * j]);
          mma16816(qb[(j >> 1) & 1], hp[2 * j - 2], hp[2 * j - 1], hp[2 * j], hp[2 * j + 1], hp[2 * j - 1], hp[2 * j + 1]);
        }
      }
      if (q4 == (r0 >> 1)) {
        __stcg(psd, make_float4(d[0][0] + d[1][0], (r0 & 1) ? qa[0][1] + qa[1][1] : qa[0][0] + qa[1][0], d[0][1] + d[1][1], 0.f));
        __stcg(psd + 8, make_float4(d[0][2] + d[1][2], (r0 & 1) ? qb[0][3] + qb[1][3] : qb[0][2] + qb[1][2], d[0][3] + d[1][3], 0.f));
      }
    }
    TL(2, 11, tid == 128);
    mbar_wait_c(B(B_EMPTY3 + 1), 0);
    stage_store_128(stg, lane, hp);
    if (ffn) mbar_wait_c(B(B_WF2), 1);
    grab(wf + 96, 6 * SLOT, 0, 8);
    const float wsum = *reinterpret_cast<const float*>(sp + OFF_MISC + 1024);
    __syncwarp();
    {
      uint4 ps[4];
      poll_chunks(ps, pss, XR_SIZE);
      TL(2, 12, tid == 128);
      auto F = [](uint32_t u) { return __uint_as_float(u); };
      float s1 = (F(ps[0].x) + F(ps[1].x)) + (F(ps[2].x) + F(ps[3].x)), s2 = (F(ps[0].y) + F(ps[1].y)) + (F(ps[2].y) + F(ps[3].y));
      float s3 = (F(ps[0].z) + F(ps[1].z)) + (F(ps[2].z) + F(ps[3].z));
      __syncwarp();
      s1 += __shfl_xor_sync(~0u, s1, 1); s2 += __shfl_xor_sync(~0u, s2, 1); s3 += __shfl_xor_sync(~0u, s3, 1);
      const float mean = s1 * (1.f / DM);
      float mb, inv;
      ln_round(mean, fmaxf(fmaf(s2, 1.f / DM, -mean * mean), 0.f), mb, inv);
      uint32_t u = pack_bf16((s3 - mb * wsum) * inv, 0.f);
      if (u == 0x8000u) u = 0;
      u = (u & 0x8000u) ? (~u & 0xFFFFu) : (u | 0x8000u);
      const uint32_t key = (u << 16) | (0x7FFFu - (mt * 128 + (ct >> 1)));
      const uint32_t nm2 = pack_bf16(-mb, -mb);
      const uint32_t c1 = __reduce_max_sync(~0u, key);
      const uint32_t c2 = __reduce_max_sync(~0u, key == c1 ? 0u : key);
      if (lane == 0) {
        __stcg(reinterpret_cast<uint2*>(xr + XR_KEY) + cw, make_uint2(c1, c2));
        mbar_arrive(B(B_OUT));
      }
      TL(2, 13, tid == 128);
      const int row = (0x7FFF - (((lane >> 4) ? c2 : c1) & 0x7FFF)) & 15;
      const uint32_t rn = __shfl_sync(~0u, nm2, row * 2);
      const float ri = __shfl_sync(~0u, inv, row * 2);
      uint32_t v[4];
#pragma unroll
      for (int i = 0; i < 4; i++)
        asm volatile("ld.shared.u32 %0, [%1];" : "=r"(v[i]) : "r"(stg + ((lane >> 3) & 1) * 8192 + row * 128 + ((((lane & 4) + i) ^ (row & 7)) << 4) + q4 * 4) : "memory");
      __stcg(xr + XR_CAND + cw * 64 + 32 + lane, make_uint4(ln_apply(v[0], rn, ri), ln_apply(v[1], rn, ri), ln_apply(v[2], rn, ri), ln_apply(v[3], rn, ri)));
      __stcg(xr + XR_CAND + cw * 64 + lane, make_uint4(v[0], v[1], v[2], v[3]));
      sched_fence(stg);
      const uint32_t na = __shfl_sync(~0u, nm2, r0 * 2), nb = __shfl_sync(~0u, nm2, r0 * 2 + 16);
      const float ia = __shfl_sync(~0u, inv, r0 * 2), ib = __shfl_sync(~0u, inv, r0 * 2 + 16);
#pragma unroll
      for (int i = 0; i < 32; i++) hp[i] = hadd2_bf(hp[i], ln_apply(hp[i], (i & 1) ? nb : na, (i & 1) ? ib : ia));
      __syncwarp();
      stage_store_128(stg, lane, hp);
      asm volatile("fence.proxy.async.shared::cta;" ::: "memory");
      publish(B_OUT3 - B_PUB);
    }
    uint32_t wd[16][4];
    sched_fence(stg);
    if (ffn) mbar_wait_c(B(B_FULL3 + 5 * w), 1 - w);
    auto load_wd = [&](int h) {
#pragma unroll
      for (int i = h; i < 16; i += 2)
        asm volatile("ldmatrix.sync.aligned.m8n8.x4.trans.shared.b16 {%0,%1,%2,%3}, [%4];"
                     : "=r"(wd[i][0]), "=r"(wd[i][1]), "=r"(wd[i][2]), "=r"(wd[i][3])
                     : "r"(sb + OFF_R3 + 5 * w * SLOT + (2 * (cw & 3) + (i >> 3)) * 4096 + (h * 16 + (lane & 7) + (lane >> 4) * 8) * 128 +
                           (((2 * ((i >> 1) & 3) + ((lane >> 3) & 1)) ^ (lane & 7)) << 4)) : "memory");
    };
    load_wd(0);
    __syncwarp();
    cluster_arrive();
    TL(2, 22, tid == 128);
    mbar_wait_c(B(B_OUT2), 0);
    const uint2 top = *reinterpret_cast<const uint2*>(sp + OFF_MISC);
    TL(2, 14, tid == 128);
    const int t0 = 0x7FFF - (top.x & 0x7FFF), t1 = 0x7FFF - (top.y & 0x7FFF);
    auto cand = [&](int second) {
      const int tk = second ? t1 : t0;
      return g_xr + (tk >> 7) * 8 * XR_SIZE + XR_CAND + ((tk >> 4) & 7) * 64 + ((second && (t0 >> 4) == (t1 >> 4)) ? 16 : 0);
    };
    if (ffn) {
      uint4 xb[2];
      poll_chunks(xb, cand(r0 & 1) + (r0 >> 1) * XR_SIZE + 32 + (cw >> 1) * 4 + q4, 4 * XR_SIZE);
      __syncwarp();
      TL(2, 15, tid == 128);
      float d[8][4] = {};
#pragma unroll
      for (int n = 0; n < 32; n++) {
        if (n == WD_AT) { sched_fence(stg); load_wd(1); }
        const int s = (n >> 4) * 4 + ((n >> 1) & 3), m = ((n >> 3) & 1) * 2 + (n & 1);
        const uint32_t* a = wf + 16 * s + 4 * m;
        mma16816(d[n & 7], a[0], a[1], a[2], a[3], (m & 2) ? xb[s >> 2].z : xb[s >> 2].x, (m & 2) ? xb[s >> 2].w : xb[s >> 2].y);
      }
      float v[8];
#pragma unroll
      for (int i = 0; i < 8; i++) {
        const float lo = (q4 & 1) ? d[2 + (i >> 2)][i & 3] : d[i >> 2][i & 3], hi = (q4 & 1) ? d[6 + (i >> 2)][i & 3] : d[4 + (i >> 2)][i & 3];
        v[i] = (q4 & 2) ? hi : lo;
      }
#pragma unroll
      for (int i = 0; i < 4; i++) v[i] = ((q4 & 2) ? v[i + 4] : v[i]) + __shfl_xor_sync(~0u, (q4 & 2) ? v[i] : v[i + 4], 2);
#pragma unroll
      for (int i = 0; i < 2; i++) v[i] = ((q4 & 1) ? v[i + 2] : v[i]) + __shfl_xor_sync(~0u, (q4 & 1) ? v[i] : v[i + 2], 1);
      float4* red = reinterpret_cast<float4*>(sp + SL_SCR * SLOT);
      reinterpret_cast<float2*>(red + cw * 16 + (q4 >> 1) * 8 + r0)[q4 & 1] = make_float2(v[0], v[1]);
      bar_sync(3, 256);
      TL(2, 16, tid == 128);
      const float4 z0 = red[lane], z1 = red[32 + lane], z2 = red[64 + lane], z3 = red[96 + lane];
      const uint32_t ub = pack_bf16((z0.x + z1.x) + (z2.x + z3.x), (z0.y + z1.y) + (z2.y + z3.y));
      const uint32_t gb = pack_bf16((z0.z + z1.z) + (z2.z + z3.z), (z0.w + z1.w) + (z2.w + z3.w));
      const float g0 = bf_lo(gb), g1 = bf_hi(gb);
      const uint32_t sg = pack_bf16(__fdividef(g0, 1.f + __expf(-g0)), __fdividef(g1, 1.f + __expf(-g1)));
      const uint32_t act = pack_bf16(bf_lo(sg) * bf_lo(ub), bf_hi(sg) * bf_hi(ub));
      const uint32_t pr = __byte_perm(act, __shfl_xor_sync(~0u, act, 1), (lane & 1) ? 0x3276 : 0x5410);
      const int src = q4 * 2 + (r0 & 1);
      const uint32_t a0 = __shfl_sync(~0u, pr, src), a1 = __shfl_sync(~0u, pr, src + 8), a2 = __shfl_sync(~0u, pr, src + 16), a3 = __shfl_sync(~0u, pr, src + 24);
      TL(2, 17, tid == 128);
      float y[8][4] = {};
#pragma unroll
      for (int i = 0; i < 8; i++) mma16816(y[i], wd[2 * i][0], wd[2 * i][1], wd[2 * i][2], wd[2 * i][3], a0, a1);
#pragma unroll
      for (int i = 0; i < 8; i++) mma16816(y[i], wd[2 * i + 1][0], wd[2 * i + 1][1], wd[2 * i + 1][2], wd[2 * i + 1][3], a2, a3);
      float2* yd = reinterpret_cast<float2*>(g_xr + (cw * 16 + 2 * q4) * XR_SIZE + XR_Y + fid * 4) + r0;
#pragma unroll
      for (int j = 0; j < 2; j++) {
        float v[4];
#pragma unroll
        for (int e = 0; e < 4; e++) {
          const float lo = (q4 & 1) ? y[4 * j + 1][e] : y[4 * j][e], hi = (q4 & 1) ? y[4 * j + 3][e] : y[4 * j + 2][e];
          v[e] = (q4 & 2) ? hi : lo;
        }
        __stcg(yd + j * 16 * XR_SIZE, make_float2(v[0], v[1]));
        __stcg(yd + j * 16 * XR_SIZE + 2 * XR_SIZE, make_float2(v[2], v[3]));
      }
    }
    TL(2, 18, tid == 128);
    if (rid == 127 && ct < C_NUM) g_cnt[ct] = 0;
    if (cw < 2) {
      const int tok = (lane >> 1) & 1, pair = cw * 2 + (lane & 1);
      idle(ffn ? YD : YD + 2000);
      uint4 z[7];
      poll_chunks(z, xr + XR_Y + (lane >> 1) * 4 + pair, 64);
      __syncwarp();
      TL(2, 19, tid == 128);
      mbar_wait_c(B(B_FIN), 0);
      const uint4 op = lds128(sb + OFF_MISC + 128 + (tok * 4 + pair) * 16);
      auto F = [](uint32_t u) { return __uint_as_float(u); };
      const float v0 = ((F(z[0].x) + F(z[1].x)) + (F(z[2].x) + F(z[3].x))) + ((F(z[4].x) + F(z[5].x)) + F(z[6].x));
      const float v1 = ((F(z[0].y) + F(z[1].y)) + (F(z[2].y) + F(z[3].y))) + ((F(z[4].y) + F(z[5].y)) + F(z[6].y));
      const float v2 = ((F(z[0].z) + F(z[1].z)) + (F(z[2].z) + F(z[3].z))) + ((F(z[4].z) + F(z[5].z)) + F(z[6].z));
      const float v3 = ((F(z[0].w) + F(z[1].w)) + (F(z[2].w) + F(z[3].w))) + ((F(z[4].w) + F(z[5].w)) + F(z[6].w));
      float ya = (tok ? v1 : v0) + __shfl_xor_sync(~0u, tok ? v0 : v1, 2), yb = (tok ? v3 : v2) + __shfl_xor_sync(~0u, tok ? v2 : v3, 2);
#pragma unroll
      for (int o = 4; o < 32; o <<= 1) { ya += __shfl_xor_sync(~0u, ya, o); yb += __shfl_xor_sync(~0u, yb, o); }
      const uint32_t yp = pack_bf16(ya, yb);
      if (lane < 4) reinterpret_cast<uint32_t*>(out + (size_t)(tok ? t1 : t0) * DM)[rid * 4 + pair] = hadd2_bf(op.x, hadd2_bf(op.y, pack_bf16(bf_lo(yp) * F(op.z), bf_hi(yp) * F(op.z))));
      TL(2, 21, tid == 128);
    }
    TL(2, 20, tid == 128);
    __syncwarp();
    cluster_wait();
    TL_DUMP();
  }
}

typedef CUresult (*EncodeFn)(CUtensorMap*, CUtensorMapDataType, cuuint32_t, void*, const cuuint64_t*, const cuuint64_t*, const cuuint32_t*,
                             const cuuint32_t*, CUtensorMapInterleave, CUtensorMapSwizzle, CUtensorMapL2promotion, CUtensorMapFloatOOBfill);
EncodeFn g_enc = nullptr;

void map2(CUtensorMap* m, const void* ptr, uint64_t rows, uint64_t cols, uint32_t bc, uint32_t br) {
  const CUtensorMapSwizzle sw = bc == 64 ? CU_TENSOR_MAP_SWIZZLE_128B : CU_TENSOR_MAP_SWIZZLE_64B;
  cuuint64_t gd[2] = {cols, rows}, gs[1] = {cols * 2};
  cuuint32_t bd[2] = {bc, br}, es[2] = {1, 1};
  g_enc(m, CU_TENSOR_MAP_DATA_TYPE_BFLOAT16, 2, (void*)ptr, gd, gs, bd, es, CU_TENSOR_MAP_INTERLEAVE_NONE, sw,
        CU_TENSOR_MAP_L2_PROMOTION_L2_128B, CU_TENSOR_MAP_FLOAT_OOB_FILL_NONE);
}
void map3(CUtensorMap* m, const void* ptr, uint64_t rows, uint64_t cols, uint32_t br, uint32_t bch, uint32_t bc = 64) {
  cuuint64_t gd[3] = {bc, rows, cols / bc}, gs[2] = {cols * 2, bc * 2};
  cuuint32_t bd[3] = {bc, br, bch}, es[3] = {1, 1, 1};
  g_enc(m, CU_TENSOR_MAP_DATA_TYPE_BFLOAT16, 3, (void*)ptr, gd, gs, bd, es, CU_TENSOR_MAP_INTERLEAVE_NONE, bc == 64 ? CU_TENSOR_MAP_SWIZZLE_128B : CU_TENSOR_MAP_SWIZZLE_64B,
        CU_TENSOR_MAP_L2_PROMOTION_L2_128B, CU_TENSOR_MAP_FLOAT_OOB_FILL_NONE);
}

}

extern "C" void kernel_launch(void* const* d_in, const int* in_sizes, int n_in, void* d_out, int out_size) {
  const __nv_bfloat16* x = (const __nv_bfloat16*)d_in[0];
  const __nv_bfloat16* ckv = (const __nv_bfloat16*)d_in[1];
  const __nv_bfloat16* wq = (const __nv_bfloat16*)d_in[2];
  const __nv_bfloat16* wk = (const __nv_bfloat16*)d_in[3];
  const __nv_bfloat16* wv = (const __nv_bfloat16*)d_in[4];
  const __nv_bfloat16* wo = (const __nv_bfloat16*)d_in[5];
  const __nv_bfloat16* w_r = (const __nv_bfloat16*)d_in[7];
  const __nv_bfloat16* wgate = (const __nv_bfloat16*)d_in[8];
  const __nv_bfloat16* wup = (const __nv_bfloat16*)d_in[9];
  const __nv_bfloat16* wdown = (const __nv_bfloat16*)d_in[10];
  __nv_bfloat16* out = (__nv_bfloat16*)d_out;

  if (!g_enc) {
    void* fn = nullptr;
    cudaDriverEntryPointQueryResult qr;
    cudaGetDriverEntryPoint("cuTensorMapEncodeTiled", &fn, cudaEnableDefault, &qr);
    g_enc = (EncodeFn)fn;
    cudaFuncSetAttribute(fused_kernel, cudaFuncAttributeMaxDynamicSharedMemorySize, SMEM_BYTES);
  }
  void *xn, *qkv;
  cudaGetSymbolAddress(&xn, g_xn);
  cudaGetSymbolAddress(&qkv, g_qkv);

  Params p;
  map2(&p.xn, xn, SEQ, DM, 64, 128);
  map2(&p.ckv, ckv, SEQ, DC, 64, 128);
  map3(&p.wq, wq, DM, NQ, 64, 2);
  map3(&p.wk, wk, DC, NQ, 64, 2);
  map3(&p.wv, wv, DC, NQ, 64, 2);
  map3(&p.kv, qkv, 3 * SEQ, NQ, 128, 1);
  map2(&p.ctx_ld, qkv, SEQ, NQ, 64, 128);
  map3(&p.ctx_st, qkv, SEQ, NQ, 64, ST_G, 32);
  map3(&p.wo, wo, NQ, DM, 64, 1);
  map3(&p.x, x, SEQ, DM, 64, 1);
  map3(&p.wd, wdown, FF, DM, 32, 8);
  map2(&p.out, out, SEQ, DM, 64, OUT_R);
  map2(&p.wg, wgate, DM, FF, 32, 128);
  map2(&p.wu, wup, DM, FF, 32, 128);
  fused_kernel<<<128, 384, SMEM_BYTES, cudaStreamPerThread>>>(x, wq, w_r, out, p);
}
```

```cpp
#include <cuda_runtime.h>
#include <cuda_bf16.h>
#include <cuda.h>
#include <stdint.h>
#include <type_traits>

#pragma nv_diag_suppress 549
namespace {

constexpr int SEQ = 2048, DM = 1024, NH = 32, HD = 128, DC = 512, NQ = NH * HD, FF = 3584;

__device__ __align__(1024) __nv_bfloat16 g_xn[SEQ * DM];
__device__ __align__(1024) __nv_bfloat16 g_qkv[3 * SEQ * NQ];
constexpr int XR_PS = 0;
constexpr int XR_KEY = 128;
constexpr int XR_FLAG = 132;
constexpr int XR_CAND = 136;
constexpr int XR_Y = 648;
constexpr int XR_SIZE = 1104;
__device__ __align__(1024) uint4 g_xr[128 * XR_SIZE];
constexpr int C_LN = 0, C_QKV = 16, C_CTX = 32, C_NUM = 64;
__device__ unsigned g_cnt[C_NUM];

#define TL(k, i, cond) do {} while (0)
#define TL_BYTES 0
#define TL_INIT() do {} while (0)
#define TL_DUMP() do {} while (0)
#define TC(g, i) do {} while (0)
#define TS(i) do {} while (0)
#undef TCLK
#define TCLK 0

__device__ __forceinline__ uint32_t s2u(const void* p) { return (uint32_t)__cvta_generic_to_shared(p); }
__device__ __forceinline__ void mbar_init(uint32_t b, uint32_t c) { asm volatile("mbarrier.init.shared::cta.b64 [%0], %1;" ::"r"(b), "r"(c) : "memory"); }
__device__ __forceinline__ void mbar_expect(uint32_t b, uint32_t bytes) { asm volatile("mbarrier.arrive.expect_tx.shared::cta.b64 _, [%0], %1;" ::"r"(b), "r"(bytes) : "memory"); }
__device__ __forceinline__ void mbar_arrive(uint32_t b) { asm volatile("mbarrier.arrive.shared::cta.b64 _, [%0];" ::"r"(b) : "memory"); }
__device__ __forceinline__ bool mbar_test(uint32_t b, uint32_t ph) {
  uint32_t ok;
  asm volatile("{\n.reg .pred p;\nmbarrier.test_wait.parity.shared::cta.b64 p, [%1], %2;\nselp.u32 %0, 1, 0, p;\n}" : "=r"(ok) : "r"(b), "r"(ph) : "memory");
  return ok;
}
__device__ __forceinline__ void mbar_wait(uint32_t b, uint32_t ph) {
  asm volatile(
      "{\n.reg .pred p;\n.reg .u32 n;\nmov.u32 n, 0;\n"
      "LW:\nmbarrier.try_wait.parity.shared::cta.b64 p, [%0], %1, 20000;\n@p bra LD;\n"
      "add.u32 n, n, 1;\nsetp.lt.u32 p, n, 0x40000;\n@p bra LW;\ntrap;\nLD:\n}" ::"r"(b), "r"(ph) : "memory");
}
__device__ __forceinline__ void mbar_wait_c(uint32_t b, uint32_t ph) {
  asm volatile(
      "{\n.reg .pred p;\n.reg .u32 n;\nmov.u32 n, 0;\n"
      "LW:\nmbarrier.try_wait.parity.shared::cta.b64 p, [%0], %1;\n@p bra LD;\n"
      "add.u32 n, n, 1;\nsetp.lt.u32 p, n, 0x100000;\n@p bra LW;\ntrap;\nLD:\n}" ::"r"(b), "r"(ph) : "memory");
}
__device__ __forceinline__ bool mbar_try(uint32_t b, uint32_t ph) {
  uint32_t ok;
  asm volatile("{\n.reg .pred p;\nmbarrier.try_wait.parity.shared::cta.b64 p, [%1], %2;\nselp.u32 %0, 1, 0, p;\n}" : "=r"(ok) : "r"(b), "r"(ph) : "memory");
  return ok;
}
#define UNLIKELY(c) __builtin_expect(!!(c), 0)
__device__ __forceinline__ uint32_t pinned(uint32_t v) { uint32_t r; asm volatile("mov.b32 %0, %1;" : "=r"(r) : "r"(v)); return r; }
__device__ __forceinline__ bool elect_one() {
  uint32_t p;
  asm volatile("{\n.reg .pred p;\nelect.sync _|p, 0xFFFFFFFF;\nselp.u32 %0, 1, 0, p;\n}" : "=r"(p));
  return p;
}
__device__ __forceinline__ int lane_id() { int r; asm volatile("mov.u32 %0, %%laneid;" : "=r"(r)); return r; }
template <bool SLEEP = false>
__device__ __forceinline__ void spin_until_ge(const unsigned* p, unsigned target) {
  asm volatile(
      "{\n.reg .pred p, q;\n.reg .u32 n, v;\nmov.u32 n, 0;\nsetp.ne.u32 q, %2, 0;\n"
      "LW:\nld.acquire.gpu.global.u32 v, [%0];\nsetp.ge.u32 p, v, %1;\n@p bra LD;\n@q nanosleep.u32 200;\n"
      "add.u32 n, n, 1;\nsetp.lt.u32 p, n, 0x400000;\n@p bra LW;\ntrap;\nLD:\n}" ::"l"(p), "r"(target), "n"((int)SLEEP) : "memory");
}
template <int N>
__device__ __forceinline__ void poll_chunks(uint4 (&v)[N], const uint4* p, int stride) {
  uint32_t m[N];
#pragma unroll
  for (int i = 0; i < N; i++) { m[i] = ~0u; v[i] = make_uint4(0, 0, 0, 0); }
#pragma unroll 1
  for (int n = 0; n < 0x400000; n++) {
    uint32_t a = 0;
#pragma unroll
    for (int i = 0; i < N; i++)
      asm volatile("{\n.reg .pred p;\nsetp.eq.u32 p, %5, 0xFFFFFFFF;\n@p ld.relaxed.gpu.global.v4.u32 {%0,%1,%2,%3}, [%4];\n}"
                   : "+r"(v[i].x), "+r"(v[i].y), "+r"(v[i].z), "+r"(v[i].w) : "l"(p + i * stride), "r"(m[i]) : "memory");
#pragma unroll
    for (int i = 0; i < N; i++) { m[i] = max(max(v[i].x, v[i].y), max(v[i].z, v[i].w)); a = max(a, m[i]); }
    if (__all_sync(~0u, a != 0xFFFFFFFFu)) break;
  }
}
__device__ __forceinline__ void fence_async_all() { asm volatile("fence.proxy.async;" ::: "memory"); }
__device__ __forceinline__ void bar_sync(int id, int n) { asm volatile("bar.sync %0, %1;" ::"r"(id), "r"(n) : "memory"); }
__device__ __forceinline__ void bar_arrive(int id, int n) { asm volatile("bar.arrive %0, %1;" ::"r"(id), "r"(n) : "memory"); }
__device__ __forceinline__ void cluster_arrive() { asm volatile("barrier.cluster.arrive.relaxed.aligned;" ::: "memory"); }
__device__ __forceinline__ void cluster_wait() { asm volatile("barrier.cluster.wait.acquire.aligned;" ::: "memory"); }
__device__ __forceinline__ void fence_gpu() { asm volatile("fence.acq_rel.gpu;" ::: "memory"); }
__device__ __forceinline__ void red_add(unsigned* p, unsigned v) { asm volatile("red.relaxed.gpu.global.add.u32 [%0], %1;" ::"l"(p), "r"(v) : "memory"); }
__device__ __forceinline__ void prefetch_tm(const CUtensorMap* m) { asm volatile("prefetch.tensormap [%0];" ::"l"(m) : "memory"); }

constexpr uint64_t EV_N = 0x1000000000000000ull, EV_F = 0x12F0000000000000ull;
__device__ __forceinline__ void tma_ld2(uint32_t dst, const CUtensorMap* m, uint32_t bar, int c0, int c1, bool ef = false) {
  asm volatile("cp.async.bulk.tensor.2d.shared::cta.global.mbarrier::complete_tx::bytes.L2::cache_hint [%0], [%1, {%3,%4}], [%2], %5;" ::"r"(dst), "l"(m), "r"(bar), "r"(c0), "r"(c1), "l"(ef ? EV_F : EV_N) : "memory");
}
__device__ __forceinline__ void tma_ld3(uint32_t dst, const CUtensorMap* m, uint32_t bar, int c0, int c1, int c2, bool ef = false) {
  asm volatile("cp.async.bulk.tensor.3d.shared::cta.global.mbarrier::complete_tx::bytes.L2::cache_hint [%0], [%1, {%3,%4,%5}], [%2], %6;" ::"r"(dst), "l"(m), "r"(bar), "r"(c0), "r"(c1), "r"(c2), "l"(ef ? EV_F : EV_N) : "memory");
}
__device__ __forceinline__ void tma_ld3_mc(uint32_t dst, const CUtensorMap* m, uint32_t bar, int c0, int c1, int c2, uint16_t mask, bool ef = false) {
  asm volatile("cp.async.bulk.tensor.3d.shared::cluster.global.mbarrier::complete_tx::bytes.multicast::cluster.L2::cache_hint [%0], [%1, {%3,%4,%5}], [%2], %6, %7;" ::"r"(dst), "l"(m), "r"(bar), "r"(c0), "r"(c1), "r"(c2), "h"(mask), "l"(ef ? EV_F : EV_N) : "memory");
}
__device__ __forceinline__ void tma_pf3(const CUtensorMap* m, int c0, int c1, int c2) {
  asm volatile("cp.async.bulk.prefetch.tensor.3d.L2.global [%0, {%1,%2,%3}];" ::"l"(m), "r"(c0), "r"(c1), "r"(c2) : "memory");
}
__device__ __forceinline__ void l2_prefetch(const void* p, uint32_t bytes) { asm volatile("cp.async.bulk.prefetch.L2.global [%0], %1;" ::"l"(p), "r"(bytes) : "memory"); }

__device__ __forceinline__ void wg_fence() { asm volatile("wgmma.fence.sync.aligned;" ::: "memory"); }
__device__ __forceinline__ void wg_commit() { asm volatile("wgmma.commit_group.sync.aligned;" ::: "memory"); }
template <int N> __device__ __forceinline__ void wg_wait() { asm volatile("wgmma.wait_group.sync.aligned %0;" ::"n"(N) : "memory"); }
template <int N> __device__ __forceinline__ void reg_alloc() { asm volatile("setmaxnreg.inc.sync.aligned.u32 %0;" ::"n"(N)); }
template <int N> __device__ __forceinline__ void reg_dealloc() { asm volatile("setmaxnreg.dec.sync.aligned.u32 %0;" ::"n"(N)); }
template <int N> __device__ __forceinline__ void fence_regs(float* d) {
#pragma unroll
  for (int i = 0; i < N; i++) asm volatile("" : "+f"(d[i])::"memory");
}
template <int N> __device__ __forceinline__ void fence_regs(uint32_t* d) {
#pragma unroll
  for (int i = 0; i < N; i++) asm volatile("" : "+r"(d[i])::"memory");
}

__device__ __forceinline__ uint64_t mk_desc(uint32_t addr, uint32_t lbo, uint32_t sbo, uint32_t swz) {
  uint32_t lo = ((addr & 0x3FFFF) >> 4) | ((lbo >> 4) << 16);
  uint32_t hi = (sbo >> 4) | (swz << 30);
  return ((uint64_t)hi << 32) | lo;
}
__device__ __forceinline__ uint64_t desc_add(uint64_t d, uint32_t bytes) {
  uint32_t lo = (uint32_t)d + (bytes >> 4);
  return (d & 0xFFFFFFFF00000000ull) | lo;
}

#define R8(b) "+f"(d[b + 0]), "+f"(d[b + 1]), "+f"(d[b + 2]), "+f"(d[b + 3]), "+f"(d[b + 4]), "+f"(d[b + 5]), "+f"(d[b + 6]), "+f"(d[b + 7])
#define REGS32 "%0,%1,%2,%3,%4,%5,%6,%7,%8,%9,%10,%11,%12,%13,%14,%15,%16,%17,%18,%19,%20,%21,%22,%23,%24,%25,%26,%27,%28,%29,%30,%31"
#define REGS64 REGS32 ",%32,%33,%34,%35,%36,%37,%38,%39,%40,%41,%42,%43,%44,%45,%46,%47,%48,%49,%50,%51,%52,%53,%54,%55,%56,%57,%58,%59,%60,%61,%62,%63"
#define REGS128 REGS64 ",%64,%65,%66,%67,%68,%69,%70,%71,%72,%73,%74,%75,%76,%77,%78,%79,%80,%81,%82,%83,%84,%85,%86,%87,%88,%89,%90,%91,%92,%93,%94,%95," \
               "%96,%97,%98,%99,%100,%101,%102,%103,%104,%105,%106,%107,%108,%109,%110,%111,%112,%113,%114,%115,%116,%117,%118,%119,%120,%121,%122,%123,%124,%125,%126,%127"

template <int TB>
__device__ __forceinline__ void mma_n256_ss(float (&d)[128], uint64_t a, uint64_t b, int acc) {
  asm volatile("{\n.reg .pred p;\nsetp.ne.b32 p, %130, 0;\n"
               "wgmma.mma_async.sync.aligned.m64n256k16.f32.bf16.bf16 {" REGS128 "}, %128, %129, p, 1, 1, 0, %131;\n}\n"
               : R8(0), R8(8), R8(16), R8(24), R8(32), R8(40), R8(48), R8(56), R8(64), R8(72), R8(80), R8(88), R8(96), R8(104), R8(112), R8(120)
               : "l"(a), "l"(b), "r"(acc), "n"(TB));
}
template <int TB>
__device__ __forceinline__ void mma_n128_ss(float* d, uint64_t a, uint64_t b, int acc) {
  asm volatile("{\n.reg .pred p;\nsetp.ne.b32 p, %66, 0;\n"
               "wgmma.mma_async.sync.aligned.m64n128k16.f32.bf16.bf16 {" REGS64 "}, %64, %65, p, 1, 1, 0, %67;\n}\n"
               : R8(0), R8(8), R8(16), R8(24), R8(32), R8(40), R8(48), R8(56)
               : "l"(a), "l"(b), "r"(acc), "n"(TB));
}
template <int TB>
__device__ __forceinline__ void mma_n128_rs(float* d, const uint32_t* a, uint64_t b, int acc) {
  asm volatile("{\n.reg .pred p;\nsetp.ne.b32 p, %69, 0;\n"
               "wgmma.mma_async.sync.aligned.m64n128k16.f32.bf16.bf16 {" REGS64 "}, {%64,%65,%66,%67}, %68, p, 1, 1, %70;\n}\n"
               : R8(0), R8(8), R8(16), R8(24), R8(32), R8(40), R8(48), R8(56)
               : "r"(a[0]), "r"(a[1]), "r"(a[2]), "r"(a[3]), "l"(b), "r"(acc), "n"(TB));
}
__device__ __forceinline__ void mma_n64_rs(float* d, const uint32_t* a, uint64_t b, int acc) {
  asm volatile("{\n.reg .pred p;\nsetp.ne.b32 p, %37, 0;\n"
               "wgmma.mma_async.sync.aligned.m64n64k16.f32.bf16.bf16 {" REGS32 "}, {%32,%33,%34,%35}, %36, p, 1, 1, 0;\n}\n"
               : R8(0), R8(8), R8(16), R8(24)
               : "r"(a[0]), "r"(a[1]), "r"(a[2]), "r"(a[3]), "l"(b), "r"(acc));
}
#define W8(b) "=f"(d[b + 0]), "=f"(d[b + 1]), "=f"(d[b + 2]), "=f"(d[b + 3]), "=f"(d[b + 4]), "=f"(d[b + 5]), "=f"(d[b + 6]), "=f"(d[b + 7])
__device__ __forceinline__ void mma_n128_rs0(float* d, const uint32_t* a, uint64_t b) {
  asm volatile("wgmma.mma_async.sync.aligned.m64n128k16.f32.bf16.bf16 {" REGS64 "}, {%64,%65,%66,%67}, %68, 0, 1, 1, 0;\n"
               : W8(0), W8(8), W8(16), W8(24), W8(32), W8(40), W8(48), W8(56)
               : "r"(a[0]), "r"(a[1]), "r"(a[2]), "r"(a[3]), "l"(b));
}
__device__ __forceinline__ void mma_n64_rs0(float* d, const uint32_t* a, uint64_t b) {
  asm volatile("wgmma.mma_async.sync.aligned.m64n64k16.f32.bf16.bf16 {" REGS32 "}, {%32,%33,%34,%35}, %36, 0, 1, 1, 0;\n"
               : W8(0), W8(8), W8(16), W8(24)
               : "r"(a[0]), "r"(a[1]), "r"(a[2]), "r"(a[3]), "l"(b));
}
__device__ __forceinline__ uint32_t pack_bf16(float lo, float hi) {
  uint32_t r;
  asm("cvt.rn.bf16x2.f32 %0, %1, %2;" : "=r"(r) : "f"(hi), "f"(lo));
  return r;
}
__device__ __forceinline__ float bf_lo(uint32_t v) { return __uint_as_float(v << 16); }
__device__ __forceinline__ float bf_hi(uint32_t v) { return __uint_as_float(v & 0xFFFF0000u); }
__device__ __forceinline__ float bf_round(float v) { return bf_lo(pack_bf16(v, v)); }
__device__ __forceinline__ void stsm4(uint32_t addr, uint32_t r0, uint32_t r1, uint32_t r2, uint32_t r3) {
  asm volatile("stmatrix.sync.aligned.m8n8.x4.shared.b16 [%0], {%1,%2,%3,%4};" ::"r"(addr), "r"(r0), "r"(r1), "r"(r2), "r"(r3) : "memory");
}
__device__ __forceinline__ uint4 lds128(uint32_t addr) {
  uint4 v;
  asm volatile("ld.shared.v4.u32 {%0,%1,%2,%3}, [%4];" : "=r"(v.x), "=r"(v.y), "=r"(v.z), "=r"(v.w) : "r"(addr));
  return v;
}
__device__ __forceinline__ float ex2(float x) {
  float y;
  asm("ex2.approx.ftz.f32 %0, %1;" : "=f"(y) : "f"(x));
  return y;
}
__device__ __forceinline__ void pin_order(float v, uint32_t dummy) {
  asm volatile("{\n.reg .pred p;\nsetp.eq.b32 p, %0, 0xFFFFFFFF;\n@p st.shared.b32 [%1], %0;\n}" ::"r"(__float_as_uint(v)), "r"(dummy) : "memory");
}
__device__ __forceinline__ void sched_fence(uint32_t dummy) {
  asm volatile("{\n.reg .pred p;\n.reg .u32 c;\nsetp.eq.b32 p, %0, 0xFFFFFFFF;\nmov.u32 c, %%clock;\n@p st.shared.b32 [%0], c;\n}" ::"r"(dummy) : "memory");
}
__device__ __forceinline__ void idle(int n) {
  asm volatile("{\n.reg .pred p;\n.reg .u32 a, b;\nmov.u32 a, %%clock;\nLI:\nmov.u32 b, %%clock;\nsub.u32 b, b, a;\nsetp.lt.u32 p, b, %0;\n@p bra LI;\n}" ::"r"(n) : "memory");
}
__device__ __forceinline__ void stage_store_128(uint32_t base, int lane, const uint32_t* pk) {
  const int row = (lane & 7) + ((lane >> 3) & 1) * 8;
  const uint32_t rb = base + row * 128;
  const int hi = lane >> 4;
#pragma unroll
  for (int j = 0; j < 8; j++) {
    const int chunk = 2 * j + hi;
    const uint32_t a = rb + (j >> 2) * 8192 + (((chunk & 7) ^ (lane & 7)) << 4);
    stsm4(a, pk[4 * j + 0], pk[4 * j + 1], pk[4 * j + 2], pk[4 * j + 3]);
  }
}
__device__ __forceinline__ void ln_round(float mean, float var, float& m_bf, float& inv_s) {
  const uint32_t mv = pack_bf16(mean, var);
  m_bf = bf_lo(mv);
  float sq, rc;
  asm("sqrt.approx.f32 %0, %1;" : "=f"(sq) : "f"(bf_round(bf_hi(mv) + 1e-5f)));
  asm("rcp.approx.ftz.f32 %0, %1;" : "=f"(rc) : "f"(bf_round(sq)));
  inv_s = rc;
}
__device__ __forceinline__ uint32_t hadd2_bf(uint32_t a, uint32_t b) {
  uint32_t r;
  asm("add.rn.bf16x2 %0, %1, %2;" : "=r"(r) : "r"(a), "r"(b));
  return r;
}
__device__ __forceinline__ uint32_t ln_apply(uint32_t h, uint32_t nm2, float inv_s) {
  const uint32_t d = hadd2_bf(h, nm2);
  return pack_bf16(bf_lo(d) * inv_s, bf_hi(d) * inv_s);
}
__device__ __forceinline__ void ldsm4(uint32_t* r, uint32_t addr) {
  asm volatile("ldmatrix.sync.aligned.m8n8.x4.shared.b16 {%0,%1,%2,%3}, [%4];" : "=r"(r[0]), "=r"(r[1]), "=r"(r[2]), "=r"(r[3]) : "r"(addr) : "memory");
}
__device__ __forceinline__ void mma16816(float* d, uint32_t a0, uint32_t a1, uint32_t a2, uint32_t a3, uint32_t b0, uint32_t b1) {
  asm volatile("mma.sync.aligned.m16n8k16.row.col.f32.bf16.bf16.f32 {%0,%1,%2,%3}, {%4,%5,%6,%7}, {%8,%9}, {%0,%1,%2,%3};"
               : "+f"(d[0]), "+f"(d[1]), "+f"(d[2]), "+f"(d[3]) : "r"(a0), "r"(a1), "r"(a2), "r"(a3), "r"(b0), "r"(b1));
}

template <class F>
__device__ __forceinline__ void unroll8(F f) {
  f(std::integral_constant<int, 0>{}); f(std::integral_constant<int, 1>{}); f(std::integral_constant<int, 2>{}); f(std::integral_constant<int, 3>{});
  f(std::integral_constant<int, 4>{}); f(std::integral_constant<int, 5>{}); f(std::integral_constant<int, 6>{}); f(std::integral_constant<int, 7>{});
}

constexpr float AT_C = 0.08838834764831845f * 1.4426950408889634f;
constexpr float AT_LO = 0x1p-40f, AT_HI = 0x1p40f;
constexpr int AT_R1 = 48;
template <int I0, int I1>
__device__ __forceinline__ void at_exp(float* S) {
#pragma unroll
  for (int i = I0; i < I1; i++) asm volatile("ex2.approx.ftz.f32 %0, %0;" : "+f"(S[i]));
}
template <int I0, int I1>
__device__ __forceinline__ void at_fin(const float* S, uint32_t* P) {
#pragma unroll
  for (int i = I0; i < I1; i += 4) {
    P[i / 2] = pack_bf16(S[i], S[i + 1]); P[i / 2 + 1] = pack_bf16(S[i + 2], S[i + 3]);
  }
}
__device__ __forceinline__ void at_sum(const uint32_t* P, bool half, float& l0, float& l1) {
  uint32_t u[4];
#pragma unroll
  for (int r = 0; r < 4; r++) {
    const uint32_t* q = P + (r >> 1) * 16 + (r & 1);
    u[r] = hadd2_bf(hadd2_bf(hadd2_bf(q[0], q[2]), hadd2_bf(q[4], q[6])), hadd2_bf(hadd2_bf(q[8], q[10]), hadd2_bf(q[12], q[14])));
  }
  u[0] = hadd2_bf(u[0], half ? 0u : u[2]);
  u[1] = hadd2_bf(u[1], half ? 0u : u[3]);
  l0 += bf_lo(u[0]) + bf_hi(u[0]);
  l1 += bf_lo(u[1]) + bf_hi(u[1]);
}
template <int j>
__device__ __forceinline__ void at_mask1(float* S, int d) {
  float dummy0 = 0.f, dummy1 = 0.f;
  float& lo0 = j < 7 ? S[4 * (j < 7 ? j + 1 : j) + 2] : dummy0;
  float& lo1 = j < 7 ? S[4 * (j < 7 ? j + 1 : j) + 3] : dummy1;
  asm("{\n.reg .pred p, q;\nsetp.lt.s32 p, %4, %5;\nsetp.le.s32 q, %4, %5;\n"
      "@p add.f32 %0, %0, 0fFF800000;\n@q add.f32 %1, %1, 0fFF800000;\n@p add.f32 %2, %2, 0fFF800000;\n@q add.f32 %3, %3, 0fFF800000;\n}"
      : "+f"(S[4 * j]), "+f"(S[4 * j + 1]), "+f"(lo0), "+f"(lo1) : "r"(d), "r"(8 * j));
}
__device__ __forceinline__ void at_mask(float* S, int r, int lane) {
  unroll8([&](auto jc) { at_mask1<decltype(jc)::value>(S, r + (lane >> 2) - (lane & 3) * 2); });
}
__device__ __forceinline__ uint32_t ldg32(const __nv_bfloat16* p) { return __ldcg(reinterpret_cast<const uint32_t*>(p)); }
__device__ __forceinline__ uint32_t ldg16x2(const __nv_bfloat16* p, int stride) {
  return (uint32_t)__ldcg(reinterpret_cast<const unsigned short*>(p)) | ((uint32_t)__ldcg(reinterpret_cast<const unsigned short*>(p + stride)) << 16);
}
__device__ __forceinline__ void slow_tile(float* O, uint32_t* Q, float& l0, float& l1, const __nv_bfloat16* wq, int row0, int head, int lane, uint32_t dummy) {
  const int r = lane >> 2, q = lane & 3;
#pragma unroll
  for (int i = 0; i < 64; i++) O[i] = 0.f;
  {
    const __nv_bfloat16* xa = g_xn + (size_t)(row0 + r) * DM + 2 * q;
    const __nv_bfloat16* wb = wq + (size_t)(2 * q) * NQ + head * HD + (r >> 1) * 8 + (r & 1);
#pragma unroll 1
    for (int k = 0; k < DM; k += 16) {
      const uint32_t a0 = ldg32(xa + k), a1 = ldg32(xa + k + 8 * DM), a2 = ldg32(xa + k + 8), a3 = ldg32(xa + k + 8 * DM + 8);
#pragma unroll
      for (int j = 0; j < 16; j++) {
        const __nv_bfloat16* wp = wb + (size_t)k * NQ + (j >> 2) * 32 + (j & 3) * 2;
        mma16816(O + 4 * j, a0, a1, a2, a3, ldg16x2(wp, NQ), ldg16x2(wp + 8 * NQ, NQ));
        if (j == 7) sched_fence(dummy);
      }
    }
  }
#pragma unroll
  for (int i = 0; i < 32; i++) Q[i] = pack_bf16(O[2 * i], O[2 * i + 1]);
#pragma unroll
  for (int i = 0; i < 64; i++) O[i] = 0.f;
  float m0 = -INFINITY, m1 = -INFINITY;
  l0 = l1 = 0.f;
#pragma unroll 1
  for (int kv = 0; kv <= row0; kv += 16) {
    float s[8] = {0.f, 0.f, 0.f, 0.f, 0.f, 0.f, 0.f, 0.f};
    const __nv_bfloat16* kp = g_qkv + (size_t)(SEQ + kv + r) * NQ + head * HD + 2 * q;
#pragma unroll
    for (int k = 0; k < 8; k++) {
      mma16816(s, Q[4 * k], Q[4 * k + 1], Q[4 * k + 2], Q[4 * k + 3], ldg32(kp + 16 * k), ldg32(kp + 16 * k + 8));
      mma16816(s + 4, Q[4 * k], Q[4 * k + 1], Q[4 * k + 2], Q[4 * k + 3], ldg32(kp + 8 * NQ + 16 * k), ldg32(kp + 8 * NQ + 16 * k + 8));
    }
#pragma unroll
    for (int i = 0; i < 8; i++)
      if (kv + (i >> 2) * 8 + 2 * q + (i & 1) > row0 + r + (i & 2) * 4) s[i] = -INFINITY;
    float a = fmaxf(fmaxf(fmaxf(s[0], s[1]), fmaxf(s[4], s[5])), m0), b = fmaxf(fmaxf(fmaxf(s[2], s[3]), fmaxf(s[6], s[7])), m1);
    a = fmaxf(a, __shfl_xor_sync(~0u, a, 1)); b = fmaxf(b, __shfl_xor_sync(~0u, b, 1));
    a = fmaxf(a, __shfl_xor_sync(~0u, a, 2)); b = fmaxf(b, __shfl_xor_sync(~0u, b, 2));
    const float c0 = ex2(m0 - a), c1 = ex2(m1 - b);
    m0 = a; m1 = b;
#pragma unroll
    for (int i = 0; i < 8; i++) s[i] = ex2(s[i] - ((i & 2) ? b : a));
    l0 = l0 * c0 + (s[0] + s[1]) + (s[4] + s[5]);
    l1 = l1 * c1 + (s[2] + s[3]) + (s[6] + s[7]);
    sched_fence(dummy);
    const uint32_t p0 = pack_bf16(s[0], s[1]), p1 = pack_bf16(s[2], s[3]), p2 = pack_bf16(s[4], s[5]), p3 = pack_bf16(s[6], s[7]);
    const __nv_bfloat16* vp = g_qkv + (size_t)(2 * SEQ + kv + 2 * q) * NQ + head * HD + r;
#pragma unroll
    for (int j = 0; j < 16; j++) {
      O[4 * j] *= c0; O[4 * j + 1] *= c0; O[4 * j + 2] *= c1; O[4 * j + 3] *= c1;
      mma16816(O + 4 * j, p0, p1, p2, p3, ldg16x2(vp + 8 * j, NQ), ldg16x2(vp + 8 * NQ + 8 * j, NQ));
      if (j == 7) sched_fence(dummy);
    }
  }
}

constexpr int P1_STAGE = 49152;
constexpr int SLOT = 32768;
constexpr int OFF_LN = 6 * SLOT, OFF_R3 = 0;
constexpr int OFF_BAR = 229376;
constexpr int OFF_MISC = OFF_BAR + 8 * 58;
constexpr int SMEM_BYTES = OFF_MISC + 2080 + TL_BYTES;
enum : int {
  B_FULL1 = 0, B_KF = 4, B_VF = 6, B_FULL3 = 8, B_XF = 14, B_LN = 15, B_DEP = 16, B_OUT2 = 22, B_FIN = 23, B_SET2 = 25, B_QP = 26, B_WF2 = 29,
  B_WF = 30, B_WR = 31,
  B_LND = 32,
  B_XE = 33, B_PUB = 34, B_OUT = 40, B_OUT3 = 41,
  B_EMPTY1 = 42, B_KE = 46, B_VE = 48, B_EMPTY3 = 50, B_WE = 56, B_NUM = 57
};
constexpr int OFF_STG = SLOT, SL_SCR = 2;
constexpr int PRE = 3;
constexpr int LN_PF = 4, LN_PFN = 2, LN_LD = 9;
constexpr int WQ_0 = 18, WQ_D = 4;
constexpr int W_G0 = 22;
constexpr int X_KB = 20, G_KB = 35;
constexpr int SL_NS = 600, SET_NS = 50;
constexpr int OUT_CLK = 500, Y_CLK = 700;
struct Params {
  CUtensorMap xn, ckv, wq, wk, wv, kv, ctx_ld, ctx_st, wo, x, wd, wg, wu, out;
};

__global__ void __cluster_dims__(2, 1, 1) __launch_bounds__(384, 1)
fused_kernel(const __nv_bfloat16* __restrict__ x, const __nv_bfloat16* __restrict__ wq, const __nv_bfloat16* __restrict__ w_r,
             __nv_bfloat16* __restrict__ out, const __grid_constant__ Params p) {
  extern __shared__ __align__(1024) uint8_t sp[];
  const uint32_t sb = s2u(sp);
  const uint32_t bar = sb + OFF_BAR;
  auto B = [&](int i) { return bar + 8 * i; };
  const int tid = threadIdx.x, warp = __shfl_sync(~0u, tid >> 5, 0), wg = warp >> 2, lane = tid & 31;
  const int cta = blockIdx.x, rank = cta & 1, cl = cta >> 1;
  const int mp = cl < 4 ? 1 : (cl < 36 ? (cl & 7) : (0x3207654 >> (4 * ((cl - 36) % 7))) & 7);
  const int gq = cl < 4 ? 4 + cl : (cl < 36 ? (cl - 4) >> 3 : 4 + (cl - 36) / 7);
  const int mt = 2 * mp + rank;
  const int ti = (gq & 3) * 2 + rank, hh = mp * 2 + (gq >> 2);
  const int rid = mt * 8 + gq;
  const int fid = mt * 7 + gq;
  const bool ffn = gq < 7;
  uint4* const xr = g_xr + rid * XR_SIZE;
  TL_INIT();
  TL(0, 0, tid == 128);
  if (warp == 0) {
    if (elect_one()) {
#pragma unroll
      for (int kb = 0; kb < PRE; kb++) mbar_init(B(B_FULL1 + kb), 1);
      asm volatile("fence.mbarrier_init.release.cluster;" ::: "memory");
    }
    __syncwarp();
    cluster_arrive();
    if (elect_one()) {
#pragma unroll
      for (int kb = 0; kb < PRE; kb++) {
        mbar_expect(B(B_FULL1 + kb), P1_STAGE);
        tma_ld2(sb + kb * P1_STAGE, &p.ckv, B(B_FULL1 + kb), kb * 64, mt * 128);
        tma_ld3(sb + kb * P1_STAGE + 16384 + rank * 16384, &p.wk, B(B_FULL1 + kb), 0, kb * 64, gq * 4 + rank * 2);
        tma_ld3(sb + kb * P1_STAGE + 32768 - rank * 16384, &p.wk, B(B_FULL1 + kb), 0, kb * 64, gq * 4 + 2 - rank * 2);
      }
    }
  } else if (elect_one()) {
#pragma unroll 1
    for (int i = PRE + warp - 1; i < B_NUM; i += 11)
      mbar_init(B(i), i >= B_EMPTY1 ? 16 : (i >= B_XE ? 8 : (i == B_LND ? 3 : (i >= B_WF ? 2 : 1))));
    asm volatile("fence.mbarrier_init.release.cluster;" ::: "memory");
  }
  __syncwarp();
  if (warp) cluster_arrive();
  if (wg == 0) {
    reg_dealloc<40>();
    if (warp == 1 && elect_one()) {
      if (mt >= 2 * PRE) tma_pf3(&p.wk, 0, mp * 64, gq * 4 + rank * 2);
      if (gq >= PRE) asm volatile("cp.async.bulk.prefetch.tensor.2d.L2.global [%0, {%1,%2}];" ::"l"(&p.ckv), "r"(gq * 64), "r"(mt * 128) : "memory");
    } else if (warp == 2 && elect_one()) {
      prefetch_tm(&p.wv); prefetch_tm(&p.wq); prefetch_tm(&p.xn);
    }
    __syncwarp();
    cluster_wait();
    if (warp == 0) {
      int st = 0; uint32_t ph = 1;
#pragma unroll 1
      for (int t = 0; t < 6; t++) {
        const CUtensorMap* ma = t >= 4 ? &p.xn : &p.ckv;
        const CUtensorMap* mb = t >= 4 ? &p.wq : ((t & 1) ? &p.wv : &p.wk);
        const int nk = t >= 4 ? 16 : 8;
        const int row = (t < 4 ? mt : (t == 4 ? 15 - ti : ti)) * 128;
        const int col = t < 4 ? (gq + (t >> 1) * 8) * 4 + rank * 2 : (hh + rank * 16) * 2;
        if (t >= 4) mbar_wait(B(B_DEP + t - 4), 0);
#pragma unroll 1
        for (int kb = 0; kb < nk; kb++) {
          const uint32_t d = sb + st * P1_STAGE, fb = B(B_FULL1 + st);
          const int n = t * 8 + kb;
          if (n >= PRE) {
            mbar_wait_c(B(B_EMPTY1 + st), ph);
            if (elect_one()) {
              mbar_expect(fb, P1_STAGE);
              tma_ld2(d, ma, fb, kb * 64, row);
              tma_ld3_mc(d + 16384 + rank * 16384, mb, fb, 0, kb * 64, col, 3);
            }
          }
          if (t < 5 && elect_one()) {
            if (n >= LN_PF && n < LN_PF + LN_PFN) l2_prefetch(x + (size_t)cta * 16 * DM + (n - LN_PF) * (16 * DM / LN_PFN), 32768 / LN_PFN);
            if (n == LN_LD) {
              mbar_expect(B(B_LN), 32768);
              asm volatile("cp.async.bulk.shared::cluster.global.mbarrier::complete_tx::bytes [%0], [%1], %2, [%3];" ::"r"(sb + OFF_LN),
                           "l"(x + (size_t)cta * 16 * DM), "r"(32768), "r"(B(B_LN)) : "memory");
            }
            if (t < 3 && kb == 0) tma_pf3((t & 1) ? &p.wk : &p.wv, 0, mp * 64, (gq + ((t + 1) >> 1) * 8) * 4 + rank * 2);
            if (n >= WQ_0 && n < WQ_0 + 4 * WQ_D && (n - WQ_0) % WQ_D == 0) tma_pf3(&p.wq, 0, ((n - WQ_0) / WQ_D * 4 + (gq & 3)) * 64, (hh + rank * 16) * 2);
          }
          if (++st == 4) { st = 0; ph ^= 1; }
        }
      }
      if (elect_one()) { prefetch_tm(&p.kv); prefetch_tm(&p.ctx_ld); prefetch_tm(&p.wo); prefetch_tm(&p.wg); prefetch_tm(&p.wu); }
      auto load_kv = [&](int g, int isv) {
        const int h2 = g >= 17, sx = g - 17 * h2, n1 = h2 ? ti + 1 : 16 - ti;
        const int row = (1 + isv) * SEQ + (sx < n1 ? sx : 16 - sx) * 128, col = (hh + 16 * h2) * 2;
        const uint32_t d = sb + (isv ? 2 + 2 * (g & 1) : (g & 1)) * SLOT, fb = B(B_KF + 2 * isv + (g & 1));
        const bool ef = sx >= n1 || sx >= 8;
        const bool shared = sx != (h2 ? (ti & 6) + 1 : 15 - (ti & 6));
        const int h3 = g >= 16, s3 = g + 1 - 17 * h3;
        const int pb = ti < 2 ? (h3 ? (s3 >= 1 && s3 <= 8 ? 16 - s3 : -1) : (s3 < 16 ? s3 : -1)) : (ti >= 6 && h3 && s3 < 8 ? s3 : -1);
        mbar_wait_c(g < 2 ? B(B_EMPTY1 + (isv ? 1 + 2 * g : g)) : B(B_KE + 2 * isv + (g & 1)), g < 2 ? 1 : ((g >> 1) & 1) ^ 1);
        if (elect_one()) {
          mbar_expect(fb, SLOT);
          if (shared) {
            tma_ld3_mc(d + rank * 16384, &p.kv, fb, 0, row, col + rank, 3, ef);
          } else {
            tma_ld3(d, &p.kv, fb, 0, row, col, ef);
            tma_ld3(d + 16384, &p.kv, fb, 0, row, col + 1, ef);
          }
          if (pb >= 0) tma_pf3(&p.kv, 0, (1 + isv) * SEQ + pb * 128, (hh + 16 * h3) * 2 + rank);
        }
      };
      int nw = ffn ? 0 : 12;
      auto load_w = [&]() {
        const int c = nw < 8 ? (nw >> 2) + (nw & 2) : nw >> 1;
        if (elect_one()) {
          if (!(nw & 3)) mbar_expect(B(B_WF - (nw >> 3)), 32768);
          tma_ld2(sb + (c < 2 ? 3 : 4) * SLOT + c * 16384 + (nw & 1) * 8192, (nw & 1) ? &p.wg : &p.wu, B(B_WF - (nw >> 3)), fid * 32, c * 128, true);
        }
        nw++;
      };
#pragma unroll 1
      for (int g = 0; g < 34; g++) {
        if (g == 0 || g == 16) mbar_wait(B(B_DEP + 2 + (g > 0)), 0);
        load_kv(g, 0);
        if (g > 0) load_kv(g - 1, 1);
        if (g >= W_G0 && nw < 12 && __any_sync(~0u, mbar_test(B(B_QP + (nw >> 2)), 0))) load_w();
      }
      load_kv(33, 1);
#pragma unroll 1
      while (nw < 12) { mbar_wait(B(B_QP + (nw >> 2)), 0); load_w(); }
      if (elect_one()) { prefetch_tm(&p.wd); prefetch_tm(&p.x); prefetch_tm(&p.out); }
      auto load3 = [&](int kb, int sl) {
        if (elect_one()) {
          mbar_expect(B(B_FULL3 + sl), SLOT);
          tma_ld2(sb + OFF_R3 + sl * SLOT, &p.ctx_ld, B(B_FULL3 + sl), kb * 64, mt * 128);
          tma_ld3_mc(sb + OFF_R3 + sl * SLOT + 16384 + rank * 8192, &p.wo, B(B_FULL3 + sl), 0, kb * 64, gq * 2 + rank, 3);
        }
      };
      mbar_wait(B(B_DEP + 4), 0);
#pragma unroll
      for (int kb = 0; kb < 5; kb++) {
        mbar_wait_c(B(kb == 3 ? B_WE : (kb == 4 ? B_VE + 1 : B_KE + kb)), 0);
        load3(kb, kb);
      }
      if (elect_one()) mbar_arrive(B(B_FULL3 + 5));
#pragma unroll 1
      for (int r = 1; r < 11; r++) {
#pragma unroll
        for (int j = 0; j < 6; j++) {
          if (j == 5 && r == 10) break;
          if (j == 3 && r == 5) mbar_wait(B(B_DEP + 5), 0);
          mbar_wait_c(B(B_EMPTY3 + j), ~r & 1);
          load3(r * 6 + j - 1, j);
          if (j == 5 && r == 9 && elect_one()) l2_prefetch(xr, XR_CAND * 16);
        }
      }
      if (ffn) {
#pragma unroll
        for (int j = 1; j >= 0; j--) {
          mbar_wait(B(B_EMPTY3 + 5 * j), j);
          if (elect_one()) {
            mbar_expect(B(B_FULL3 + 5 * j), SLOT);
            tma_ld3(sb + OFF_R3 + 5 * j * SLOT, &p.wd, B(B_FULL3 + 5 * j), 0, fid * 32, 8 * j, true);
          }
        }
      }
    } else {
      if (warp >= 2) {
#pragma unroll 1
        for (int i = tid - 64; i < XR_CAND; i += 64) xr[i] = make_uint4(~0u, ~0u, ~0u, ~0u);
        if (warp == 2) { __syncwarp(); if (lane == 0) mbar_arrive(B(B_WR)); }
      }
      if (warp == 3) {
        float ws = 0.f;
#pragma unroll
        for (int j = 0; j < 4; j++) {
          const uint4 q = __ldg(reinterpret_cast<const uint4*>(w_r) + j * 32 + lane);
          ws += bf_lo(q.x) + bf_hi(q.x) + bf_lo(q.y) + bf_hi(q.y) + bf_lo(q.z) + bf_hi(q.z) + bf_lo(q.w) + bf_hi(q.w);
        }
#pragma unroll
        for (int o = 16; o; o >>= 1) ws += __shfl_xor_sync(~0u, ws, o);
        uint2* tab = reinterpret_cast<uint2*>(sp + OFF_MISC + 512);
        tab[lane] = make_uint2(0x3F803F80u, 0x3F803F80u);
        tab[32 + lane] = __ldg(reinterpret_cast<const uint2*>(w_r + gq * 128) + lane);
        if (lane == 0) *reinterpret_cast<float*>(sp + OFF_MISC + 1024) = ws;
        __syncwarp();
        if (lane == 0) mbar_arrive(B(B_WR));
      }
      if (tid == 32) TS(0);
      mbar_wait(B(B_LN), 0);
#pragma unroll 1
      for (int r = warp - 1; r < 16; r += 3) {
        uint4 v[4];
        float a0 = 0.f, a1 = 0.f, b0 = 0.f, b1 = 0.f;
#pragma unroll
        for (int j = 0; j < 4; j++) {
          v[j] = lds128(sb + OFF_LN + r * 2048 + lane * 16 + j * 512);
          const uint32_t u[4] = {v[j].x, v[j].y, v[j].z, v[j].w};
#pragma unroll
          for (int i = 0; i < 4; i++) { const float a = bf_lo(u[i]), b = bf_hi(u[i]); a0 += a; a1 += b; b0 = fmaf(a, a, b0); b1 = fmaf(b, b, b1); }
        }
        a0 += a1; b0 += b1;
#pragma unroll
        for (int o = 16; o; o >>= 1) { a0 += __shfl_xor_sync(~0u, a0, o); b0 += __shfl_xor_sync(~0u, b0, o); }
        const float mean = a0 * (1.f / DM);
        float mb, inv;
        ln_round(mean, fmaxf(fmaf(b0, 1.f / DM, -mean * mean), 0.f), mb, inv);
        inv *= AT_C;
        const uint32_t nm2 = pack_bf16(-mb, -mb);
        uint4* dst = reinterpret_cast<uint4*>(g_xn + (size_t)(cta * 16 + r) * DM) + lane;
#pragma unroll
        for (int j = 0; j < 4; j++)
          dst[j * 32] = make_uint4(ln_apply(v[j].x, nm2, inv), ln_apply(v[j].y, nm2, inv), ln_apply(v[j].z, nm2, inv), ln_apply(v[j].w, nm2, inv));
      }
      __syncwarp();
      if (lane == 0) {
        mbar_arrive(B(B_LND));
        fence_gpu();
        red_add(&g_cnt[C_LN + (cta >> 3)], 1);
      }
      TL(3, warp, lane == 0);
      __syncwarp();
      if (warp == 3) {
        if (lane == 0) {
#pragma unroll 1
          for (int i = 0; i < 6; i++) {
            const int c = i < 2 ? C_LN + (i ? ti : 15 - ti) : (i < 4 ? C_QKV + (i - 2) * 8 + mp : C_CTX + (i - 4) * 16 + mt);
            spin_until_ge<true>(&g_cnt[c], i < 2 ? 24 : 16);
            fence_async_all();
            mbar_arrive(B(B_DEP + i));
            TL(3, 4 + i, true);
          }
        }
      } else if (warp == 1 && elect_one()) {
        mbar_wait(B(B_WR), 0);
#pragma unroll 1
        for (int i = 0; i < 6; i++) {
          const int c = i < 2 ? C_QKV + gq + i * 8 : C_CTX + (i >> 2) * 16 + ((i == 3 || i == 4) ? ti : 15 - ti);
          mbar_wait(B(B_PUB + i), 0);
          if (i >= 2 && i < 5) {
            asm volatile("fence.proxy.async.shared::cta;" ::: "memory");
#pragma unroll 1
            for (int n = 0; n < 8; n++) {
              const int h = n >> 2, a = n & 3;
              asm volatile("cp.async.bulk.tensor.3d.global.shared::cta.bulk_group [%0, {%2,%3,%4}], [%1];" ::"l"(&p.ctx_st),
                           "r"(sb + (i == 4 ? 6 * SLOT + h * 16384 : (3 + 2 * h) * SLOT + (i - 2) * 16384) + a * 4096),
                           "r"(0), "r"((i == 2 ? 15 - ti : ti) * 128 + h * 64), "r"((hh + (i >> 2) * 16) * 4 + a) : "memory");
              asm volatile("cp.async.bulk.commit_group;\ncp.async.bulk.wait_group.read 0;" ::: "memory");
            }
            mbar_arrive(B(B_QP + i - 2));
            asm volatile("cp.async.bulk.wait_group 0;" ::: "memory");
          }
          fence_gpu();
          red_add(&g_cnt[c], 1);
          TS(1 + i);
        }
      }
      if (warp == 2) {
#pragma unroll 1
        for (int n = 0; n < 8; n++) {
          if (!(n & 3)) mbar_wait(B(B_XE), n >> 2);
          if ((n < 4 || ffn) && elect_one()) {
            const uint32_t fb = B(n < 4 ? B_XF : B_WF2), d = sb + 6 * SLOT + (n & 3) * 8192;
            if (!(n & 3)) mbar_expect(fb, 32768);
            if (n < 4) tma_ld3(d, &p.x, fb, 0, mt * 128 + (n >> 1) * 64, gq * 2 + (n & 1), true);
            else tma_ld2(d, (n & 1) ? &p.wg : &p.wu, fb, fid * 32, (4 + (n >> 1)) * 128, true);
          }
          __nanosleep(SL_NS);
        }
#pragma unroll 1
        for (int i = XR_CAND + lane; i < XR_SIZE; i += 32) { xr[i] = make_uint4(~0u, ~0u, ~0u, ~0u); __nanosleep(SET_NS); }
        __syncwarp();
        if (lane == 0) { fence_gpu(); mbar_arrive(B(B_SET2)); }
        TL(2, 26, lane == 0);
        __syncwarp();
      }
      __syncwarp();
      if (warp == 3) {
        mbar_wait(B(B_OUT), 0);
        uint4 kv[2];
        poll_chunks(kv, g_xr + ((lane >> 1) * 8 + gq) * XR_SIZE + XR_KEY + (lane & 1) * 2, 1);
        const uint32_t a1 = max(kv[0].x, kv[0].z), a2 = max(min(kv[0].x, kv[0].z), max(kv[0].y, kv[0].w));
        const uint32_t b1 = max(kv[1].x, kv[1].z), b2 = max(min(kv[1].x, kv[1].z), max(kv[1].y, kv[1].w));
        const uint32_t k1 = max(a1, b1), k2 = max(min(a1, b1), max(a2, b2));
        const uint32_t m1 = __reduce_max_sync(~0u, k1);
        const uint32_t m2 = __reduce_max_sync(~0u, k1 == m1 ? k2 : k1);
        if (lane == 0) {
          *reinterpret_cast<uint2*>(sp + OFF_MISC) = make_uint2(m1, m2);
          mbar_arrive(B(B_OUT2));
        }
        const uint32_t key = (lane & 4) ? m2 : m1;
        const int tk = 0x7FFF - (key & 0x7FFF);
        const uint4* src = g_xr + ((tk >> 7) * 8 + (rid >> 4)) * XR_SIZE;
        poll_chunks(kv, src + XR_CAND + ((tk >> 4) & 7) * 64 + (((lane & 4) && !((m1 ^ m2) & 0x7FF0)) ? 16 : 0) + (rid & 12) + (lane & 3), 32);
        uint32_t u = key >> 16;
        u = (u & 0x8000u) ? (u & 0x7FFFu) : (~u & 0xFFFFu);
        const float rs = bf_round(__fdividef(1.f, 1.f + __expf(-__uint_as_float(u << 16))));
        if (lane < 8)
          *reinterpret_cast<uint4*>(sp + OFF_MISC + 128 + lane * 16) = make_uint4((rid & 2) ? ((rid & 1) ? kv[0].w : kv[0].z) : ((rid & 1) ? kv[0].y : kv[0].x),
              (rid & 2) ? ((rid & 1) ? kv[1].w : kv[1].z) : ((rid & 1) ? kv[1].y : kv[1].x), __float_as_uint(rs), 0);
#pragma unroll 1
        for (int n = 0; n < 0x400000; n++) {
          uint32_t v;
          asm volatile("ld.acquire.gpu.global.u32 %0, [%1];" : "=r"(v) : "l"(src + XR_FLAG) : "memory");
          if (__all_sync(~0u, v == 0)) break;
        }
        if (lane == 0) mbar_arrive(B(B_FIN));
      }
      if (warp == 1 && elect_one()) {
        mbar_wait(B(B_OUT3), 0);
        auto owner = [&]() {
          uint2 top;
          asm volatile("ld.shared.v2.u32 {%0,%1}, [%2];" : "=r"(top.x), "=r"(top.y) : "r"(sb + OFF_MISC) : "memory");
          return (0x7FFF - (top.x & 0x7FFF)) >> 7 == mt || (0x7FFF - (top.y & 0x7FFF)) >> 7 == mt;
        };
#pragma unroll 1
        for (int n = 0; n < 4; n++) {
          if (n && !(mbar_test(B(B_OUT2), 0) && owner())) idle(OUT_CLK);
          asm volatile("cp.async.bulk.tensor.2d.global.shared::cta.bulk_group [%0, {%2,%3}], [%1];" ::"l"(&p.out), "r"(sb + OFF_STG + n * 8192),
                       "r"(gq * 128 + (n & 1) * 64), "r"(mt * 128 + (n >> 1) * 64) : "memory");
        }
        asm volatile("cp.async.bulk.commit_group;" ::: "memory");
        mbar_wait(B(B_OUT2), 0);
        if (owner()) {
          asm volatile("cp.async.bulk.wait_group 0;" ::: "memory");
          asm volatile("st.release.gpu.global.u32 [%0], 0;" ::"l"(xr + XR_FLAG) : "memory");
        } else {
          asm volatile("cp.async.bulk.wait_group.read 0;" ::: "memory");
        }
        TL(2, 25, true);
      }
    }
    __syncwarp();
    cluster_arrive();
    cluster_wait();
    TL_DUMP();
    if (tid == 32) TS(8);
  } else {
    reg_alloc<232>();
    cluster_wait();
    const int w = wg - 1, cw = warp - 4;
    int lane = lane_id();
    const uint32_t stg = sb + OFF_STG + w * 16384 + (cw & 3) * 2048;
    auto publish = [&](int i) { __syncwarp(); if (lane == 0) mbar_arrive(B(B_PUB + i)); };
    uint32_t rbar;
    asm("mapa.shared::cluster.u32 %0, %1, %2;" : "=r"(rbar) : "r"(bar), "r"(lane & 1));
    auto release2 = [&](int i) { if (lane < 2) asm volatile("mbarrier.arrive.shared::cluster.b64 _, [%0];" ::"r"(rbar + 8 * i) : "memory"); };
    float R[128];
    float O[64], acc[64];
    uint32_t pk[64];
    uint32_t* const Q = pk;
    uint32_t P[32];
    auto packed = [&](int i) {
      const float* v = R + 16 * (i >> 1) + 2 * (i & 1);
      return make_uint4(pack_bf16(v[0], v[1]), pack_bf16(v[4], v[5]), pack_bf16(v[8], v[9]), pack_bf16(v[12], v[13]));
    };
    const uint32_t q_st = sb + (cw & 3) * 1024 + (lane >> 2) * 64 + (((lane & 3) ^ (lane >> 3)) << 4);
    const uint32_t q_ld = sb + (cw & 3) * 1024 + (lane & 15) * 64 + (((lane >> 4) ^ ((lane >> 1) & 3)) << 4);
    auto park = [&](uint32_t off, int i, uint4 v) {
      asm volatile("st.shared.v4.u32 [%0], {%1,%2,%3,%4};" ::"r"(q_st + off + (i >> 1) * 4096 + (i & 1) * 512), "r"(v.x), "r"(v.y), "r"(v.z), "r"(v.w) : "memory");
    };
    auto load_q = [&](uint32_t off, int k) { ldsm4(Q + 4 * k, ((q_ld + off) ^ ((k & 1) << 5)) + (k >> 1) * 4096); };
    {
      TL(0, 1, tid == 128);
      __nv_bfloat16* pdst = g_qkv;
      auto put2 = [&](int j) {
#pragma unroll
        for (int i = (j >> 1) * 4 + (j & 1); i < (j >> 1) * 4 + 4; i += 2)
          __stcs(reinterpret_cast<uint4*>(pdst + (i & 1) * 8 * NQ + (i >> 1) * 32), make_uint4(pk[4 * i], pk[4 * i + 1], pk[4 * i + 2], pk[4 * i + 3]));
      };
      const uint64_t da0 = mk_desc(sb + w * 8192, 16, 1024, 1);
      const uint64_t db0 = mk_desc(sb + 16384, 8192, 1024, 1);
      int st = 0; uint32_t ph = 0;
      auto issue = [&](int accum, auto between) {
        mbar_wait_c(B(B_FULL1 + st), ph);
        const uint64_t da = desc_add(da0, st * P1_STAGE), db = desc_add(db0, st * P1_STAGE);
        between();
        wg_fence();
#pragma unroll
        for (int k = 0; k < 4; k++) mma_n256_ss<1>(R, desc_add(da, k * 32), desc_add(db, k * 2048), k == 0 ? accum : 1);
        wg_commit();
      };
      issue(0, []() {});
#pragma unroll 1
      for (int t = 0;; t++) {
        const int nk = t >= 4 ? 16 : 8;
        const bool tr = t > 0 && t < 5;
        TL(0, 2 + 2 * t + 16 * w, (tid & 127) == 0);
        int prev = st;
        if (++st == 4) { st = 0; ph ^= 1; }
#pragma unroll 1
        for (int kb = 1; kb < nk; kb++) {
          if (kb == nk - 1 && w == 1) bar_sync(5, 256);
          issue(1, []() {});
          if (kb == nk - 1 && w == 0) bar_arrive(5, 256);
          if (tr) {
#pragma unroll
            for (int i = 1; i < 8; i++) if (kb == i) put2(i);
            if (kb == 7 && !(t & 1)) publish((t >> 1) - 1);
          } else if (t == 5) {
            if (kb == 2) {
              mbar_wait_c(B(B_LND), 0);
#pragma unroll
              for (int i = 0; i < 8; i++) park(6 * SLOT + w * 16384, i, make_uint4(pk[4 * i], pk[4 * i + 1], pk[4 * i + 2], pk[4 * i + 3]));
              __syncwarp();
            }
            if (kb == 4) {
#pragma unroll
              for (int k = 0; k < 8; k++) load_q(6 * SLOT + w * 16384, k);
              __syncwarp();
            }
            if (kb == 6) {
#pragma unroll
              for (int i = 0; i < 8; i++) park(6 * SLOT + w * 16384, i, make_uint4(pk[32 + 4 * i], pk[33 + 4 * i], pk[34 + 4 * i], pk[35 + 4 * i]));
            }
          }
          wg_wait<1>();
          release2(B_EMPTY1 + prev);
          prev = st;
          if (++st == 4) { st = 0; ph ^= 1; }
        }
        if (t == 5) break;
        issue(0, [&]() {
          sched_fence(q_st);
          wg_wait<0>();
          fence_regs<128>(R);
          TL(0, 3 + 2 * t + 16 * w, (tid & 127) == 0);
#pragma unroll
          for (int i = 0; i < 16; i++) { const uint4 v = packed(i); pk[4 * i] = v.x; pk[4 * i + 1] = v.y; pk[4 * i + 2] = v.z; pk[4 * i + 3] = v.w; }
          release2(B_EMPTY1 + prev);
          fence_regs<128>(R);
        });
        if (w == 1) bar_arrive(4, 256);
        sched_fence(q_st);
        pdst = g_qkv + (size_t)(((t & 1) + 1) * SEQ + mt * 128 + cw * 16 + (lane >> 2)) * NQ + (gq + (t >> 1) * 8) * 256 + (lane & 3) * 8;
        if (t < 4) put2(0);
        if (w == 0) bar_sync(4, 256);
      }
      if (w == 1) bar_arrive(6, 256);
      mbar_wait_c(B(B_KF), 0);
      sched_fence(q_st);
      wg_wait<0>();
      fence_regs<128>(R);
      release2(B_EMPTY1 + 3);
      TL(0, 13 + 16 * w, (tid & 127) == 0);
    }
    auto issue3 = [&](int st, uint32_t ph, int accum) {
      mbar_wait_c(B(B_FULL3 + st), ph);
      const uint64_t da = mk_desc(sb + OFF_R3 + w * 8192 + st * SLOT, 16, 1024, 1), db = mk_desc(sb + OFF_R3 + 16384 + st * SLOT, 8192, 1024, 1);
      wg_fence();
#pragma unroll
      for (int k = 0; k < 4; k++) mma_n128_ss<1>(acc, desc_add(da, k * 32), desc_add(db, k * 2048), k == 0 ? accum : 1);
      wg_commit();
    };
    uint32_t wf[128];
    auto w_addr = [&](uint32_t off, int m) {
      const uint32_t w_ld = sb + ((lane >> 3) & 1) * 8192 + ((cw >> 1) * 32 + (lane & 7) + (lane >> 4) * 8) * 64 + ((((cw & 1) * 2) ^ ((lane >> 1) & 3)) << 4);
      return ((w_ld + off) ^ ((m & 1) << 4)) + (m >> 2) * 16384 + ((m >> 1) & 1) * 1024;
    };
    auto grab = [&](uint32_t* d, uint32_t off, int m0, int m1) {
#pragma unroll
      for (int m = m0; m < m1; m++)
        asm volatile("ldmatrix.sync.aligned.m8n8.x4.trans.shared.b16 {%0,%1,%2,%3}, [%4];"
                     : "=r"(d[4 * m]), "=r"(d[4 * m + 1]), "=r"(d[4 * m + 2]), "=r"(d[4 * m + 3]) : "r"(w_addr(off, m)) : "memory");
    };
    float inv[2] = {0.f, 0.f};
    auto scaled = [&](int i) {
      const float* o = O + 16 * (i >> 1) + 2 * (i & 1);
      const float c = inv[i & 1];
      return make_uint4(pack_bf16(o[0] * c, o[1] * c), pack_bf16(o[4] * c, o[5] * c), pack_bf16(o[8] * c, o[9] * c), pack_bf16(o[12] * c, o[13] * c));
    };
    {
      const int wrow = cw * 16;
      const uint64_t dk0 = mk_desc(sb, 16, 1024, 1);
      const uint64_t dv0 = mk_desc(sb + 2 * SLOT, 16384, 1024, 1);
      const uint32_t pin = sb + OFF_MISC + 1028;
      float l0 = 0.f, l1 = 0.f;
      int g = 0, t = 0;
      uint32_t fail = 0;
      auto piece = [&](int tt) { return (uint32_t)(tt == 3 ? 6 * SLOT + w * 16384 : (3 + 2 * w) * SLOT + (tt - 1) * 16384); };
      uint32_t par = 0;
      auto issue_s = [&](float* S) {
        const uint64_t dk = desc_add(dk0, par * 16);
        mma_n128_rs0(S, Q, dk);
#pragma unroll
        for (int k = 1; k < 8; k++) mma_n128_rs<0>(S, Q + 4 * k, desc_add(dk, (k >> 2) * 16384 + (k & 3) * 32), 1);
        wg_commit();
      };
      auto issue_pv = [&](bool half, int accum) {
        const uint64_t dv = desc_add(dv0, ((g - 1) & 1) * 2 * SLOT);
        wg_fence();
#pragma unroll
        for (int k = 0; k < 4; k++) mma_n128_rs<1>(O, P + 4 * k, desc_add(dv, k * 2048), k == 0 ? accum : 1);
        wg_commit();
        if (UNLIKELY(half)) {
          wg_fence();
          wg_commit();
        } else {
          wg_fence();
#pragma unroll
          for (int k = 4; k < 8; k++) mma_n128_rs<1>(O, P + 4 * k, desc_add(dv, k * 2048), 1);
          wg_commit();
        }
        bar_arrive(2 - w, 256);
        wg_wait<2>();
        fence_regs<32>(Q);
      };
      auto release_k = [&]() { release2(B_KE); rbar ^= 8; };
      auto pv_done = [&]() {
        TC(g, 3);
        sched_fence(q_st);
        wg_wait<0>();
        fence_regs<64>(O); fence_regs<32>(P);
        TC(g, 4);
        release2(B_VE);
      };
      auto row_inv = [&](bool go) {
        float a = l0 + __shfl_xor_sync(~0u, l0, 1), b = l1 + __shfl_xor_sync(~0u, l1, 1);
        a += __shfl_xor_sync(~0u, a, 2); b += __shfl_xor_sync(~0u, b, 2);
        const bool ok = __all_sync(~0u, a >= AT_LO && a <= AT_HI && b >= AT_LO && b <= AT_HI) != 0;
        asm("rcp.approx.ftz.f32 %0, %1;" : "=f"(inv[0]) : "f"(a));
        asm("rcp.approx.ftz.f32 %0, %1;" : "=f"(inv[1]) : "f"(b));
        fail |= (uint32_t)(go && !ok) << t;
        l0 = go ? 0.f : l0; l1 = go ? 0.f : l1;
        t += go;
      };
      const uint64_t m_first = 1ull | (1ull << (16 - ti)) | (1ull << 17) | (1ull << (18 + ti));
      const uint64_t m_diag = (3ull << (15 - ti)) | (3ull << (17 + ti));
      enum { F_FIRST = 1, F_DIAG = 2, F_LAST = 4, F_PFIRST = 8, F_PHALF = 16, F_STOP = 32 };
      auto kind = [&](int gn) {
        const uint32_t a = (uint32_t)((m_first << 1) >> gn), d = (uint32_t)((m_diag << 1) >> gn);
        return ((a >> 1) & 1) * F_FIRST | ((d >> 1) & 1) * F_DIAG | ((a >> 2) & 1) * F_LAST | (a & 1) * F_PFIRST |
               (w == 0 ? (d & 1) * F_PHALF | ((d >> 1) & 1) * F_STOP : 0) | (gn == 34 ? F_STOP : 0);
      };
      uint32_t kinds;
      {
        uint32_t qt[64];
#pragma unroll
        for (int i = 0; i < 16; i++) { const uint4 v = packed(i); qt[4 * i] = v.x; qt[4 * i + 1] = v.y; qt[4 * i + 2] = v.z; qt[4 * i + 3] = v.w; }
        fence_regs<64>(qt);
        sched_fence(q_st);
        float S[64];
        wg_fence();
        issue_s(S);
        bar_arrive(w ? 1 : 7, 256);
        bar_sync(6 + w, 256);
        sched_fence(q_st);
        TL(1, 0, tid == 128);
#pragma unroll
        for (int i = 0; i < 16; i++) park(piece(1), i, make_uint4(qt[4 * i], qt[4 * i + 1], qt[4 * i + 2], qt[4 * i + 3]));
        kinds = pinned(kind(lane + 3));
        sched_fence(q_st);
        wg_wait<0>();
        fence_regs<64>(S);
        release_k();
        TL(1, 1, tid == 128);
        const bool kok = mbar_try(B(B_KF + 1), 0);
        at_exp<0, 32>(S);
        sched_fence(q_st);
        at_exp<32, 64>(S); at_fin<0, 64>(S, P);
        if (UNLIKELY(!kok)) mbar_wait_c(B(B_KF + 1), 0);
        TL(1, 2, tid == 128);
      }
      uint32_t f = F_PFIRST, fn;
      auto shadow = [&]() {
        const bool vok = mbar_try(B(B_VF + ((g - 1) & 1)), ((g - 1) >> 1) & 1);
        at_sum(P, f & F_PHALF, l0, l1);
        fn = __shfl_sync(~0u, kinds, max(g - 2, 0));
        if (UNLIKELY(!vok)) mbar_wait_c(B(B_VF + ((g - 1) & 1)), ((g - 1) >> 1) & 1);
      };
      auto hand_over = [&]() { __syncwarp(); if (lane == 0 && !((fail >> (t - 1)) & 1)) mbar_arrive(B(B_PUB + 1 + t)); };
      auto exp_q = [&](float* S, auto kc, auto nc) {
        constexpr int k = decltype(kc)::value, n = decltype(nc)::value;
        asm volatile("{\n.reg .pred p;\nsetp.ne.b32 p, %5, 0;\n@p ldmatrix.sync.aligned.m8n8.x4.shared.b16 {%0,%1,%2,%3}, [%4];\n}"
                     : "+r"(Q[4 * k]), "+r"(Q[4 * k + 1]), "+r"(Q[4 * k + 2]), "+r"(Q[4 * k + 3])
                     : "r"(((q_ld + piece(t + 1)) ^ ((k & 1) << 5)) + (k >> 1) * 4096), "r"(f & F_LAST) : "memory");
        at_exp<n * k, n * k + n>(S);
      };
      g = 1; par = SLOT / 16;
#pragma unroll 1
      for (;;) {
        {
          TC(g, 0);
          bar_sync(1 + w, 256);
          fence_regs<32>(Q);
          float S[64];
          wg_fence();
          issue_s(S);
          sched_fence(q_st);
          TC(g, 1);
          shadow();
          fence_regs<64>(O); fence_regs<32>(P);
          issue_pv(f & F_PHALF, ~f & F_PFIRST);
          fence_regs<64>(S);
          TC(g, 2);
          release_k();
          at_exp<0, 8>(S);
          const bool first = f & F_FIRST;
          if (UNLIKELY(f & (F_FIRST | F_LAST))) {
            row_inv(first);
            at_mask(S + 32, (f & F_DIAG) ? wrow - 64 : 64, lane);
            unroll8([&](auto kc) { exp_q(S + 8, kc, std::integral_constant<int, AT_R1 / 8 - 1>{}); });
          } else {
            at_exp<8, AT_R1>(S);
          }
          pv_done();
          g = pinned(g + 1); par = pinned(par ^ (SLOT / 16)); f = fn;
          const bool kok = mbar_try(B(B_KF + (g & 1)), g < 34 ? (g >> 1) & 1 : 0);
          if (UNLIKELY(first)) {
            unroll8([&](auto ic) {
              constexpr int i = decltype(ic)::value, n = (64 - AT_R1) / 8;
              at_exp<AT_R1 + n * i, AT_R1 + n * i + n>(S);
              park(piece(t), i, scaled(i));
            });
            at_fin<0, 64>(S, P);
            hand_over();
          } else {
            at_exp<AT_R1, 64>(S); at_fin<0, 64>(S, P);
          }
          TC(g - 1, 5);
          if (!TCLK) TL(1, 1 + g, tid == 128);
          if (kok && !(f & F_STOP)) continue;
          if (UNLIKELY(!kok)) mbar_wait_c(B(B_KF + (g & 1)), (g >> 1) & 1);
          if (g == 34) break;
        }
#pragma unroll 1
        while (f & F_STOP) {
          TC(g, 0);
          bar_sync(1, 256);
          fence_regs<64>(O); fence_regs<32>(Q); fence_regs<32>(P);
          float S[32];
          const uint64_t dk = desc_add(dk0, par * 16);
          wg_fence();
          mma_n64_rs0(S, Q, dk);
#pragma unroll
          for (int k = 1; k < 8; k++) mma_n64_rs(S, Q + 4 * k, desc_add(dk, (k >> 2) * 16384 + (k & 3) * 32), 1);
          wg_commit();
          TC(g, 1);
          mbar_wait_c(B(B_VF + ((g - 1) & 1)), ((g - 1) >> 1) & 1);
          issue_pv(f & F_PHALF, ~f & F_PFIRST);
          fence_regs<32>(S);
          TC(g, 2);
          release_k();
          const bool first = f & F_FIRST;
          at_sum(P, f & F_PHALF, l0, l1);
          fn = __shfl_sync(~0u, kinds, g - 2);
          row_inv(first);
          pv_done();
          sched_fence(q_st);
          at_mask(S, wrow, lane);
          unroll8([&](auto kc) { exp_q(S, kc, std::integral_constant<int, 4>{}); });
          g++; par ^= SLOT / 16; f = fn;
          at_fin<0, 32>(S, P);
          if (first) {
#pragma unroll
            for (int i = 0; i < 8; i++) park(piece(t), i, scaled(i));
            hand_over();
          }
          TC(g - 1, 5);
          if (!TCLK) TL(1, 1 + g, tid == 128);
          mbar_wait_c(B(B_KF + (g & 1)), (g >> 1) & 1);
        }
      }
      const bool wok = mbar_test(B(ffn ? B_WF : B_QP + 1), 0);
      grab(wf, 3 * SLOT, 0, 8);
      mbar_wait_c(B(B_VF + 1), 0);
      bar_sync(1 + w, 256);
      fence_regs<64>(O); fence_regs<32>(P);
      wg_fence();
#pragma unroll
      for (int k = 0; k < 8; k++) mma_n128_rs<1>(O, P + 4 * k, desc_add(dv0, 2 * SLOT + k * 2048), 1);
      wg_commit();
      if (w == 0) bar_arrive(2, 256);
      pin_order(__uint_as_float(wf[28] & wf[24]), pin);
      __syncwarp();
      if (wok) release2(B_WE);
      TL(3, 12 + 16 * w, (tid & 127) == 0);
      sched_fence(q_st);
      at_sum(P, false, l0, l1);
      row_inv(true);
      sched_fence(q_st);
      wg_wait<0>();
      fence_regs<64>(O); fence_regs<32>(P);
      release2(B_VE + 1);
      if (UNLIKELY(!wok || fail != 0)) {
#pragma unroll 1
        for (int tt = 0; tt < 4; tt++) {
          if (!((tt < 3 ? fail >> tt : fail != 0) & 1)) continue;
          slow_tile(O, P, l0, l1, wq, (((tt + 1) & 2) ? ti : 15 - ti) * 128 + wrow, hh + (tt & 2) * 8, lane, q_st);
          row_inv(false);
          if (tt < 3) {
#pragma unroll
            for (int i = 0; i < 8; i++) park(piece(tt + 1), i, scaled(i));
            publish(2 + tt);
          }
        }
        if (!wok) {
          mbar_wait_c(B(ffn ? B_WF : B_QP + 1), 0);
          grab(wf, 3 * SLOT, 0, 8);
          pin_order(__uint_as_float(wf[28] & wf[24]), pin);
          __syncwarp();
          release2(B_WE);
        }
      }
      TL(3, 13 + 16 * w, (tid & 127) == 0);
      issue3(0, 0, 0);
      TL(3, 14 + 16 * w, (tid & 127) == 0);
      TL(1, 36, tid == 128);
    }
    uint32_t hp[32];
    lane = lane_id();
    {
      int st = 1, prev = 0; uint32_t ph = 0;
      __nv_bfloat16* dst = g_qkv + (size_t)((15 - ti) * 128 + cw * 16 + (lane >> 2)) * NQ + (hh + 16) * 128 + (lane & 3) * 8;
      auto kblock = [&](auto between, int lim = 6) {
        issue3(st, ph, 1);
        between();
        wg_wait<1>();
        release2(B_EMPTY3 + prev);
        prev = st;
        if (++st == lim) { st = 0; ph ^= 1; }
      };
      kblock([&]() { TL(3, 15 + 16 * w, (tid & 127) == 0); });
      kblock([&]() { grab(wf + 32, 5 * SLOT, 0, 8); TL(3, 16 + 16 * w, (tid & 127) == 0); });
#pragma unroll 1
      for (int kb = 3; kb < 11; kb++) {
        kblock([&]() {
#pragma unroll
          for (int i = 0; i < 8; i++)
            if (kb == 3 + (i & 4) + (i & 1) * 2 + ((i >> 1) & 1)) *reinterpret_cast<uint4*>(dst + (i & 1) * 8 * NQ + (i >> 1) * 32) = scaled(i);
          TL(3, 14 + kb + 16 * w, (tid & 127) == 0);
          if (kb == 8) TL(2, 2, tid == 128);
        }, kb == 4 ? 5 : 6);
        if (kb == 4) release2(B_EMPTY3 + 5);
      }
      publish(5);
      kblock([&]() { mbar_wait_c(B(ffn ? B_WF2 : B_QP + 2), 0); grab(wf + 32, 5 * SLOT, 8, 16); });
#pragma unroll 1
      for (int kb = 12; kb < G_KB; kb++) {
        kblock([&]() { if ((kb & 7) == 0) TL(2, 1 + (kb >> 3), tid == 128); });
        if (kb == X_KB && lane == 0) mbar_arrive(B(B_XE));
      }
      kblock([&]() {
        mbar_wait_c(B(B_XF), 0);
#pragma unroll
        for (int i = 0; i < 8; i++)
          ldsm4(hp + 4 * i, sb + 6 * SLOT + w * 16384 + ((cw & 3) * 16 + (lane & 15)) * 128 + (i >> 2) * 8192 + ((((i & 3) * 2 + (lane >> 4)) ^ (lane & 7)) << 4));
      });
#pragma unroll 1
      for (int kb = G_KB + 1; kb < 64; kb++) {
        kblock([&]() { if ((kb & 7) == 0) TL(2, 1 + (kb >> 3), tid == 128); });
        if (kb == G_KB + 2 && lane == 0) mbar_arrive(B(B_XE));
      }
    }
    lane = lane_id();
    const int r0 = lane >> 2, q4 = lane & 3, ct = cw * 32 + lane;
    uint32_t tb[16];
    mbar_wait_c(B(B_WR), 0);
#pragma unroll
    for (int i = 0; i < 4; i++) ldsm4(tb + 4 * i, sb + OFF_MISC + 512 + (lane & 1) * 256 + (lane >> 3) * 16 + i * 64);
    mbar_wait_c(B(B_SET2), 0);
    float4* const psd = reinterpret_cast<float4*>(xr + XR_PS + cw * 16 + r0);
    const uint4* const pss = g_xr + (mt * 8 + (ct & 1) * 4) * XR_SIZE + XR_PS + (ct >> 1);
    sched_fence(stg);
    wg_wait<0>();
    fence_regs<64>(acc);
    TL(2, 10, tid == 128);
    {
      float d[2][4] = {}, qa[2][4] = {}, qb[2][4] = {};
#pragma unroll
      for (int j = 0; j < 16; j++) {
        hp[2 * j] = hadd2_bf(hp[2 * j], pack_bf16(acc[4 * j], acc[4 * j + 1]));
        hp[2 * j + 1] = hadd2_bf(hp[2 * j + 1], pack_bf16(acc[4 * j + 2], acc[4 * j + 3]));
        if (j & 1) {
          mma16816(d[(j >> 1) & 1], hp[2 * j - 2], hp[2 * j - 1], hp[2 * j], hp[2 * j + 1], tb[j - 1], tb[j]);
          mma16816(qa[(j >> 1) & 1], hp[2 * j - 2], hp[2 * j - 1], hp[2 * j], hp[2 * j + 1], hp[2 * j - 2], hp[2 * j]);
          mma16816(qb[(j >> 1) & 1], hp[2 * j - 2], hp[2 * j - 1], hp[2 * j], hp[2 * j + 1], hp[2 * j - 1], hp[2 * j + 1]);
        }
      }
      if (q4 == (r0 >> 1)) {
        __stcg(psd, make_float4(d[0][0] + d[1][0], (r0 & 1) ? qa[0][1] + qa[1][1] : qa[0][0] + qa[1][0], d[0][1] + d[1][1], 0.f));
        __stcg(psd + 8, make_float4(d[0][2] + d[1][2], (r0 & 1) ? qb[0][3] + qb[1][3] : qb[0][2] + qb[1][2], d[0][3] + d[1][3], 0.f));
      }
    }
    TL(2, 11, tid == 128);
    mbar_wait_c(B(B_EMPTY3 + 1), 0);
    stage_store_128(stg, lane, hp);
    if (ffn) mbar_wait_c(B(B_WF2), 1);
    grab(wf + 96, 6 * SLOT, 0, 8);
    const float wsum = *reinterpret_cast<const float*>(sp + OFF_MISC + 1024);
    __syncwarp();
    {
      uint4 ps[4];
      poll_chunks(ps, pss, XR_SIZE);
      TL(2, 12, tid == 128);
      auto F = [](uint32_t u) { return __uint_as_float(u); };
      float s1 = (F(ps[0].x) + F(ps[1].x)) + (F(ps[2].x) + F(ps[3].x)), s2 = (F(ps[0].y) + F(ps[1].y)) + (F(ps[2].y) + F(ps[3].y));
      float s3 = (F(ps[0].z) + F(ps[1].z)) + (F(ps[2].z) + F(ps[3].z));
      __syncwarp();
      s1 += __shfl_xor_sync(~0u, s1, 1); s2 += __shfl_xor_sync(~0u, s2, 1); s3 += __shfl_xor_sync(~0u, s3, 1);
      const float mean = s1 * (1.f / DM);
      float mb, inv;
      ln_round(mean, fmaxf(fmaf(s2, 1.f / DM, -mean * mean), 0.f), mb, inv);
      uint32_t u = pack_bf16((s3 - mb * wsum) * inv, 0.f);
      if (u == 0x8000u) u = 0;
      u = (u & 0x8000u) ? (~u & 0xFFFFu) : (u | 0x8000u);
      const uint32_t key = (u << 16) | (0x7FFFu - (mt * 128 + (ct >> 1)));
      const uint32_t nm2 = pack_bf16(-mb, -mb);
      const uint32_t c1 = __reduce_max_sync(~0u, key);
      const uint32_t c2 = __reduce_max_sync(~0u, key == c1 ? 0u : key);
      if (lane == 0) {
        __stcg(reinterpret_cast<uint2*>(xr + XR_KEY) + cw, make_uint2(c1, c2));
        mbar_arrive(B(B_OUT));
      }
      TL(2, 13, tid == 128);
      const int row = (0x7FFF - (((lane >> 4) ? c2 : c1) & 0x7FFF)) & 15;
      const uint32_t rn = __shfl_sync(~0u, nm2, row * 2);
      const float ri = __shfl_sync(~0u, inv, row * 2);
      uint32_t v[4];
#pragma unroll
      for (int i = 0; i < 4; i++)
        asm volatile("ld.shared.u32 %0, [%1];" : "=r"(v[i]) : "r"(stg + ((lane >> 3) & 1) * 8192 + row * 128 + ((((lane & 4) + i) ^ (row & 7)) << 4) + q4 * 4) : "memory");
      __stcg(xr + XR_CAND + cw * 64 + 32 + lane, make_uint4(ln_apply(v[0], rn, ri), ln_apply(v[1], rn, ri), ln_apply(v[2], rn, ri), ln_apply(v[3], rn, ri)));
      __stcg(xr + XR_CAND + cw * 64 + lane, make_uint4(v[0], v[1], v[2], v[3]));
      sched_fence(stg);
      const uint32_t na = __shfl_sync(~0u, nm2, r0 * 2), nb = __shfl_sync(~0u, nm2, r0 * 2 + 16);
      const float ia = __shfl_sync(~0u, inv, r0 * 2), ib = __shfl_sync(~0u, inv, r0 * 2 + 16);
#pragma unroll
      for (int i = 0; i < 32; i++) hp[i] = hadd2_bf(hp[i], ln_apply(hp[i], (i & 1) ? nb : na, (i & 1) ? ib : ia));
      __syncwarp();
      stage_store_128(stg, lane, hp);
      asm volatile("fence.proxy.async.shared::cta;" ::: "memory");
      publish(B_OUT3 - B_PUB);
    }
    uint32_t wd[16][4];
    sched_fence(stg);
    if (ffn) mbar_wait_c(B(B_FULL3 + 5 * w), 1 - w);
    auto load_wd = [&](int h) {
#pragma unroll
      for (int i = h; i < 16; i += 2)
        asm volatile("ldmatrix.sync.aligned.m8n8.x4.trans.shared.b16 {%0,%1,%2,%3}, [%4];"
                     : "=r"(wd[i][0]), "=r"(wd[i][1]), "=r"(wd[i][2]), "=r"(wd[i][3])
                     : "r"(sb + OFF_R3 + 5 * w * SLOT + (2 * (cw & 3) + (i >> 3)) * 4096 + (h * 16 + (lane & 7) + (lane >> 4) * 8) * 128 +
                           (((2 * ((i >> 1) & 3) + ((lane >> 3) & 1)) ^ (lane & 7)) << 4)) : "memory");
    };
    load_wd(0);
    __syncwarp();
    cluster_arrive();
    TL(2, 22, tid == 128);
    mbar_wait_c(B(B_OUT2), 0);
    const uint2 top = *reinterpret_cast<const uint2*>(sp + OFF_MISC);
    TL(2, 14, tid == 128);
    const int t0 = 0x7FFF - (top.x & 0x7FFF), t1 = 0x7FFF - (top.y & 0x7FFF);
    auto cand = [&](int second) {
      const int tk = second ? t1 : t0;
      return g_xr + (tk >> 7) * 8 * XR_SIZE + XR_CAND + ((tk >> 4) & 7) * 64 + ((second && (t0 >> 4) == (t1 >> 4)) ? 16 : 0);
    };
    if (ffn) {
      uint4 xb[2];
      poll_chunks(xb, cand(r0 & 1) + (r0 >> 1) * XR_SIZE + 32 + (cw >> 1) * 4 + q4, 4 * XR_SIZE);
      __syncwarp();
      TL(2, 15, tid == 128);
      float d[8][4] = {};
#pragma unroll
      for (int n = 0; n < 32; n++) {
        if (n == 8) { sched_fence(stg); load_wd(1); }
        const int s = (n >> 4) * 4 + ((n >> 1) & 3), m = ((n >> 3) & 1) * 2 + (n & 1);
        const uint32_t* a = wf + 16 * s + 4 * m;
        mma16816(d[n & 7], a[0], a[1], a[2], a[3], (m & 2) ? xb[s >> 2].z : xb[s >> 2].x, (m & 2) ? xb[s >> 2].w : xb[s >> 2].y);
      }
      float v[8];
#pragma unroll
      for (int i = 0; i < 8; i++) {
        const float lo = (q4 & 1) ? d[2 + (i >> 2)][i & 3] : d[i >> 2][i & 3], hi = (q4 & 1) ? d[6 + (i >> 2)][i & 3] : d[4 + (i >> 2)][i & 3];
        v[i] = (q4 & 2) ? hi : lo;
      }
#pragma unroll
      for (int i = 0; i < 4; i++) v[i] = ((q4 & 2) ? v[i + 4] : v[i]) + __shfl_xor_sync(~0u, (q4 & 2) ? v[i] : v[i + 4], 2);
#pragma unroll
      for (int i = 0; i < 2; i++) v[i] = ((q4 & 1) ? v[i + 2] : v[i]) + __shfl_xor_sync(~0u, (q4 & 1) ? v[i] : v[i + 2], 1);
      float4* red = reinterpret_cast<float4*>(sp + SL_SCR * SLOT);
      reinterpret_cast<float2*>(red + cw * 16 + (q4 >> 1) * 8 + r0)[q4 & 1] = make_float2(v[0], v[1]);
      bar_sync(3, 256);
      TL(2, 16, tid == 128);
      const float4 z0 = red[lane], z1 = red[32 + lane], z2 = red[64 + lane], z3 = red[96 + lane];
      const uint32_t ub = pack_bf16((z0.x + z1.x) + (z2.x + z3.x), (z0.y + z1.y) + (z2.y + z3.y));
      const uint32_t gb = pack_bf16((z0.z + z1.z) + (z2.z + z3.z), (z0.w + z1.w) + (z2.w + z3.w));
      const float g0 = bf_lo(gb), g1 = bf_hi(gb);
      const uint32_t sg = pack_bf16(__fdividef(g0, 1.f + __expf(-g0)), __fdividef(g1, 1.f + __expf(-g1)));
      const uint32_t act = pack_bf16(bf_lo(sg) * bf_lo(ub), bf_hi(sg) * bf_hi(ub));
      const uint32_t pr = __byte_perm(act, __shfl_xor_sync(~0u, act, 1), (lane & 1) ? 0x3276 : 0x5410);
      const int src = q4 * 2 + (r0 & 1);
      const uint32_t a0 = __shfl_sync(~0u, pr, src), a1 = __shfl_sync(~0u, pr, src + 8), a2 = __shfl_sync(~0u, pr, src + 16), a3 = __shfl_sync(~0u, pr, src + 24);
      TL(2, 17, tid == 128);
      float y[8][4] = {};
#pragma unroll
      for (int i = 0; i < 8; i++) mma16816(y[i], wd[2 * i][0], wd[2 * i][1], wd[2 * i][2], wd[2 * i][3], a0, a1);
#pragma unroll
      for (int i = 0; i < 8; i++) mma16816(y[i], wd[2 * i + 1][0], wd[2 * i + 1][1], wd[2 * i + 1][2], wd[2 * i + 1][3], a2, a3);
      float2* yd = reinterpret_cast<float2*>(g_xr + (cw * 16 + 2 * q4) * XR_SIZE + XR_Y + fid * 4) + r0;
#pragma unroll
      for (int j = 0; j < 2; j++) {
        float v[4];
#pragma unroll
        for (int e = 0; e < 4; e++) {
          const float lo = (q4 & 1) ? y[4 * j + 1][e] : y[4 * j][e], hi = (q4 & 1) ? y[4 * j + 3][e] : y[4 * j + 2][e];
          v[e] = (q4 & 2) ? hi : lo;
        }
        __stcg(yd + j * 16 * XR_SIZE, make_float2(v[0], v[1]));
        __stcg(yd + j * 16 * XR_SIZE + 2 * XR_SIZE, make_float2(v[2], v[3]));
      }
    }
    TL(2, 18, tid == 128);
    if (rid == 127 && ct < C_NUM) g_cnt[ct] = 0;
    if (cw < 2) {
      const int tok = (lane >> 1) & 1, pair = cw * 2 + (lane & 1);
      idle(ffn ? Y_CLK : Y_CLK + 2000);
      uint4 z[7];
      poll_chunks(z, xr + XR_Y + (lane >> 1) * 4 + pair, 64);
      __syncwarp();
      TL(2, 19, tid == 128);
      mbar_wait_c(B(B_FIN), 0);
      const uint4 op = lds128(sb + OFF_MISC + 128 + (tok * 4 + pair) * 16);
      auto F = [](uint32_t u) { return __uint_as_float(u); };
      const float v0 = ((F(z[0].x) + F(z[1].x)) + (F(z[2].x) + F(z[3].x))) + ((F(z[4].x) + F(z[5].x)) + F(z[6].x));
      const float v1 = ((F(z[0].y) + F(z[1].y)) + (F(z[2].y) + F(z[3].y))) + ((F(z[4].y) + F(z[5].y)) + F(z[6].y));
      const float v2 = ((F(z[0].z) + F(z[1].z)) + (F(z[2].z) + F(z[3].z))) + ((F(z[4].z) + F(z[5].z)) + F(z[6].z));
      const float v3 = ((F(z[0].w) + F(z[1].w)) + (F(z[2].w) + F(z[3].w))) + ((F(z[4].w) + F(z[5].w)) + F(z[6].w));
      float ya = (tok ? v1 : v0) + __shfl_xor_sync(~0u, tok ? v0 : v1, 2), yb = (tok ? v3 : v2) + __shfl_xor_sync(~0u, tok ? v2 : v3, 2);
#pragma unroll
      for (int o = 4; o < 32; o <<= 1) { ya += __shfl_xor_sync(~0u, ya, o); yb += __shfl_xor_sync(~0u, yb, o); }
      const uint32_t yp = pack_bf16(ya, yb);
      if (lane < 4) reinterpret_cast<uint32_t*>(out + (size_t)(tok ? t1 : t0) * DM)[rid * 4 + pair] = hadd2_bf(op.x, hadd2_bf(op.y, pack_bf16(bf_lo(yp) * F(op.z), bf_hi(yp) * F(op.z))));
      TL(2, 21, tid == 128);
    }
    TL(2, 20, tid == 128);
    __syncwarp();
    cluster_wait();
    TL_DUMP();
  }
}

typedef CUresult (*EncodeFn)(CUtensorMap*, CUtensorMapDataType, cuuint32_t, void*, const cuuint64_t*, const cuuint64_t*, const cuuint32_t*,
                             const cuuint32_t*, CUtensorMapInterleave, CUtensorMapSwizzle, CUtensorMapL2promotion, CUtensorMapFloatOOBfill);
EncodeFn g_enc = nullptr;

void map2(CUtensorMap* m, const void* ptr, uint64_t rows, uint64_t cols, uint32_t bc, uint32_t br) {
  const CUtensorMapSwizzle sw = bc == 64 ? CU_TENSOR_MAP_SWIZZLE_128B : CU_TENSOR_MAP_SWIZZLE_64B;
  cuuint64_t gd[2] = {cols, rows}, gs[1] = {cols * 2};
  cuuint32_t bd[2] = {bc, br}, es[2] = {1, 1};
  g_enc(m, CU_TENSOR_MAP_DATA_TYPE_BFLOAT16, 2, (void*)ptr, gd, gs, bd, es, CU_TENSOR_MAP_INTERLEAVE_NONE, sw,
        CU_TENSOR_MAP_L2_PROMOTION_L2_128B, CU_TENSOR_MAP_FLOAT_OOB_FILL_NONE);
}
void map3(CUtensorMap* m, const void* ptr, uint64_t rows, uint64_t cols, uint32_t br, uint32_t bch, uint32_t bc = 64) {
  cuuint64_t gd[3] = {bc, rows, cols / bc}, gs[2] = {cols * 2, bc * 2};
  cuuint32_t bd[3] = {bc, br, bch}, es[3] = {1, 1, 1};
  g_enc(m, CU_TENSOR_MAP_DATA_TYPE_BFLOAT16, 3, (void*)ptr, gd, gs, bd, es, CU_TENSOR_MAP_INTERLEAVE_NONE, bc == 64 ? CU_TENSOR_MAP_SWIZZLE_128B : CU_TENSOR_MAP_SWIZZLE_64B,
        CU_TENSOR_MAP_L2_PROMOTION_L2_128B, CU_TENSOR_MAP_FLOAT_OOB_FILL_NONE);
}

}

extern "C" void kernel_launch(void* const* d_in, const int* in_sizes, int n_in, void* d_out, int out_size) {
  const __nv_bfloat16* x = (const __nv_bfloat16*)d_in[0];
  const __nv_bfloat16* ckv = (const __nv_bfloat16*)d_in[1];
  const __nv_bfloat16* wq = (const __nv_bfloat16*)d_in[2];
  const __nv_bfloat16* wk = (const __nv_bfloat16*)d_in[3];
  const __nv_bfloat16* wv = (const __nv_bfloat16*)d_in[4];
  const __nv_bfloat16* wo = (const __nv_bfloat16*)d_in[5];
  const __nv_bfloat16* w_r = (const __nv_bfloat16*)d_in[7];
  const __nv_bfloat16* wgate = (const __nv_bfloat16*)d_in[8];
  const __nv_bfloat16* wup = (const __nv_bfloat16*)d_in[9];
  const __nv_bfloat16* wdown = (const __nv_bfloat16*)d_in[10];
  __nv_bfloat16* out = (__nv_bfloat16*)d_out;

  if (!g_enc) {
    void* fn = nullptr;
    cudaDriverEntryPointQueryResult qr;
    cudaGetDriverEntryPoint("cuTensorMapEncodeTiled", &fn, cudaEnableDefault, &qr);
    g_enc = (EncodeFn)fn;
    cudaFuncSetAttribute(fused_kernel, cudaFuncAttributeMaxDynamicSharedMemorySize, SMEM_BYTES);
  }
  void *xn, *qkv;
  cudaGetSymbolAddress(&xn, g_xn);
  cudaGetSymbolAddress(&qkv, g_qkv);

  Params p;
  map2(&p.xn, xn, SEQ, DM, 64, 128);
  map2(&p.ckv, ckv, SEQ, DC, 64, 128);
  map3(&p.wq, wq, DM, NQ, 64, 2);
  map3(&p.wk, wk, DC, NQ, 64, 2);
  map3(&p.wv, wv, DC, NQ, 64, 2);
  map3(&p.kv, qkv, 3 * SEQ, NQ, 128, 1);
  map2(&p.ctx_ld, qkv, SEQ, NQ, 64, 128);
  map3(&p.ctx_st, qkv, SEQ, NQ, 64, 1, 32);
  map3(&p.wo, wo, NQ, DM, 64, 1);
  map3(&p.x, x, SEQ, DM, 64, 1);
  map3(&p.wd, wdown, FF, DM, 32, 8);
  map2(&p.out, out, SEQ, DM, 64, 64);
  map2(&p.wg, wgate, DM, FF, 32, 128);
  map2(&p.wu, wup, DM, FF, 32, 128);
  fused_kernel<<<128, 384, SMEM_BYTES, cudaStreamPerThread>>>(x, wq, w_r, out, p);
}
```

```cpp
#include <cuda_runtime.h>
#include <cuda_bf16.h>
#include <cuda.h>
#include <stdint.h>
#include <type_traits>

#pragma nv_diag_suppress 549
namespace {

constexpr int SEQ = 2048, DM = 1024, NH = 32, HD = 128, DC = 512, NQ = NH * HD, FF = 3584;

__device__ __align__(1024) __nv_bfloat16 g_xn[SEQ * DM];
__device__ __align__(1024) __nv_bfloat16 g_qkv[3 * SEQ * NQ];
constexpr int XR_PS = 0;
constexpr int XR_KEY = 128;
constexpr int XR_FLAG = 132;
constexpr int XR_CAND = 136;
constexpr int XR_Y = 648;
constexpr int XR_SIZE = 1104;
__device__ __align__(1024) uint4 g_xr[128 * XR_SIZE];
constexpr int C_LN = 0, C_QKV = 16, C_CTX = 32, C_NUM = 64;
__device__ unsigned g_cnt[C_NUM];

#define TL(k, i, cond) do {} while (0)
#define TL_BYTES 0
#define TL_INIT() do {} while (0)
#define TL_DUMP() do {} while (0)
#define TC(g, i) do {} while (0)
#define TS(i) do {} while (0)
#undef TCLK
#define TCLK 0

__device__ __forceinline__ uint32_t s2u(const void* p) { return (uint32_t)__cvta_generic_to_shared(p); }
__device__ __forceinline__ void mbar_init(uint32_t b, uint32_t c) { asm volatile("mbarrier.init.shared::cta.b64 [%0], %1;" ::"r"(b), "r"(c) : "memory"); }
__device__ __forceinline__ void mbar_expect(uint32_t b, uint32_t bytes) { asm volatile("mbarrier.arrive.expect_tx.shared::cta.b64 _, [%0], %1;" ::"r"(b), "r"(bytes) : "memory"); }
__device__ __forceinline__ void mbar_arrive(uint32_t b) { asm volatile("mbarrier.arrive.shared::cta.b64 _, [%0];" ::"r"(b) : "memory"); }
__device__ __forceinline__ bool mbar_test(uint32_t b, uint32_t ph) {
  uint32_t ok;
  asm volatile("{\n.reg .pred p;\nmbarrier.test_wait.parity.shared::cta.b64 p, [%1], %2;\nselp.u32 %0, 1, 0, p;\n}" : "=r"(ok) : "r"(b), "r"(ph) : "memory");
  return ok;
}
__device__ __forceinline__ void mbar_wait(uint32_t b, uint32_t ph) {
  asm volatile(
      "{\n.reg .pred p;\n.reg .u32 n;\nmov.u32 n, 0;\n"
      "LW:\nmbarrier.try_wait.parity.shared::cta.b64 p, [%0], %1, 20000;\n@p bra LD;\n"
      "add.u32 n, n, 1;\nsetp.lt.u32 p, n, 0x40000;\n@p bra LW;\ntrap;\nLD:\n}" ::"r"(b), "r"(ph) : "memory");
}
__device__ __forceinline__ void mbar_wait_c(uint32_t b, uint32_t ph) {
  asm volatile(
      "{\n.reg .pred p;\n.reg .u32 n;\nmov.u32 n, 0;\n"
      "LW:\nmbarrier.try_wait.parity.shared::cta.b64 p, [%0], %1;\n@p bra LD;\n"
      "add.u32 n, n, 1;\nsetp.lt.u32 p, n, 0x100000;\n@p bra LW;\ntrap;\nLD:\n}" ::"r"(b), "r"(ph) : "memory");
}
__device__ __forceinline__ bool mbar_try(uint32_t b, uint32_t ph) {
  uint32_t ok;
  asm volatile("{\n.reg .pred p;\nmbarrier.try_wait.parity.shared::cta.b64 p, [%1], %2;\nselp.u32 %0, 1, 0, p;\n}" : "=r"(ok) : "r"(b), "r"(ph) : "memory");
  return ok;
}
#define UNLIKELY(c) __builtin_expect(!!(c), 0)
__device__ __forceinline__ uint32_t pinned(uint32_t v) { uint32_t r; asm volatile("mov.b32 %0, %1;" : "=r"(r) : "r"(v)); return r; }
__device__ __forceinline__ bool elect_one() {
  uint32_t p;
  asm volatile("{\n.reg .pred p;\nelect.sync _|p, 0xFFFFFFFF;\nselp.u32 %0, 1, 0, p;\n}" : "=r"(p));
  return p;
}
__device__ __forceinline__ int lane_id() { int r; asm volatile("mov.u32 %0, %%laneid;" : "=r"(r)); return r; }
template <bool SLEEP = false>
__device__ __forceinline__ void spin_until_ge(const unsigned* p, unsigned target) {
  asm volatile(
      "{\n.reg .pred p, q;\n.reg .u32 n, v;\nmov.u32 n, 0;\nsetp.ne.u32 q, %2, 0;\n"
      "LW:\nld.acquire.gpu.global.u32 v, [%0];\nsetp.ge.u32 p, v, %1;\n@p bra LD;\n@q nanosleep.u32 200;\n"
      "add.u32 n, n, 1;\nsetp.lt.u32 p, n, 0x400000;\n@p bra LW;\ntrap;\nLD:\n}" ::"l"(p), "r"(target), "n"((int)SLEEP) : "memory");
}
template <int N>
__device__ __forceinline__ void poll_chunks(uint4 (&v)[N], const uint4* p, int stride) {
  uint32_t m[N];
#pragma unroll
  for (int i = 0; i < N; i++) { m[i] = ~0u; v[i] = make_uint4(0, 0, 0, 0); }
#pragma unroll 1
  for (int n = 0; n < 0x400000; n++) {
    uint32_t a = 0;
#pragma unroll
    for (int i = 0; i < N; i++)
      asm volatile("{\n.reg .pred p;\nsetp.eq.u32 p, %5, 0xFFFFFFFF;\n@p ld.relaxed.gpu.global.v4.u32 {%0,%1,%2,%3}, [%4];\n}"
                   : "+r"(v[i].x), "+r"(v[i].y), "+r"(v[i].z), "+r"(v[i].w) : "l"(p + i * stride), "r"(m[i]) : "memory");
#pragma unroll
    for (int i = 0; i < N; i++) { m[i] = max(max(v[i].x, v[i].y), max(v[i].z, v[i].w)); a = max(a, m[i]); }
    if (__all_sync(~0u, a != 0xFFFFFFFFu)) break;
  }
}
__device__ __forceinline__ void fence_async_all() { asm volatile("fence.proxy.async;" ::: "memory"); }
__device__ __forceinline__ void bar_sync(int id, int n) { asm volatile("bar.sync %0, %1;" ::"r"(id), "r"(n) : "memory"); }
__device__ __forceinline__ void bar_arrive(int id, int n) { asm volatile("bar.arrive %0, %1;" ::"r"(id), "r"(n) : "memory"); }
__device__ __forceinline__ void cluster_arrive() { asm volatile("barrier.cluster.arrive.relaxed.aligned;" ::: "memory"); }
__device__ __forceinline__ void cluster_wait() { asm volatile("barrier.cluster.wait.acquire.aligned;" ::: "memory"); }
__device__ __forceinline__ void fence_gpu() { asm volatile("fence.acq_rel.gpu;" ::: "memory"); }
__device__ __forceinline__ void red_add(unsigned* p, unsigned v) { asm volatile("red.relaxed.gpu.global.add.u32 [%0], %1;" ::"l"(p), "r"(v) : "memory"); }
__device__ __forceinline__ void prefetch_tm(const CUtensorMap* m) { asm volatile("prefetch.tensormap [%0];" ::"l"(m) : "memory"); }

constexpr uint64_t EV_N = 0x1000000000000000ull, EV_F = 0x12F0000000000000ull;
__device__ __forceinline__ void tma_ld2(uint32_t dst, const CUtensorMap* m, uint32_t bar, int c0, int c1, bool ef = false) {
  asm volatile("cp.async.bulk.tensor.2d.shared::cta.global.mbarrier::complete_tx::bytes.L2::cache_hint [%0], [%1, {%3,%4}], [%2], %5;" ::"r"(dst), "l"(m), "r"(bar), "r"(c0), "r"(c1), "l"(ef ? EV_F : EV_N) : "memory");
}
__device__ __forceinline__ void tma_ld3(uint32_t dst, const CUtensorMap* m, uint32_t bar, int c0, int c1, int c2, bool ef = false) {
  asm volatile("cp.async.bulk.tensor.3d.shared::cta.global.mbarrier::complete_tx::bytes.L2::cache_hint [%0], [%1, {%3,%4,%5}], [%2], %6;" ::"r"(dst), "l"(m), "r"(bar), "r"(c0), "r"(c1), "r"(c2), "l"(ef ? EV_F : EV_N) : "memory");
}
__device__ __forceinline__ void tma_ld3_mc(uint32_t dst, const CUtensorMap* m, uint32_t bar, int c0, int c1, int c2, uint16_t mask, bool ef = false) {
  asm volatile("cp.async.bulk.tensor.3d.shared::cluster.global.mbarrier::complete_tx::bytes.multicast::cluster.L2::cache_hint [%0], [%1, {%3,%4,%5}], [%2], %6, %7;" ::"r"(dst), "l"(m), "r"(bar), "r"(c0), "r"(c1), "r"(c2), "h"(mask), "l"(ef ? EV_F : EV_N) : "memory");
}
__device__ __forceinline__ void tma_pf3(const CUtensorMap* m, int c0, int c1, int c2) {
  asm volatile("cp.async.bulk.prefetch.tensor.3d.L2.global [%0, {%1,%2,%3}];" ::"l"(m), "r"(c0), "r"(c1), "r"(c2) : "memory");
}
__device__ __forceinline__ void l2_prefetch(const void* p, uint32_t bytes) { asm volatile("cp.async.bulk.prefetch.L2.global [%0], %1;" ::"l"(p), "r"(bytes) : "memory"); }

__device__ __forceinline__ void wg_fence() { asm volatile("wgmma.fence.sync.aligned;" ::: "memory"); }
__device__ __forceinline__ void wg_commit() { asm volatile("wgmma.commit_group.sync.aligned;" ::: "memory"); }
template <int N> __device__ __forceinline__ void wg_wait() { asm volatile("wgmma.wait_group.sync.aligned %0;" ::"n"(N) : "memory"); }
template <int N> __device__ __forceinline__ void reg_alloc() { asm volatile("setmaxnreg.inc.sync.aligned.u32 %0;" ::"n"(N)); }
template <int N> __device__ __forceinline__ void reg_dealloc() { asm volatile("setmaxnreg.dec.sync.aligned.u32 %0;" ::"n"(N)); }
template <int N> __device__ __forceinline__ void fence_regs(float* d) {
#pragma unroll
  for (int i = 0; i < N; i++) asm volatile("" : "+f"(d[i])::"memory");
}
template <int N> __device__ __forceinline__ void fence_regs(uint32_t* d) {
#pragma unroll
  for (int i = 0; i < N; i++) asm volatile("" : "+r"(d[i])::"memory");
}

__device__ __forceinline__ uint64_t mk_desc(uint32_t addr, uint32_t lbo, uint32_t sbo, uint32_t swz) {
  uint32_t lo = ((addr & 0x3FFFF) >> 4) | ((lbo >> 4) << 16);
  uint32_t hi = (sbo >> 4) | (swz << 30);
  return ((uint64_t)hi << 32) | lo;
}
__device__ __forceinline__ uint64_t desc_add(uint64_t d, uint32_t bytes) {
  uint32_t lo = (uint32_t)d + (bytes >> 4);
  return (d & 0xFFFFFFFF00000000ull) | lo;
}

#define R8(b) "+f"(d[b + 0]), "+f"(d[b + 1]), "+f"(d[b + 2]), "+f"(d[b + 3]), "+f"(d[b + 4]), "+f"(d[b + 5]), "+f"(d[b + 6]), "+f"(d[b + 7])
#define REGS32 "%0,%1,%2,%3,%4,%5,%6,%7,%8,%9,%10,%11,%12,%13,%14,%15,%16,%17,%18,%19,%20,%21,%22,%23,%24,%25,%26,%27,%28,%29,%30,%31"
#define REGS64 REGS32 ",%32,%33,%34,%35,%36,%37,%38,%39,%40,%41,%42,%43,%44,%45,%46,%47,%48,%49,%50,%51,%52,%53,%54,%55,%56,%57,%58,%59,%60,%61,%62,%63"
#define REGS128 REGS64 ",%64,%65,%66,%67,%68,%69,%70,%71,%72,%73,%74,%75,%76,%77,%78,%79,%80,%81,%82,%83,%84,%85,%86,%87,%88,%89,%90,%91,%92,%93,%94,%95," \
               "%96,%97,%98,%99,%100,%101,%102,%103,%104,%105,%106,%107,%108,%109,%110,%111,%112,%113,%114,%115,%116,%117,%118,%119,%120,%121,%122,%123,%124,%125,%126,%127"

template <int TB>
__device__ __forceinline__ void mma_n256_ss(float (&d)[128], uint64_t a, uint64_t b, int acc) {
  asm volatile("{\n.reg .pred p;\nsetp.ne.b32 p, %130, 0;\n"
               "wgmma.mma_async.sync.aligned.m64n256k16.f32.bf16.bf16 {" REGS128 "}, %128, %129, p, 1, 1, 0, %131;\n}\n"
               : R8(0), R8(8), R8(16), R8(24), R8(32), R8(40), R8(48), R8(56), R8(64), R8(72), R8(80), R8(88), R8(96), R8(104), R8(112), R8(120)
               : "l"(a), "l"(b), "r"(acc), "n"(TB));
}
template <int TB>
__device__ __forceinline__ void mma_n128_ss(float* d, uint64_t a, uint64_t b, int acc) {
  asm volatile("{\n.reg .pred p;\nsetp.ne.b32 p, %66, 0;\n"
               "wgmma.mma_async.sync.aligned.m64n128k16.f32.bf16.bf16 {" REGS64 "}, %64, %65, p, 1, 1, 0, %67;\n}\n"
               : R8(0), R8(8), R8(16), R8(24), R8(32), R8(40), R8(48), R8(56)
               : "l"(a), "l"(b), "r"(acc), "n"(TB));
}
template <int TB>
__device__ __forceinline__ void mma_n128_rs(float* d, const uint32_t* a, uint64_t b, int acc) {
  asm volatile("{\n.reg .pred p;\nsetp.ne.b32 p, %69, 0;\n"
               "wgmma.mma_async.sync.aligned.m64n128k16.f32.bf16.bf16 {" REGS64 "}, {%64,%65,%66,%67}, %68, p, 1, 1, %70;\n}\n"
               : R8(0), R8(8), R8(16), R8(24), R8(32), R8(40), R8(48), R8(56)
               : "r"(a[0]), "r"(a[1]), "r"(a[2]), "r"(a[3]), "l"(b), "r"(acc), "n"(TB));
}
__device__ __forceinline__ void mma_n64_rs(float* d, const uint32_t* a, uint64_t b, int acc) {
  asm volatile("{\n.reg .pred p;\nsetp.ne.b32 p, %37, 0;\n"
               "wgmma.mma_async.sync.aligned.m64n64k16.f32.bf16.bf16 {" REGS32 "}, {%32,%33,%34,%35}, %36, p, 1, 1, 0;\n}\n"
               : R8(0), R8(8), R8(16), R8(24)
               : "r"(a[0]), "r"(a[1]), "r"(a[2]), "r"(a[3]), "l"(b), "r"(acc));
}
#define W8(b) "=f"(d[b + 0]), "=f"(d[b + 1]), "=f"(d[b + 2]), "=f"(d[b + 3]), "=f"(d[b + 4]), "=f"(d[b + 5]), "=f"(d[b + 6]), "=f"(d[b + 7])
__device__ __forceinline__ void mma_n128_rs0(float* d, const uint32_t* a, uint64_t b) {
  asm volatile("wgmma.mma_async.sync.aligned.m64n128k16.f32.bf16.bf16 {" REGS64 "}, {%64,%65,%66,%67}, %68, 0, 1, 1, 0;\n"
               : W8(0), W8(8), W8(16), W8(24), W8(32), W8(40), W8(48), W8(56)
               : "r"(a[0]), "r"(a[1]), "r"(a[2]), "r"(a[3]), "l"(b));
}
__device__ __forceinline__ void mma_n64_rs0(float* d, const uint32_t* a, uint64_t b) {
  asm volatile("wgmma.mma_async.sync.aligned.m64n64k16.f32.bf16.bf16 {" REGS32 "}, {%32,%33,%34,%35}, %36, 0, 1, 1, 0;\n"
               : W8(0), W8(8), W8(16), W8(24)
               : "r"(a[0]), "r"(a[1]), "r"(a[2]), "r"(a[3]), "l"(b));
}
__device__ __forceinline__ uint32_t pack_bf16(float lo, float hi) {
  uint32_t r;
  asm("cvt.rn.bf16x2.f32 %0, %1, %2;" : "=r"(r) : "f"(hi), "f"(lo));
  return r;
}
__device__ __forceinline__ float bf_lo(uint32_t v) { return __uint_as_float(v << 16); }
__device__ __forceinline__ float bf_hi(uint32_t v) { return __uint_as_float(v & 0xFFFF0000u); }
__device__ __forceinline__ float bf_round(float v) { return bf_lo(pack_bf16(v, v)); }
__device__ __forceinline__ void stsm4(uint32_t addr, uint32_t r0, uint32_t r1, uint32_t r2, uint32_t r3) {
  asm volatile("stmatrix.sync.aligned.m8n8.x4.shared.b16 [%0], {%1,%2,%3,%4};" ::"r"(addr), "r"(r0), "r"(r1), "r"(r2), "r"(r3) : "memory");
}
__device__ __forceinline__ uint4 lds128(uint32_t addr) {
  uint4 v;
  asm volatile("ld.shared.v4.u32 {%0,%1,%2,%3}, [%4];" : "=r"(v.x), "=r"(v.y), "=r"(v.z), "=r"(v.w) : "r"(addr));
  return v;
}
__device__ __forceinline__ float ex2(float x) {
  float y;
  asm("ex2.approx.ftz.f32 %0, %1;" : "=f"(y) : "f"(x));
  return y;
}
__device__ __forceinline__ void pin_order(float v, uint32_t dummy) {
  asm volatile("{\n.reg .pred p;\nsetp.eq.b32 p, %0, 0xFFFFFFFF;\n@p st.shared.b32 [%1], %0;\n}" ::"r"(__float_as_uint(v)), "r"(dummy) : "memory");
}
__device__ __forceinline__ float sigmoid(float x) {
  float y;
  asm("rcp.approx.ftz.f32 %0, %1;" : "=f"(y) : "f"(1.f + ex2(x * -1.4426950408889634f)));
  return y;
}
__device__ __forceinline__ void sched_fence(uint32_t dummy) {
  asm volatile("{\n.reg .pred p;\n.reg .u32 c;\nsetp.eq.b32 p, %0, 0xFFFFFFFF;\nmov.u32 c, %%clock;\n@p st.shared.b32 [%0], c;\n}" ::"r"(dummy) : "memory");
}
__device__ __forceinline__ void idle(int n) {
  asm volatile("{\n.reg .pred p;\n.reg .u32 a, b;\nmov.u32 a, %%clock;\nLI:\nmov.u32 b, %%clock;\nsub.u32 b, b, a;\nsetp.lt.u32 p, b, %0;\n@p bra LI;\n}" ::"r"(n) : "memory");
}
__device__ __forceinline__ void stage_store_128(uint32_t base, int lane, const uint32_t* pk) {
  const int row = (lane & 7) + ((lane >> 3) & 1) * 8;
  const uint32_t rb = base + row * 128;
  const int hi = lane >> 4;
#pragma unroll
  for (int j = 0; j < 8; j++) {
    const int chunk = 2 * j + hi;
    const uint32_t a = rb + (j >> 2) * 8192 + (((chunk & 7) ^ (lane & 7)) << 4);
    stsm4(a, pk[4 * j + 0], pk[4 * j + 1], pk[4 * j + 2], pk[4 * j + 3]);
  }
}
__device__ __forceinline__ void ln_round(float mean, float var, float& m_bf, float& inv_s) {
  const uint32_t mv = pack_bf16(mean, var);
  m_bf = bf_lo(mv);
  float sq, rc;
  asm("sqrt.approx.ftz.f32 %0, %1;" : "=f"(sq) : "f"(bf_round(bf_hi(mv) + 1e-5f)));
  asm("rcp.approx.ftz.f32 %0, %1;" : "=f"(rc) : "f"(bf_round(sq)));
  inv_s = rc;
}
__device__ __forceinline__ uint32_t hadd2_bf(uint32_t a, uint32_t b) {
  uint32_t r;
  asm("add.rn.bf16x2 %0, %1, %2;" : "=r"(r) : "r"(a), "r"(b));
  return r;
}
__device__ __forceinline__ uint32_t ln_apply(uint32_t h, uint32_t nm2, float inv_s) {
  const uint32_t d = hadd2_bf(h, nm2);
  return pack_bf16(bf_lo(d) * inv_s, bf_hi(d) * inv_s);
}
__device__ __forceinline__ void ldsm4(uint32_t* r, uint32_t addr) {
  asm volatile("ldmatrix.sync.aligned.m8n8.x4.shared.b16 {%0,%1,%2,%3}, [%4];" : "=r"(r[0]), "=r"(r[1]), "=r"(r[2]), "=r"(r[3]) : "r"(addr) : "memory");
}
__device__ __forceinline__ void mma16816(float* d, uint32_t a0, uint32_t a1, uint32_t a2, uint32_t a3, uint32_t b0, uint32_t b1) {
  asm volatile("mma.sync.aligned.m16n8k16.row.col.f32.bf16.bf16.f32 {%0,%1,%2,%3}, {%4,%5,%6,%7}, {%8,%9}, {%0,%1,%2,%3};"
               : "+f"(d[0]), "+f"(d[1]), "+f"(d[2]), "+f"(d[3]) : "r"(a0), "r"(a1), "r"(a2), "r"(a3), "r"(b0), "r"(b1));
}

template <class F>
__device__ __forceinline__ void unroll8(F f) {
  f(std::integral_constant<int, 0>{}); f(std::integral_constant<int, 1>{}); f(std::integral_constant<int, 2>{}); f(std::integral_constant<int, 3>{});
  f(std::integral_constant<int, 4>{}); f(std::integral_constant<int, 5>{}); f(std::integral_constant<int, 6>{}); f(std::integral_constant<int, 7>{});
}

constexpr float AT_C = 0.08838834764831845f * 1.4426950408889634f;
constexpr float AT_LO = 0x1p-40f, AT_HI = 0x1p40f;
constexpr int AT_R1 = 48;
template <int I0, int I1>
__device__ __forceinline__ void at_exp(float* S) {
#pragma unroll
  for (int i = I0; i < I1; i++) asm volatile("ex2.approx.ftz.f32 %0, %0;" : "+f"(S[i]));
}
template <int I0, int I1>
__device__ __forceinline__ void at_fin(const float* S, uint32_t* P) {
#pragma unroll
  for (int i = I0; i < I1; i += 4) {
    P[i / 2] = pack_bf16(S[i], S[i + 1]); P[i / 2 + 1] = pack_bf16(S[i + 2], S[i + 3]);
  }
}
__device__ __forceinline__ void at_sum(const uint32_t* P, bool half, float& l0, float& l1) {
  uint32_t u[4];
#pragma unroll
  for (int r = 0; r < 4; r++) {
    const uint32_t* q = P + (r >> 1) * 16 + (r & 1);
    u[r] = hadd2_bf(hadd2_bf(hadd2_bf(q[0], q[2]), hadd2_bf(q[4], q[6])), hadd2_bf(hadd2_bf(q[8], q[10]), hadd2_bf(q[12], q[14])));
  }
  u[0] = hadd2_bf(u[0], half ? 0u : u[2]);
  u[1] = hadd2_bf(u[1], half ? 0u : u[3]);
  l0 += bf_lo(u[0]) + bf_hi(u[0]);
  l1 += bf_lo(u[1]) + bf_hi(u[1]);
}
template <int j>
__device__ __forceinline__ void at_mask1(float* S, int d) {
  float dummy0 = 0.f, dummy1 = 0.f;
  float& lo0 = j < 7 ? S[4 * (j < 7 ? j + 1 : j) + 2] : dummy0;
  float& lo1 = j < 7 ? S[4 * (j < 7 ? j + 1 : j) + 3] : dummy1;
  asm("{\n.reg .pred p, q;\nsetp.lt.s32 p, %4, %5;\nsetp.le.s32 q, %4, %5;\n"
      "@p add.f32 %0, %0, 0fFF800000;\n@q add.f32 %1, %1, 0fFF800000;\n@p add.f32 %2, %2, 0fFF800000;\n@q add.f32 %3, %3, 0fFF800000;\n}"
      : "+f"(S[4 * j]), "+f"(S[4 * j + 1]), "+f"(lo0), "+f"(lo1) : "r"(d), "r"(8 * j));
}
__device__ __forceinline__ void at_mask(float* S, int r, int lane) {
  unroll8([&](auto jc) { at_mask1<decltype(jc)::value>(S, r + (lane >> 2) - (lane & 3) * 2); });
}
__device__ __forceinline__ uint32_t ldg32(const __nv_bfloat16* p) { return __ldcg(reinterpret_cast<const uint32_t*>(p)); }
__device__ __forceinline__ uint32_t ldg16x2(const __nv_bfloat16* p, int stride) {
  return (uint32_t)__ldcg(reinterpret_cast<const unsigned short*>(p)) | ((uint32_t)__ldcg(reinterpret_cast<const unsigned short*>(p + stride)) << 16);
}
__device__ __forceinline__ void slow_tile(float* O, uint32_t* Q, float& l0, float& l1, const __nv_bfloat16* wq, int row0, int head, int lane, uint32_t dummy) {
  const int r = lane >> 2, q = lane & 3;
#pragma unroll
  for (int i = 0; i < 64; i++) O[i] = 0.f;
  {
    const __nv_bfloat16* xa = g_xn + (size_t)(row0 + r) * DM + 2 * q;
    const __nv_bfloat16* wb = wq + (size_t)(2 * q) * NQ + head * HD + (r >> 1) * 8 + (r & 1);
#pragma unroll 1
    for (int k = 0; k < DM; k += 16) {
      const uint32_t a0 = ldg32(xa + k), a1 = ldg32(xa + k + 8 * DM), a2 = ldg32(xa + k + 8), a3 = ldg32(xa + k + 8 * DM + 8);
#pragma unroll
      for (int j = 0; j < 16; j++) {
        const __nv_bfloat16* wp = wb + (size_t)k * NQ + (j >> 2) * 32 + (j & 3) * 2;
        mma16816(O + 4 * j, a0, a1, a2, a3, ldg16x2(wp, NQ), ldg16x2(wp + 8 * NQ, NQ));
        if (j == 7) sched_fence(dummy);
      }
    }
  }
#pragma unroll
  for (int i = 0; i < 32; i++) Q[i] = pack_bf16(O[2 * i], O[2 * i + 1]);
#pragma unroll
  for (int i = 0; i < 64; i++) O[i] = 0.f;
  float m0 = -INFINITY, m1 = -INFINITY;
  l0 = l1 = 0.f;
#pragma unroll 1
  for (int kv = 0; kv <= row0; kv += 16) {
    float s[8] = {0.f, 0.f, 0.f, 0.f, 0.f, 0.f, 0.f, 0.f};
    const __nv_bfloat16* kp = g_qkv + (size_t)(SEQ + kv + r) * NQ + head * HD + 2 * q;
#pragma unroll
    for (int k = 0; k < 8; k++) {
      mma16816(s, Q[4 * k], Q[4 * k + 1], Q[4 * k + 2], Q[4 * k + 3], ldg32(kp + 16 * k), ldg32(kp + 16 * k + 8));
      mma16816(s + 4, Q[4 * k], Q[4 * k + 1], Q[4 * k + 2], Q[4 * k + 3], ldg32(kp + 8 * NQ + 16 * k), ldg32(kp + 8 * NQ + 16 * k + 8));
    }
#pragma unroll
    for (int i = 0; i < 8; i++)
      if (kv + (i >> 2) * 8 + 2 * q + (i & 1) > row0 + r + (i & 2) * 4) s[i] = -INFINITY;
    float a = fmaxf(fmaxf(fmaxf(s[0], s[1]), fmaxf(s[4], s[5])), m0), b = fmaxf(fmaxf(fmaxf(s[2], s[3]), fmaxf(s[6], s[7])), m1);
    a = fmaxf(a, __shfl_xor_sync(~0u, a, 1)); b = fmaxf(b, __shfl_xor_sync(~0u, b, 1));
    a = fmaxf(a, __shfl_xor_sync(~0u, a, 2)); b = fmaxf(b, __shfl_xor_sync(~0u, b, 2));
    const float c0 = ex2(m0 - a), c1 = ex2(m1 - b);
    m0 = a; m1 = b;
#pragma unroll
    for (int i = 0; i < 8; i++) s[i] = ex2(s[i] - ((i & 2) ? b : a));
    l0 = l0 * c0 + (s[0] + s[1]) + (s[4] + s[5]);
    l1 = l1 * c1 + (s[2] + s[3]) + (s[6] + s[7]);
    sched_fence(dummy);
    const uint32_t p0 = pack_bf16(s[0], s[1]), p1 = pack_bf16(s[2], s[3]), p2 = pack_bf16(s[4], s[5]), p3 = pack_bf16(s[6], s[7]);
    const __nv_bfloat16* vp = g_qkv + (size_t)(2 * SEQ + kv + 2 * q) * NQ + head * HD + r;
#pragma unroll
    for (int j = 0; j < 16; j++) {
      O[4 * j] *= c0; O[4 * j + 1] *= c0; O[4 * j + 2] *= c1; O[4 * j + 3] *= c1;
      mma16816(O + 4 * j, p0, p1, p2, p3, ldg16x2(vp + 8 * j, NQ), ldg16x2(vp + 8 * NQ + 8 * j, NQ));
      if (j == 7) sched_fence(dummy);
    }
  }
}

constexpr int P1_STAGE = 49152;
constexpr int SLOT = 32768;
constexpr int OFF_LN = 6 * SLOT, OFF_R3 = 0;
constexpr int OFF_BAR = 229376;
constexpr int OFF_MISC = OFF_BAR + 8 * 58;
constexpr int SMEM_BYTES = OFF_MISC + 2080 + TL_BYTES;
enum : int {
  B_FULL1 = 0, B_KF = 4, B_VF = 6, B_FULL3 = 8, B_XF = 14, B_LN = 15, B_DEP = 16, B_OUT2 = 22, B_FIN = 23, B_SET2 = 25, B_QP = 26, B_WF2 = 29,
  B_WF = 30, B_WR = 31,
  B_LND = 32,
  B_XE = 33, B_PUB = 34, B_OUT = 40, B_OUT3 = 41,
  B_EMPTY1 = 42, B_KE = 46, B_VE = 48, B_EMPTY3 = 50, B_WE = 56, B_NUM = 57
};
constexpr int OFF_STG = SLOT, SL_SCR = 2;
constexpr int PRE = 3;
constexpr int LN_PF = 4, LN_PFN = 2, LN_LD = 9;
constexpr int WQ_0 = 18, WQ_D = 4;
constexpr int W_G0 = 22;
constexpr int X_KB = 20, G_KB = 35;
constexpr int SL_NS = 600, SET_NS = 50;
constexpr int OUT_CLK = 500, Y_CLK = 400;
struct Params {
  CUtensorMap xn, ckv, wq, wk, wv, kv, ctx_ld, ctx_st, wo, x, wd, wg, wu, out;
};

__global__ void __cluster_dims__(2, 1, 1) __launch_bounds__(384, 1)
fused_kernel(const __nv_bfloat16* __restrict__ x, const __nv_bfloat16* __restrict__ wq, const __nv_bfloat16* __restrict__ w_r,
             __nv_bfloat16* __restrict__ out, const __grid_constant__ Params p) {
  extern __shared__ __align__(1024) uint8_t sp[];
  const uint32_t sb = s2u(sp);
  const uint32_t bar = sb + OFF_BAR;
  auto B = [&](int i) { return bar + 8 * i; };
  const int tid = threadIdx.x, warp = __shfl_sync(~0u, tid >> 5, 0), wg = warp >> 2, lane = tid & 31;
  const int cta = blockIdx.x, rank = cta & 1, cl = cta >> 1;
  const int mp = cl < 4 ? 1 : (cl < 36 ? (cl & 7) : (0x3207654 >> (4 * ((cl - 36) % 7))) & 7);
  const int gq = cl < 4 ? 4 + cl : (cl < 36 ? (cl - 4) >> 3 : 4 + (cl - 36) / 7);
  const int mt = 2 * mp + rank;
  const int ti = (gq & 3) * 2 + rank, hh = mp * 2 + (gq >> 2);
  const int rid = mt * 8 + gq;
  const int fid = mt * 7 + gq;
  const bool ffn = gq < 7;
  uint4* const xr = g_xr + rid * XR_SIZE;
  TL_INIT();
  TL(0, 0, tid == 128);
  if (warp == 0) {
    if (elect_one()) {
#pragma unroll
      for (int kb = 0; kb < PRE; kb++) mbar_init(B(B_FULL1 + kb), 1);
      asm volatile("fence.mbarrier_init.release.cluster;" ::: "memory");
    }
    __syncwarp();
    cluster_arrive();
    if (elect_one()) {
#pragma unroll
      for (int kb = 0; kb < PRE; kb++) {
        mbar_expect(B(B_FULL1 + kb), P1_STAGE);
        tma_ld2(sb + kb * P1_STAGE, &p.ckv, B(B_FULL1 + kb), kb * 64, mt * 128);
        tma_ld3(sb + kb * P1_STAGE + 16384 + rank * 16384, &p.wk, B(B_FULL1 + kb), 0, kb * 64, gq * 4 + rank * 2);
        tma_ld3(sb + kb * P1_STAGE + 32768 - rank * 16384, &p.wk, B(B_FULL1 + kb), 0, kb * 64, gq * 4 + 2 - rank * 2);
      }
    }
  } else if (elect_one()) {
#pragma unroll 1
    for (int i = PRE + warp - 1; i < B_NUM; i += 11)
      mbar_init(B(i), i >= B_EMPTY1 ? 16 : (i >= B_XE ? 8 : (i == B_LND ? 3 : (i >= B_WF ? 2 : 1))));
    asm volatile("fence.mbarrier_init.release.cluster;" ::: "memory");
  }
  __syncwarp();
  if (warp) cluster_arrive();
  if (wg == 0) {
    reg_dealloc<40>();
    if (warp == 1 && elect_one()) {
      if (mt >= 2 * PRE) tma_pf3(&p.wk, 0, mp * 64, gq * 4 + rank * 2);
      if (gq >= PRE) asm volatile("cp.async.bulk.prefetch.tensor.2d.L2.global [%0, {%1,%2}];" ::"l"(&p.ckv), "r"(gq * 64), "r"(mt * 128) : "memory");
    } else if (warp == 2 && elect_one()) {
      prefetch_tm(&p.wv); prefetch_tm(&p.wq); prefetch_tm(&p.xn);
    }
    __syncwarp();
    cluster_wait();
    if (warp == 0) {
      int st = 0; uint32_t ph = 1;
#pragma unroll 1
      for (int t = 0; t < 6; t++) {
        const CUtensorMap* ma = t >= 4 ? &p.xn : &p.ckv;
        const CUtensorMap* mb = t >= 4 ? &p.wq : ((t & 1) ? &p.wv : &p.wk);
        const int nk = t >= 4 ? 16 : 8;
        const int row = (t < 4 ? mt : (t == 4 ? 15 - ti : ti)) * 128;
        const int col = t < 4 ? (gq + (t >> 1) * 8) * 4 + rank * 2 : (hh + rank * 16) * 2;
        if (t >= 4) mbar_wait(B(B_DEP + t - 4), 0);
#pragma unroll 1
        for (int kb = 0; kb < nk; kb++) {
          const uint32_t d = sb + st * P1_STAGE, fb = B(B_FULL1 + st);
          const int n = t * 8 + kb;
          if (n >= PRE) {
            mbar_wait_c(B(B_EMPTY1 + st), ph);
            if (elect_one()) {
              mbar_expect(fb, P1_STAGE);
              tma_ld2(d, ma, fb, kb * 64, row);
              tma_ld3_mc(d + 16384 + rank * 16384, mb, fb, 0, kb * 64, col, 3);
            }
          }
          if (t < 5 && elect_one()) {
            if (n >= LN_PF && n < LN_PF + LN_PFN) l2_prefetch(x + (size_t)cta * 16 * DM + (n - LN_PF) * (16 * DM / LN_PFN), 32768 / LN_PFN);
            if (n == LN_LD) {
              mbar_expect(B(B_LN), 32768);
              asm volatile("cp.async.bulk.shared::cluster.global.mbarrier::complete_tx::bytes [%0], [%1], %2, [%3];" ::"r"(sb + OFF_LN),
                           "l"(x + (size_t)cta * 16 * DM), "r"(32768), "r"(B(B_LN)) : "memory");
            }
            if (t < 3 && kb == 0) tma_pf3((t & 1) ? &p.wk : &p.wv, 0, mp * 64, (gq + ((t + 1) >> 1) * 8) * 4 + rank * 2);
            if (n >= WQ_0 && n < WQ_0 + 4 * WQ_D && (n - WQ_0) % WQ_D == 0) tma_pf3(&p.wq, 0, ((n - WQ_0) / WQ_D * 4 + (gq & 3)) * 64, (hh + rank * 16) * 2);
          }
          if (++st == 4) { st = 0; ph ^= 1; }
        }
      }
      if (elect_one()) { prefetch_tm(&p.kv); prefetch_tm(&p.ctx_ld); prefetch_tm(&p.wo); prefetch_tm(&p.wg); prefetch_tm(&p.wu); }
      auto load_kv = [&](int g, int isv) {
        const int h2 = g >= 17, sx = g - 17 * h2, n1 = h2 ? ti + 1 : 16 - ti;
        const int row = (1 + isv) * SEQ + (sx < n1 ? sx : 16 - sx) * 128, col = (hh + 16 * h2) * 2;
        const uint32_t d = sb + (isv ? 2 + 2 * (g & 1) : (g & 1)) * SLOT, fb = B(B_KF + 2 * isv + (g & 1));
        const bool ef = sx >= n1 || sx >= 8;
        const bool shared = sx != (h2 ? (ti & 6) + 1 : 15 - (ti & 6));
        const int h3 = g >= 16, s3 = g + 1 - 17 * h3;
        const int pb = ti < 2 ? (h3 ? (s3 >= 1 && s3 <= 8 ? 16 - s3 : -1) : (s3 < 16 ? s3 : -1)) : (ti >= 6 && h3 && s3 < 8 ? s3 : -1);
        mbar_wait_c(g < 2 ? B(B_EMPTY1 + (isv ? 1 + 2 * g : g)) : B(B_KE + 2 * isv + (g & 1)), g < 2 ? 1 : ((g >> 1) & 1) ^ 1);
        if (elect_one()) {
          mbar_expect(fb, SLOT);
          if (shared) {
            tma_ld3_mc(d + rank * 16384, &p.kv, fb, 0, row, col + rank, 3, ef);
          } else {
            tma_ld3(d, &p.kv, fb, 0, row, col, ef);
            tma_ld3(d + 16384, &p.kv, fb, 0, row, col + 1, ef);
          }
          if (pb >= 0) tma_pf3(&p.kv, 0, (1 + isv) * SEQ + pb * 128, (hh + 16 * h3) * 2 + rank);
        }
      };
      int nw = ffn ? 0 : 12;
      auto load_w = [&]() {
        const int c = nw < 8 ? (nw >> 2) + (nw & 2) : nw >> 1;
        if (elect_one()) {
          if (!(nw & 3)) mbar_expect(B(B_WF - (nw >> 3)), 32768);
          tma_ld2(sb + (c < 2 ? 3 : 4) * SLOT + c * 16384 + (nw & 1) * 8192, (nw & 1) ? &p.wg : &p.wu, B(B_WF - (nw >> 3)), fid * 32, c * 128, true);
        }
        nw++;
      };
#pragma unroll 1
      for (int g = 0; g < 34; g++) {
        if (g == 0 || g == 16) mbar_wait(B(B_DEP + 2 + (g > 0)), 0);
        load_kv(g, 0);
        if (g > 0) load_kv(g - 1, 1);
        if (g >= W_G0 && nw < 12 && __any_sync(~0u, mbar_test(B(B_QP + (nw >> 2)), 0))) load_w();
      }
      load_kv(33, 1);
#pragma unroll 1
      while (nw < 12) { mbar_wait(B(B_QP + (nw >> 2)), 0); load_w(); }
      if (elect_one()) { prefetch_tm(&p.wd); prefetch_tm(&p.x); prefetch_tm(&p.out); }
      auto load3 = [&](int kb, int sl) {
        if (elect_one()) {
          mbar_expect(B(B_FULL3 + sl), SLOT);
          tma_ld2(sb + OFF_R3 + sl * SLOT, &p.ctx_ld, B(B_FULL3 + sl), kb * 64, mt * 128);
          tma_ld3_mc(sb + OFF_R3 + sl * SLOT + 16384 + rank * 8192, &p.wo, B(B_FULL3 + sl), 0, kb * 64, gq * 2 + rank, 3);
        }
      };
      mbar_wait(B(B_DEP + 4), 0);
#pragma unroll
      for (int kb = 0; kb < 5; kb++) {
        mbar_wait_c(B(kb == 3 ? B_WE : (kb == 4 ? B_VE + 1 : B_KE + kb)), 0);
        load3(kb, kb);
      }
      if (elect_one()) mbar_arrive(B(B_FULL3 + 5));
#pragma unroll 1
      for (int r = 1; r < 11; r++) {
#pragma unroll
        for (int j = 0; j < 6; j++) {
          if (j == 5 && r == 10) break;
          if (j == 3 && r == 5) mbar_wait(B(B_DEP + 5), 0);
          mbar_wait_c(B(B_EMPTY3 + j), ~r & 1);
          load3(r * 6 + j - 1, j);
          if (j == 5 && r == 9 && elect_one()) l2_prefetch(xr, XR_CAND * 16);
        }
      }
      if (ffn) {
#pragma unroll
        for (int j = 1; j >= 0; j--) {
          mbar_wait(B(B_EMPTY3 + 5 * j), j);
          if (elect_one()) {
            mbar_expect(B(B_FULL3 + 5 * j), SLOT);
            tma_ld3(sb + OFF_R3 + 5 * j * SLOT, &p.wd, B(B_FULL3 + 5 * j), 0, fid * 32, 8 * j, true);
          }
        }
      }
    } else {
      if (warp >= 2) {
#pragma unroll 1
        for (int i = tid - 64; i < XR_CAND; i += 64) xr[i] = make_uint4(~0u, ~0u, ~0u, ~0u);
        if (warp == 2) { __syncwarp(); if (lane == 0) mbar_arrive(B(B_WR)); }
      }
      if (warp == 3) {
        float ws = 0.f;
#pragma unroll
        for (int j = 0; j < 4; j++) {
          const uint4 q = __ldg(reinterpret_cast<const uint4*>(w_r) + j * 32 + lane);
          ws += bf_lo(q.x) + bf_hi(q.x) + bf_lo(q.y) + bf_hi(q.y) + bf_lo(q.z) + bf_hi(q.z) + bf_lo(q.w) + bf_hi(q.w);
        }
#pragma unroll
        for (int o = 16; o; o >>= 1) ws += __shfl_xor_sync(~0u, ws, o);
        uint2* tab = reinterpret_cast<uint2*>(sp + OFF_MISC + 512);
        tab[lane] = make_uint2(0x3F803F80u, 0x3F803F80u);
        tab[32 + lane] = __ldg(reinterpret_cast<const uint2*>(w_r + gq * 128) + lane);
        if (lane == 0) *reinterpret_cast<float*>(sp + OFF_MISC + 1024) = ws;
        __syncwarp();
        if (lane == 0) mbar_arrive(B(B_WR));
      }
      if (tid == 32) TS(0);
      mbar_wait(B(B_LN), 0);
#pragma unroll 1
      for (int r = warp - 1; r < 16; r += 3) {
        uint4 v[4];
        float a0 = 0.f, a1 = 0.f, b0 = 0.f, b1 = 0.f;
#pragma unroll
        for (int j = 0; j < 4; j++) {
          v[j] = lds128(sb + OFF_LN + r * 2048 + lane * 16 + j * 512);
          const uint32_t u[4] = {v[j].x, v[j].y, v[j].z, v[j].w};
#pragma unroll
          for (int i = 0; i < 4; i++) { const float a = bf_lo(u[i]), b = bf_hi(u[i]); a0 += a; a1 += b; b0 = fmaf(a, a, b0); b1 = fmaf(b, b, b1); }
        }
        a0 += a1; b0 += b1;
#pragma unroll
        for (int o = 16; o; o >>= 1) { a0 += __shfl_xor_sync(~0u, a0, o); b0 += __shfl_xor_sync(~0u, b0, o); }
        const float mean = a0 * (1.f / DM);
        float mb, inv;
        ln_round(mean, fmaxf(fmaf(b0, 1.f / DM, -mean * mean), 0.f), mb, inv);
        inv *= AT_C;
        const uint32_t nm2 = pack_bf16(-mb, -mb);
        uint4* dst = reinterpret_cast<uint4*>(g_xn + (size_t)(cta * 16 + r) * DM) + lane;
#pragma unroll
        for (int j = 0; j < 4; j++)
          dst[j * 32] = make_uint4(ln_apply(v[j].x, nm2, inv), ln_apply(v[j].y, nm2, inv), ln_apply(v[j].z, nm2, inv), ln_apply(v[j].w, nm2, inv));
      }
      __syncwarp();
      if (lane == 0) {
        mbar_arrive(B(B_LND));
        fence_gpu();
        red_add(&g_cnt[C_LN + (cta >> 3)], 1);
      }
      TL(3, warp, lane == 0);
      __syncwarp();
      cluster_arrive();
      if (warp == 3) {
        if (lane == 0) {
#pragma unroll 1
          for (int i = 0; i < 6; i++) {
            const int c = i < 2 ? C_LN + (i ? ti : 15 - ti) : (i < 4 ? C_QKV + (i - 2) * 8 + mp : C_CTX + (i - 4) * 16 + mt);
            spin_until_ge<true>(&g_cnt[c], i < 2 ? 24 : 16);
            fence_async_all();
            mbar_arrive(B(B_DEP + i));
            TL(3, 4 + i, true);
          }
        }
      } else if (warp == 1 && elect_one()) {
        mbar_wait(B(B_WR), 0);
#pragma unroll 1
        for (int i = 0; i < 6; i++) {
          const int c = i < 2 ? C_QKV + gq + i * 8 : C_CTX + (i >> 2) * 16 + ((i == 3 || i == 4) ? ti : 15 - ti);
          mbar_wait(B(B_PUB + i), 0);
          if (i >= 2 && i < 5) {
            asm volatile("fence.proxy.async.shared::cta;" ::: "memory");
#pragma unroll 1
            for (int n = 0; n < 8; n++) {
              const int h = n >> 2, a = n & 3;
              asm volatile("cp.async.bulk.tensor.3d.global.shared::cta.bulk_group [%0, {%2,%3,%4}], [%1];" ::"l"(&p.ctx_st),
                           "r"(sb + (i == 4 ? 6 * SLOT + h * 16384 : (3 + 2 * h) * SLOT + (i - 2) * 16384) + a * 4096),
                           "r"(0), "r"((i == 2 ? 15 - ti : ti) * 128 + h * 64), "r"((hh + (i >> 2) * 16) * 4 + a) : "memory");
              asm volatile("cp.async.bulk.commit_group;\ncp.async.bulk.wait_group.read 0;" ::: "memory");
            }
            mbar_arrive(B(B_QP + i - 2));
            asm volatile("cp.async.bulk.wait_group 0;" ::: "memory");
          }
          fence_gpu();
          red_add(&g_cnt[c], 1);
          TS(1 + i);
        }
      }
      if (warp == 2) {
#pragma unroll 1
        for (int n = 0; n < 8; n++) {
          if (!(n & 3)) mbar_wait(B(B_XE), n >> 2);
          if ((n < 4 || ffn) && elect_one()) {
            const uint32_t fb = B(n < 4 ? B_XF : B_WF2), d = sb + 6 * SLOT + (n & 3) * 8192;
            if (!(n & 3)) mbar_expect(fb, 32768);
            if (n < 4) tma_ld3(d, &p.x, fb, 0, mt * 128 + (n >> 1) * 64, gq * 2 + (n & 1), true);
            else tma_ld2(d, (n & 1) ? &p.wg : &p.wu, fb, fid * 32, (4 + (n >> 1)) * 128, true);
          }
          __nanosleep(SL_NS);
        }
#pragma unroll 1
        for (int i = XR_CAND + lane; i < XR_SIZE; i += 32) { xr[i] = make_uint4(~0u, ~0u, ~0u, ~0u); __nanosleep(SET_NS); }
        __syncwarp();
        if (lane == 0) { fence_gpu(); mbar_arrive(B(B_SET2)); }
        TL(2, 26, lane == 0);
        __syncwarp();
      }
      __syncwarp();
      if (warp == 3) {
        mbar_wait(B(B_OUT), 0);
        uint4 kv[2];
        poll_chunks(kv, g_xr + ((lane >> 1) * 8 + gq) * XR_SIZE + XR_KEY + (lane & 1) * 2, 1);
        const uint32_t a1 = max(kv[0].x, kv[0].z), a2 = max(min(kv[0].x, kv[0].z), max(kv[0].y, kv[0].w));
        const uint32_t b1 = max(kv[1].x, kv[1].z), b2 = max(min(kv[1].x, kv[1].z), max(kv[1].y, kv[1].w));
        const uint32_t k1 = max(a1, b1), k2 = max(min(a1, b1), max(a2, b2));
        const uint32_t m1 = __reduce_max_sync(~0u, k1);
        const uint32_t m2 = __reduce_max_sync(~0u, k1 == m1 ? k2 : k1);
        auto cand = [&](uint32_t k) { return (((~k >> 7) & 15) * (8 * XR_SIZE) + ((~k >> 4) & 7) * 64) * 16; };
        const uint32_t o1 = cand(m1), o2 = cand(m2) + (((m1 ^ m2) & 0x7FF0) ? 0 : 256);
        if (lane == 0) {
          *reinterpret_cast<uint4*>(sp + OFF_MISC) = make_uint4(m1, m2, o1, o2);
          mbar_arrive(B(B_OUT2));
        }
        const uint32_t key = (lane & 4) ? m2 : m1;
        const uint4* src = g_xr + (((~key >> 7) & 15) * 8 + (rid >> 4)) * XR_SIZE;
        poll_chunks(kv, g_xr + (((lane & 4) ? o2 : o1) >> 4) + (rid >> 4) * XR_SIZE + XR_CAND + (rid & 12) + (lane & 3), 32);
        uint32_t u = key >> 16;
        u = (u & 0x8000u) ? (u & 0x7FFFu) : (~u & 0xFFFFu);
        const float rs = bf_round(sigmoid(__uint_as_float(u << 16)));
        if (lane < 8)
          *reinterpret_cast<uint4*>(sp + OFF_MISC + 128 + lane * 16) = make_uint4((rid & 2) ? ((rid & 1) ? kv[0].w : kv[0].z) : ((rid & 1) ? kv[0].y : kv[0].x),
              (rid & 2) ? ((rid & 1) ? kv[1].w : kv[1].z) : ((rid & 1) ? kv[1].y : kv[1].x), __float_as_uint(rs), 0);
#pragma unroll 1
        for (int n = 0; n < 0x400000; n++) {
          uint32_t v;
          asm volatile("ld.acquire.gpu.global.u32 %0, [%1];" : "=r"(v) : "l"(src + XR_FLAG) : "memory");
          if (__all_sync(~0u, v == 0)) break;
        }
        if (lane == 0) mbar_arrive(B(B_FIN));
      }
      if (warp == 1 && elect_one()) {
        mbar_wait(B(B_OUT3), 0);
        auto owner = [&]() {
          uint2 top;
          asm volatile("ld.shared.v2.u32 {%0,%1}, [%2];" : "=r"(top.x), "=r"(top.y) : "r"(sb + OFF_MISC) : "memory");
          return (0x7FFF - (top.x & 0x7FFF)) >> 7 == mt || (0x7FFF - (top.y & 0x7FFF)) >> 7 == mt;
        };
#pragma unroll 1
        for (int n = 0; n < 4; n++) {
          if (n && !(mbar_test(B(B_OUT2), 0) && owner())) idle(OUT_CLK);
          asm volatile("cp.async.bulk.tensor.2d.global.shared::cta.bulk_group [%0, {%2,%3}], [%1];" ::"l"(&p.out), "r"(sb + OFF_STG + n * 8192),
                       "r"(gq * 128 + (n & 1) * 64), "r"(mt * 128 + (n >> 1) * 64) : "memory");
        }
        asm volatile("cp.async.bulk.commit_group;" ::: "memory");
        mbar_wait(B(B_OUT2), 0);
        if (owner()) {
          asm volatile("cp.async.bulk.wait_group 0;" ::: "memory");
          asm volatile("st.release.gpu.global.u32 [%0], 0;" ::"l"(xr + XR_FLAG) : "memory");
        } else {
          asm volatile("cp.async.bulk.wait_group.read 0;" ::: "memory");
        }
        TL(2, 25, true);
      }
    }
    __syncwarp();
    if (warp == 0) cluster_arrive();
    cluster_wait();
    TL_DUMP();
    if (tid == 32) TS(8);
  } else {
    reg_alloc<232>();
    cluster_wait();
    const int w = wg - 1, cw = warp - 4;
    int lane = lane_id();
    const uint32_t stg = sb + OFF_STG + w * 16384 + (cw & 3) * 2048;
    auto publish = [&](int i) { __syncwarp(); if (lane == 0) mbar_arrive(B(B_PUB + i)); };
    uint32_t rbar;
    asm("mapa.shared::cluster.u32 %0, %1, %2;" : "=r"(rbar) : "r"(bar), "r"(lane & 1));
    auto release2 = [&](int i) { if (lane < 2) asm volatile("mbarrier.arrive.shared::cluster.b64 _, [%0];" ::"r"(rbar + 8 * i) : "memory"); };
    float R[128];
    float O[64], acc[64];
    uint32_t pk[64];
    uint32_t* const Q = pk;
    uint32_t P[32];
    auto packed = [&](int i) {
      const float* v = R + 16 * (i >> 1) + 2 * (i & 1);
      return make_uint4(pack_bf16(v[0], v[1]), pack_bf16(v[4], v[5]), pack_bf16(v[8], v[9]), pack_bf16(v[12], v[13]));
    };
    const uint32_t q_st = sb + (cw & 3) * 1024 + (lane >> 2) * 64 + (((lane & 3) ^ (lane >> 3)) << 4);
    const uint32_t q_ld = sb + (cw & 3) * 1024 + (lane & 15) * 64 + (((lane >> 4) ^ ((lane >> 1) & 3)) << 4);
    auto park = [&](uint32_t off, int i, uint4 v) {
      asm volatile("st.shared.v4.u32 [%0], {%1,%2,%3,%4};" ::"r"(q_st + off + (i >> 1) * 4096 + (i & 1) * 512), "r"(v.x), "r"(v.y), "r"(v.z), "r"(v.w) : "memory");
    };
    auto load_q = [&](uint32_t off, int k) { ldsm4(Q + 4 * k, ((q_ld + off) ^ ((k & 1) << 5)) + (k >> 1) * 4096); };
    {
      TL(0, 1, tid == 128);
      __nv_bfloat16* pdst = g_qkv;
      auto put2 = [&](int j) {
#pragma unroll
        for (int i = (j >> 1) * 4 + (j & 1); i < (j >> 1) * 4 + 4; i += 2)
          __stcs(reinterpret_cast<uint4*>(pdst + (i & 1) * 8 * NQ + (i >> 1) * 32), make_uint4(pk[4 * i], pk[4 * i + 1], pk[4 * i + 2], pk[4 * i + 3]));
      };
      const uint64_t da0 = mk_desc(sb + w * 8192, 16, 1024, 1);
      const uint64_t db0 = mk_desc(sb + 16384, 8192, 1024, 1);
      int st = 0; uint32_t ph = 0;
      auto issue = [&](int accum, auto between) {
        mbar_wait_c(B(B_FULL1 + st), ph);
        const uint64_t da = desc_add(da0, st * P1_STAGE), db = desc_add(db0, st * P1_STAGE);
        between();
        wg_fence();
#pragma unroll
        for (int k = 0; k < 4; k++) mma_n256_ss<1>(R, desc_add(da, k * 32), desc_add(db, k * 2048), k == 0 ? accum : 1);
        wg_commit();
      };
      issue(0, []() {});
#pragma unroll 1
      for (int t = 0;; t++) {
        const int nk = t >= 4 ? 16 : 8;
        const bool tr = t > 0 && t < 5;
        TL(0, 2 + 2 * t + 16 * w, (tid & 127) == 0);
        int prev = st;
        if (++st == 4) { st = 0; ph ^= 1; }
#pragma unroll 1
        for (int kb = 1; kb < nk; kb++) {
          if (kb == nk - 1 && w == 1) bar_sync(5, 256);
          issue(1, []() {});
          if (kb == nk - 1 && w == 0) bar_arrive(5, 256);
          if (tr) {
#pragma unroll
            for (int i = 1; i < 8; i++) if (kb == i) put2(i);
            if (kb == 7 && !(t & 1)) publish((t >> 1) - 1);
          } else if (t == 5) {
            if (kb == 2) {
              mbar_wait_c(B(B_LND), 0);
#pragma unroll
              for (int i = 0; i < 8; i++) park(6 * SLOT + w * 16384, i, make_uint4(pk[4 * i], pk[4 * i + 1], pk[4 * i + 2], pk[4 * i + 3]));
              __syncwarp();
            }
            if (kb == 4) {
#pragma unroll
              for (int k = 0; k < 8; k++) load_q(6 * SLOT + w * 16384, k);
              __syncwarp();
            }
            if (kb == 6) {
#pragma unroll
              for (int i = 0; i < 8; i++) park(6 * SLOT + w * 16384, i, make_uint4(pk[32 + 4 * i], pk[33 + 4 * i], pk[34 + 4 * i], pk[35 + 4 * i]));
            }
          }
          wg_wait<1>();
          release2(B_EMPTY1 + prev);
          prev = st;
          if (++st == 4) { st = 0; ph ^= 1; }
        }
        if (t == 5) break;
        issue(0, [&]() {
          sched_fence(q_st);
          wg_wait<0>();
          fence_regs<128>(R);
          TL(0, 3 + 2 * t + 16 * w, (tid & 127) == 0);
#pragma unroll
          for (int i = 0; i < 16; i++) { const uint4 v = packed(i); pk[4 * i] = v.x; pk[4 * i + 1] = v.y; pk[4 * i + 2] = v.z; pk[4 * i + 3] = v.w; }
          release2(B_EMPTY1 + prev);
          fence_regs<128>(R);
        });
        if (w == 1) bar_arrive(4, 256);
        sched_fence(q_st);
        pdst = g_qkv + (size_t)(((t & 1) + 1) * SEQ + mt * 128 + cw * 16 + (lane >> 2)) * NQ + (gq + (t >> 1) * 8) * 256 + (lane & 3) * 8;
        if (t < 4) put2(0);
        if (w == 0) bar_sync(4, 256);
      }
      if (w == 1) bar_arrive(6, 256);
      mbar_wait_c(B(B_KF), 0);
      sched_fence(q_st);
      wg_wait<0>();
      fence_regs<128>(R);
      release2(B_EMPTY1 + 3);
      TL(0, 13 + 16 * w, (tid & 127) == 0);
    }
    auto issue3 = [&](int st, uint32_t ph, int accum) {
      mbar_wait_c(B(B_FULL3 + st), ph);
      const uint64_t da = mk_desc(sb + OFF_R3 + w * 8192 + st * SLOT, 16, 1024, 1), db = mk_desc(sb + OFF_R3 + 16384 + st * SLOT, 8192, 1024, 1);
      wg_fence();
#pragma unroll
      for (int k = 0; k < 4; k++) mma_n128_ss<1>(acc, desc_add(da, k * 32), desc_add(db, k * 2048), k == 0 ? accum : 1);
      wg_commit();
    };
    uint32_t wf[128];
    auto w_addr = [&](uint32_t off, int m) {
      const uint32_t w_ld = sb + ((lane >> 3) & 1) * 8192 + ((cw >> 1) * 32 + (lane & 7) + (lane >> 4) * 8) * 64 + ((((cw & 1) * 2) ^ ((lane >> 1) & 3)) << 4);
      return ((w_ld + off) ^ ((m & 1) << 4)) + (m >> 2) * 16384 + ((m >> 1) & 1) * 1024;
    };
    auto grab = [&](uint32_t* d, uint32_t off, int m0, int m1) {
#pragma unroll
      for (int m = m0; m < m1; m++)
        asm volatile("ldmatrix.sync.aligned.m8n8.x4.trans.shared.b16 {%0,%1,%2,%3}, [%4];"
                     : "=r"(d[4 * m]), "=r"(d[4 * m + 1]), "=r"(d[4 * m + 2]), "=r"(d[4 * m + 3]) : "r"(w_addr(off, m)) : "memory");
    };
    float inv[2] = {0.f, 0.f};
    auto scaled = [&](int i) {
      const float* o = O + 16 * (i >> 1) + 2 * (i & 1);
      const float c = inv[i & 1];
      return make_uint4(pack_bf16(o[0] * c, o[1] * c), pack_bf16(o[4] * c, o[5] * c), pack_bf16(o[8] * c, o[9] * c), pack_bf16(o[12] * c, o[13] * c));
    };
    {
      const int wrow = cw * 16;
      const uint64_t dk0 = mk_desc(sb, 16, 1024, 1);
      const uint64_t dv0 = mk_desc(sb + 2 * SLOT, 16384, 1024, 1);
      const uint32_t pin = sb + OFF_MISC + 1028;
      float l0 = 0.f, l1 = 0.f;
      int g = 0, t = 0;
      uint32_t fail = 0;
      auto piece = [&](int tt) { return (uint32_t)(tt == 3 ? 6 * SLOT + w * 16384 : (3 + 2 * w) * SLOT + (tt - 1) * 16384); };
      uint32_t par = 0;
      auto issue_s = [&](float* S) {
        const uint64_t dk = desc_add(dk0, par * 16);
        mma_n128_rs0(S, Q, dk);
#pragma unroll
        for (int k = 1; k < 8; k++) mma_n128_rs<0>(S, Q + 4 * k, desc_add(dk, (k >> 2) * 16384 + (k & 3) * 32), 1);
        wg_commit();
      };
      auto issue_pv = [&](bool half, int accum) {
        const uint64_t dv = desc_add(dv0, ((g - 1) & 1) * 2 * SLOT);
        wg_fence();
#pragma unroll
        for (int k = 0; k < 4; k++) mma_n128_rs<1>(O, P + 4 * k, desc_add(dv, k * 2048), k == 0 ? accum : 1);
        wg_commit();
        if (UNLIKELY(half)) {
          wg_fence();
          wg_commit();
        } else {
          wg_fence();
#pragma unroll
          for (int k = 4; k < 8; k++) mma_n128_rs<1>(O, P + 4 * k, desc_add(dv, k * 2048), 1);
          wg_commit();
        }
        bar_arrive(2 - w, 256);
        wg_wait<2>();
        fence_regs<32>(Q);
      };
      auto release_k = [&]() { release2(B_KE); rbar ^= 8; };
      auto pv_done = [&]() {
        TC(g, 3);
        sched_fence(q_st);
        wg_wait<0>();
        fence_regs<64>(O); fence_regs<32>(P);
        TC(g, 4);
        release2(B_VE);
      };
      auto row_inv = [&](bool go) {
        float a = l0 + __shfl_xor_sync(~0u, l0, 1), b = l1 + __shfl_xor_sync(~0u, l1, 1);
        a += __shfl_xor_sync(~0u, a, 2); b += __shfl_xor_sync(~0u, b, 2);
        const bool ok = __all_sync(~0u, a >= AT_LO && a <= AT_HI && b >= AT_LO && b <= AT_HI) != 0;
        asm("rcp.approx.ftz.f32 %0, %1;" : "=f"(inv[0]) : "f"(a));
        asm("rcp.approx.ftz.f32 %0, %1;" : "=f"(inv[1]) : "f"(b));
        fail |= (uint32_t)(go && !ok) << t;
        l0 = go ? 0.f : l0; l1 = go ? 0.f : l1;
        t += go;
      };
      const uint64_t m_first = 1ull | (1ull << (16 - ti)) | (1ull << 17) | (1ull << (18 + ti));
      const uint64_t m_diag = (3ull << (15 - ti)) | (3ull << (17 + ti));
      enum { F_FIRST = 1, F_DIAG = 2, F_LAST = 4, F_PFIRST = 8, F_PHALF = 16, F_STOP = 32 };
      auto kind = [&](int gn) {
        const uint32_t a = (uint32_t)((m_first << 1) >> gn), d = (uint32_t)((m_diag << 1) >> gn);
        return ((a >> 1) & 1) * F_FIRST | ((d >> 1) & 1) * F_DIAG | ((a >> 2) & 1) * F_LAST | (a & 1) * F_PFIRST |
               (w == 0 ? (d & 1) * F_PHALF | ((d >> 1) & 1) * F_STOP : 0) | (gn == 34 ? F_STOP : 0);
      };
      uint32_t kinds;
      {
        uint32_t qt[64];
#pragma unroll
        for (int i = 0; i < 16; i++) { const uint4 v = packed(i); qt[4 * i] = v.x; qt[4 * i + 1] = v.y; qt[4 * i + 2] = v.z; qt[4 * i + 3] = v.w; }
        fence_regs<64>(qt);
        sched_fence(q_st);
        float S[64];
        wg_fence();
        issue_s(S);
        bar_arrive(w ? 1 : 7, 256);
        bar_sync(6 + w, 256);
        sched_fence(q_st);
        TL(1, 0, tid == 128);
#pragma unroll
        for (int i = 0; i < 16; i++) park(piece(1), i, make_uint4(qt[4 * i], qt[4 * i + 1], qt[4 * i + 2], qt[4 * i + 3]));
        kinds = pinned(kind(lane + 3));
        sched_fence(q_st);
        wg_wait<0>();
        fence_regs<64>(S);
        release_k();
        TL(1, 1, tid == 128);
        const bool kok = mbar_try(B(B_KF + 1), 0);
        at_exp<0, 32>(S);
        sched_fence(q_st);
        at_exp<32, 64>(S); at_fin<0, 64>(S, P);
        if (UNLIKELY(!kok)) mbar_wait_c(B(B_KF + 1), 0);
        TL(1, 2, tid == 128);
      }
      uint32_t f = F_PFIRST, fn;
      auto shadow = [&]() {
        const bool vok = mbar_try(B(B_VF + ((g - 1) & 1)), ((g - 1) >> 1) & 1);
        at_sum(P, f & F_PHALF, l0, l1);
        fn = __shfl_sync(~0u, kinds, max(g - 2, 0));
        if (UNLIKELY(!vok)) mbar_wait_c(B(B_VF + ((g - 1) & 1)), ((g - 1) >> 1) & 1);
      };
      auto hand_over = [&]() { __syncwarp(); if (lane == 0 && !((fail >> (t - 1)) & 1)) mbar_arrive(B(B_PUB + 1 + t)); };
      auto exp_q = [&](float* S, auto kc, auto nc) {
        constexpr int k = decltype(kc)::value, n = decltype(nc)::value;
        asm volatile("{\n.reg .pred p;\nsetp.ne.b32 p, %5, 0;\n@p ldmatrix.sync.aligned.m8n8.x4.shared.b16 {%0,%1,%2,%3}, [%4];\n}"
                     : "+r"(Q[4 * k]), "+r"(Q[4 * k + 1]), "+r"(Q[4 * k + 2]), "+r"(Q[4 * k + 3])
                     : "r"(((q_ld + piece(t + 1)) ^ ((k & 1) << 5)) + (k >> 1) * 4096), "r"(f & F_LAST) : "memory");
        at_exp<n * k, n * k + n>(S);
      };
      g = 1; par = SLOT / 16;
#pragma unroll 1
      for (;;) {
        {
          TC(g, 0);
          bar_sync(1 + w, 256);
          fence_regs<32>(Q);
          float S[64];
          wg_fence();
          issue_s(S);
          sched_fence(q_st);
          TC(g, 1);
          shadow();
          fence_regs<64>(O); fence_regs<32>(P);
          issue_pv(f & F_PHALF, ~f & F_PFIRST);
          fence_regs<64>(S);
          TC(g, 2);
          release_k();
          at_exp<0, 8>(S);
          const bool first = f & F_FIRST;
          if (UNLIKELY(f & (F_FIRST | F_LAST))) {
            row_inv(first);
            at_mask(S + 32, (f & F_DIAG) ? wrow - 64 : 64, lane);
            unroll8([&](auto kc) { exp_q(S + 8, kc, std::integral_constant<int, AT_R1 / 8 - 1>{}); });
          } else {
            at_exp<8, AT_R1>(S);
          }
          pv_done();
          g = pinned(g + 1); par = pinned(par ^ (SLOT / 16)); f = fn;
          const bool kok = mbar_try(B(B_KF + (g & 1)), g < 34 ? (g >> 1) & 1 : 0);
          if (UNLIKELY(first)) {
            unroll8([&](auto ic) {
              constexpr int i = decltype(ic)::value, n = (64 - AT_R1) / 8;
              at_exp<AT_R1 + n * i, AT_R1 + n * i + n>(S);
              park(piece(t), i, scaled(i));
            });
            at_fin<0, 64>(S, P);
            hand_over();
          } else {
            at_exp<AT_R1, 64>(S); at_fin<0, 64>(S, P);
          }
          TC(g - 1, 5);
          if (!TCLK) TL(1, 1 + g, tid == 128);
          if (kok && !(f & F_STOP)) continue;
          if (UNLIKELY(!kok)) mbar_wait_c(B(B_KF + (g & 1)), (g >> 1) & 1);
          if (g == 34) break;
        }
#pragma unroll 1
        while (f & F_STOP) {
          TC(g, 0);
          bar_sync(1, 256);
          fence_regs<64>(O); fence_regs<32>(Q); fence_regs<32>(P);
          float S[32];
          const uint64_t dk = desc_add(dk0, par * 16);
          wg_fence();
          mma_n64_rs0(S, Q, dk);
#pragma unroll
          for (int k = 1; k < 8; k++) mma_n64_rs(S, Q + 4 * k, desc_add(dk, (k >> 2) * 16384 + (k & 3) * 32), 1);
          wg_commit();
          TC(g, 1);
          mbar_wait_c(B(B_VF + ((g - 1) & 1)), ((g - 1) >> 1) & 1);
          issue_pv(f & F_PHALF, ~f & F_PFIRST);
          fence_regs<32>(S);
          TC(g, 2);
          release_k();
          const bool first = f & F_FIRST;
          at_sum(P, f & F_PHALF, l0, l1);
          fn = __shfl_sync(~0u, kinds, g - 2);
          row_inv(first);
          pv_done();
          sched_fence(q_st);
          at_mask(S, wrow, lane);
          unroll8([&](auto kc) { exp_q(S, kc, std::integral_constant<int, 4>{}); });
          g++; par ^= SLOT / 16; f = fn;
          at_fin<0, 32>(S, P);
          if (first) {
#pragma unroll
            for (int i = 0; i < 8; i++) park(piece(t), i, scaled(i));
            hand_over();
          }
          TC(g - 1, 5);
          if (!TCLK) TL(1, 1 + g, tid == 128);
          mbar_wait_c(B(B_KF + (g & 1)), (g >> 1) & 1);
        }
      }
      const bool wok = mbar_test(B(ffn ? B_WF : B_QP + 1), 0);
      grab(wf, 3 * SLOT, 0, 8);
      mbar_wait_c(B(B_VF + 1), 0);
      bar_sync(1 + w, 256);
      fence_regs<64>(O); fence_regs<32>(P);
      wg_fence();
#pragma unroll
      for (int k = 0; k < 8; k++) mma_n128_rs<1>(O, P + 4 * k, desc_add(dv0, 2 * SLOT + k * 2048), 1);
      wg_commit();
      if (w == 0) bar_arrive(2, 256);
      pin_order(__uint_as_float(wf[28] & wf[24]), pin);
      __syncwarp();
      if (wok) release2(B_WE);
      TL(3, 12 + 16 * w, (tid & 127) == 0);
      sched_fence(q_st);
      at_sum(P, false, l0, l1);
      row_inv(true);
      sched_fence(q_st);
      wg_wait<0>();
      fence_regs<64>(O); fence_regs<32>(P);
      release2(B_VE + 1);
      if (UNLIKELY(!wok || fail != 0)) {
#pragma unroll 1
        for (int tt = 0; tt < 4; tt++) {
          if (!((tt < 3 ? fail >> tt : fail != 0) & 1)) continue;
          slow_tile(O, P, l0, l1, wq, (((tt + 1) & 2) ? ti : 15 - ti) * 128 + wrow, hh + (tt & 2) * 8, lane, q_st);
          row_inv(false);
          if (tt < 3) {
#pragma unroll
            for (int i = 0; i < 8; i++) park(piece(tt + 1), i, scaled(i));
            publish(2 + tt);
          }
        }
        if (!wok) {
          mbar_wait_c(B(ffn ? B_WF : B_QP + 1), 0);
          grab(wf, 3 * SLOT, 0, 8);
          pin_order(__uint_as_float(wf[28] & wf[24]), pin);
          __syncwarp();
          release2(B_WE);
        }
      }
      TL(3, 13 + 16 * w, (tid & 127) == 0);
      issue3(0, 0, 0);
      TL(3, 14 + 16 * w, (tid & 127) == 0);
      TL(1, 36, tid == 128);
    }
    uint32_t hp[32];
    lane = lane_id();
    {
      int st = 1, prev = 0; uint32_t ph = 0;
      __nv_bfloat16* dst = g_qkv + (size_t)((15 - ti) * 128 + cw * 16 + (lane >> 2)) * NQ + (hh + 16) * 128 + (lane & 3) * 8;
      auto kblock = [&](auto between, int lim = 6) {
        issue3(st, ph, 1);
        between();
        wg_wait<1>();
        release2(B_EMPTY3 + prev);
        prev = st;
        if (++st == lim) { st = 0; ph ^= 1; }
      };
      kblock([&]() { TL(3, 15 + 16 * w, (tid & 127) == 0); });
      kblock([&]() { grab(wf + 32, 5 * SLOT, 0, 8); TL(3, 16 + 16 * w, (tid & 127) == 0); });
#pragma unroll 1
      for (int kb = 3; kb < 11; kb++) {
        kblock([&]() {
#pragma unroll
          for (int i = 0; i < 8; i++)
            if (kb == 3 + (i & 4) + (i & 1) * 2 + ((i >> 1) & 1)) *reinterpret_cast<uint4*>(dst + (i & 1) * 8 * NQ + (i >> 1) * 32) = scaled(i);
          TL(3, 14 + kb + 16 * w, (tid & 127) == 0);
          if (kb == 8) TL(2, 2, tid == 128);
        }, kb == 4 ? 5 : 6);
        if (kb == 4) release2(B_EMPTY3 + 5);
      }
      publish(5);
      kblock([&]() { mbar_wait_c(B(ffn ? B_WF2 : B_QP + 2), 0); grab(wf + 32, 5 * SLOT, 8, 16); });
#pragma unroll 1
      for (int kb = 12; kb < G_KB; kb++) {
        kblock([&]() { if ((kb & 7) == 0) TL(2, 1 + (kb >> 3), tid == 128); });
        if (kb == X_KB && lane == 0) mbar_arrive(B(B_XE));
      }
      kblock([&]() {
        mbar_wait_c(B(B_XF), 0);
#pragma unroll
        for (int i = 0; i < 8; i++)
          ldsm4(hp + 4 * i, sb + 6 * SLOT + w * 16384 + ((cw & 3) * 16 + (lane & 15)) * 128 + (i >> 2) * 8192 + ((((i & 3) * 2 + (lane >> 4)) ^ (lane & 7)) << 4));
      });
#pragma unroll 1
      for (int kb = G_KB + 1; kb < 64; kb++) {
        kblock([&]() { if ((kb & 7) == 0) TL(2, 1 + (kb >> 3), tid == 128); });
        if (kb == G_KB + 2 && lane == 0) mbar_arrive(B(B_XE));
      }
    }
    lane = lane_id();
    const int r0 = lane >> 2, q4 = lane & 3, ct = cw * 32 + lane;
    uint32_t tb[16];
    mbar_wait_c(B(B_WR), 0);
#pragma unroll
    for (int i = 0; i < 4; i++) ldsm4(tb + 4 * i, sb + OFF_MISC + 512 + (lane & 1) * 256 + (lane >> 3) * 16 + i * 64);
    mbar_wait_c(B(B_SET2), 0);
    float4* const psd = reinterpret_cast<float4*>(xr + XR_PS + cw * 16 + r0);
    const uint4* const pss = g_xr + (mt * 8 + (ct & 1) * 4) * XR_SIZE + XR_PS + (ct >> 1);
    sched_fence(stg);
    wg_wait<0>();
    fence_regs<64>(acc);
    TL(2, 10, tid == 128);
    {
      float d[2][4] = {}, qa[2][4] = {}, qb[2][4] = {};
#pragma unroll
      for (int j = 0; j < 16; j++) {
        hp[2 * j] = hadd2_bf(hp[2 * j], pack_bf16(acc[4 * j], acc[4 * j + 1]));
        hp[2 * j + 1] = hadd2_bf(hp[2 * j + 1], pack_bf16(acc[4 * j + 2], acc[4 * j + 3]));
        if (j & 1) {
          mma16816(d[(j >> 1) & 1], hp[2 * j - 2], hp[2 * j - 1], hp[2 * j], hp[2 * j + 1], tb[j - 1], tb[j]);
          mma16816(qa[(j >> 1) & 1], hp[2 * j - 2], hp[2 * j - 1], hp[2 * j], hp[2 * j + 1], hp[2 * j - 2], hp[2 * j]);
          mma16816(qb[(j >> 1) & 1], hp[2 * j - 2], hp[2 * j - 1], hp[2 * j], hp[2 * j + 1], hp[2 * j - 1], hp[2 * j + 1]);
        }
      }
      if (q4 == (r0 >> 1)) {
        __stcg(psd, make_float4(d[0][0] + d[1][0], (r0 & 1) ? qa[0][1] + qa[1][1] : qa[0][0] + qa[1][0], d[0][1] + d[1][1], 0.f));
        __stcg(psd + 8, make_float4(d[0][2] + d[1][2], (r0 & 1) ? qb[0][3] + qb[1][3] : qb[0][2] + qb[1][2], d[0][3] + d[1][3], 0.f));
      }
    }
    TL(2, 11, tid == 128);
    mbar_wait_c(B(B_EMPTY3 + 1), 0);
    stage_store_128(stg, lane, hp);
    if (ffn) mbar_wait_c(B(B_WF2), 1);
    grab(wf + 96, 6 * SLOT, 0, 8);
    const float wsum = *reinterpret_cast<const float*>(sp + OFF_MISC + 1024);
    __syncwarp();
    {
      uint4 ps[4];
      poll_chunks(ps, pss, XR_SIZE);
      TL(2, 12, tid == 128);
      auto F = [](uint32_t u) { return __uint_as_float(u); };
      float s1 = (F(ps[0].x) + F(ps[1].x)) + (F(ps[2].x) + F(ps[3].x)), s2 = (F(ps[0].y) + F(ps[1].y)) + (F(ps[2].y) + F(ps[3].y));
      float s3 = (F(ps[0].z) + F(ps[1].z)) + (F(ps[2].z) + F(ps[3].z));
      __syncwarp();
      s1 += __shfl_xor_sync(~0u, s1, 1); s2 += __shfl_xor_sync(~0u, s2, 1); s3 += __shfl_xor_sync(~0u, s3, 1);
      const float mean = s1 * (1.f / DM);
      float mb, inv;
      ln_round(mean, fmaxf(fmaf(s2, 1.f / DM, -mean * mean), 0.f), mb, inv);
      const uint32_t u = pack_bf16(0.f, fmaf(s3 - mb * wsum, inv, 0.f));
      const uint32_t key = (u ^ ((((int)u >> 31) & 0x7FFF0000u) | 0x80000000u)) | (0x7FFFu - (mt * 128 + (ct >> 1)));
      const uint32_t nm2 = pack_bf16(-mb, -mb);
      const uint32_t c1 = __reduce_max_sync(~0u, key);
      const uint32_t c2 = __reduce_max_sync(~0u, key == c1 ? 0u : key);
      if (lane == 0) {
        __stcg(reinterpret_cast<uint2*>(psd) + (XR_KEY - XR_PS) * 2 - cw * 31, make_uint2(c1, c2));
        mbar_arrive(B(B_OUT));
      }
      TL(2, 13, tid == 128);
      const int row = (0x7FFF - (((lane >> 4) ? c2 : c1) & 0x7FFF)) & 15;
      const uint32_t rn = __shfl_sync(~0u, nm2, row * 2);
      const float ri = __shfl_sync(~0u, inv, row * 2);
      uint32_t v[4];
#pragma unroll
      for (int i = 0; i < 4; i++)
        asm volatile("ld.shared.u32 %0, [%1];" : "=r"(v[i]) : "r"(stg + ((lane >> 3) & 1) * 8192 + row * 128 + ((((lane & 4) + i) ^ (row & 7)) << 4) + q4 * 4) : "memory");
      __stcg(xr + XR_CAND + cw * 64 + 32 + lane, make_uint4(ln_apply(v[0], rn, ri), ln_apply(v[1], rn, ri), ln_apply(v[2], rn, ri), ln_apply(v[3], rn, ri)));
      __stcg(xr + XR_CAND + cw * 64 + lane, make_uint4(v[0], v[1], v[2], v[3]));
      sched_fence(stg);
      const uint32_t na = __shfl_sync(~0u, nm2, r0 * 2), nb = __shfl_sync(~0u, nm2, r0 * 2 + 16);
      const float ia = __shfl_sync(~0u, inv, r0 * 2), ib = __shfl_sync(~0u, inv, r0 * 2 + 16);
#pragma unroll
      for (int i = 0; i < 32; i++) hp[i] = hadd2_bf(hp[i], ln_apply(hp[i], (i & 1) ? nb : na, (i & 1) ? ib : ia));
      __syncwarp();
      stage_store_128(stg, lane, hp);
      asm volatile("fence.proxy.async.shared::cta;" ::: "memory");
      publish(B_OUT3 - B_PUB);
    }
    uint32_t wd[16][4];
    sched_fence(stg);
    if (ffn) mbar_wait_c(B(B_FULL3 + 5 * w), 1 - w);
    auto load_wd = [&](int h) {
#pragma unroll
      for (int i = h; i < 16; i += 2)
        asm volatile("ldmatrix.sync.aligned.m8n8.x4.trans.shared.b16 {%0,%1,%2,%3}, [%4];"
                     : "=r"(wd[i][0]), "=r"(wd[i][1]), "=r"(wd[i][2]), "=r"(wd[i][3])
                     : "r"(sb + OFF_R3 + 5 * w * SLOT + (2 * (cw & 3) + (i >> 3)) * 4096 + (h * 16 + (lane & 7) + (lane >> 4) * 8) * 128 +
                           (((2 * ((i >> 1) & 3) + ((lane >> 3) & 1)) ^ (lane & 7)) << 4)) : "memory");
    };
    load_wd(0);
    __syncwarp();
    cluster_arrive();
    const char* xsrc = reinterpret_cast<const char*>(g_xr + (r0 >> 1) * XR_SIZE + XR_CAND + 32 + (cw >> 1) * 4 + q4);
    asm volatile("" : "+l"(xsrc));
    sched_fence(stg);
    TL(2, 22, tid == 128);
    mbar_wait_c(B(B_OUT2), 0);
    TL(2, 14, tid == 128);
    if (ffn) {
      uint4 xb[2];
      poll_chunks(xb, reinterpret_cast<const uint4*>(xsrc + *reinterpret_cast<const uint32_t*>(sp + OFF_MISC + 8 + (r0 & 1) * 4)), 4 * XR_SIZE);
      __syncwarp();
      TL(2, 15, tid == 128);
      float d[8][4] = {};
#pragma unroll
      for (int n = 0; n < 32; n++) {
        if (n == 8) { sched_fence(stg); load_wd(1); }
        const int s = (n >> 4) * 4 + ((n >> 1) & 3), m = ((n >> 3) & 1) * 2 + (n & 1);
        const uint32_t* a = wf + 16 * s + 4 * m;
        mma16816(d[n & 7], a[0], a[1], a[2], a[3], (m & 2) ? xb[s >> 2].z : xb[s >> 2].x, (m & 2) ? xb[s >> 2].w : xb[s >> 2].y);
      }
      float v[8];
#pragma unroll
      for (int i = 0; i < 8; i++) {
        const float lo = (q4 & 1) ? d[2 + (i >> 2)][i & 3] : d[i >> 2][i & 3], hi = (q4 & 1) ? d[6 + (i >> 2)][i & 3] : d[4 + (i >> 2)][i & 3];
        v[i] = (q4 & 2) ? hi : lo;
      }
#pragma unroll
      for (int i = 0; i < 4; i++) v[i] = ((q4 & 2) ? v[i + 4] : v[i]) + __shfl_xor_sync(~0u, (q4 & 2) ? v[i] : v[i + 4], 2);
#pragma unroll
      for (int i = 0; i < 2; i++) v[i] = ((q4 & 1) ? v[i + 2] : v[i]) + __shfl_xor_sync(~0u, (q4 & 1) ? v[i] : v[i + 2], 1);
      float4* red = reinterpret_cast<float4*>(sp + SL_SCR * SLOT);
      reinterpret_cast<float2*>(red + cw * 16 + (q4 >> 1) * 8 + r0)[q4 & 1] = make_float2(v[0], v[1]);
      bar_sync(3, 256);
      TL(2, 16, tid == 128);
      const float4 z0 = red[lane], z1 = red[32 + lane], z2 = red[64 + lane], z3 = red[96 + lane];
      const uint32_t ub = pack_bf16((z0.x + z1.x) + (z2.x + z3.x), (z0.y + z1.y) + (z2.y + z3.y));
      const uint32_t gb = pack_bf16((z0.z + z1.z) + (z2.z + z3.z), (z0.w + z1.w) + (z2.w + z3.w));
      const float g0 = bf_lo(gb), g1 = bf_hi(gb);
      const uint32_t sg = pack_bf16(g0 * sigmoid(g0), g1 * sigmoid(g1));
      const uint32_t act = pack_bf16(bf_lo(sg) * bf_lo(ub), bf_hi(sg) * bf_hi(ub));
      const uint32_t pr = __byte_perm(act, __shfl_xor_sync(~0u, act, 1), (lane & 1) ? 0x3276 : 0x5410);
      const int src = q4 * 2 + (r0 & 1);
      const uint32_t a0 = __shfl_sync(~0u, pr, src), a1 = __shfl_sync(~0u, pr, src + 8), a2 = __shfl_sync(~0u, pr, src + 16), a3 = __shfl_sync(~0u, pr, src + 24);
      TL(2, 17, tid == 128);
      float y[8][4] = {};
#pragma unroll
      for (int i = 0; i < 8; i++) mma16816(y[i], wd[2 * i][0], wd[2 * i][1], wd[2 * i][2], wd[2 * i][3], a0, a1);
#pragma unroll
      for (int i = 0; i < 8; i++) mma16816(y[i], wd[2 * i + 1][0], wd[2 * i + 1][1], wd[2 * i + 1][2], wd[2 * i + 1][3], a2, a3);
      float2* yd = reinterpret_cast<float2*>(g_xr + (cw * 16 + 2 * q4) * XR_SIZE + XR_Y + fid * 4) + r0;
#pragma unroll
      for (int j = 0; j < 2; j++) {
        float v[4];
#pragma unroll
        for (int e = 0; e < 4; e++) {
          const float lo = (q4 & 1) ? y[4 * j + 1][e] : y[4 * j][e], hi = (q4 & 1) ? y[4 * j + 3][e] : y[4 * j + 2][e];
          v[e] = (q4 & 2) ? hi : lo;
        }
        __stcg(yd + j * 16 * XR_SIZE, make_float2(v[0], v[1]));
        __stcg(yd + j * 16 * XR_SIZE + 2 * XR_SIZE, make_float2(v[2], v[3]));
      }
    }
    TL(2, 18, tid == 128);
    cluster_wait();
    if (rid == 127 && ct < C_NUM) g_cnt[ct] = 0;
    if (cw < 2) {
      const int tok = (lane >> 1) & 1, pair = cw * 2 + (lane & 1);
      uint32_t* const dst = reinterpret_cast<uint32_t*>(out + (size_t)(~*reinterpret_cast<const uint32_t*>(sp + OFF_MISC + tok * 4) & 0x7FF) * DM) + rid * 4 + pair;
      idle(ffn ? Y_CLK : Y_CLK + 2000);
      const bool fin = mbar_test(B(B_FIN), 0);
      uint4 op = lds128(sb + OFF_MISC + 128 + (tok * 4 + pair) * 16);
      uint4 z[7];
      poll_chunks(z, xr + XR_Y + (lane >> 1) * 4 + pair, 64);
      __syncwarp();
      TL(2, 19, tid == 128);
      if (!fin) { mbar_wait_c(B(B_FIN), 0); op = lds128(sb + OFF_MISC + 128 + (tok * 4 + pair) * 16); }
      auto F = [](uint32_t u) { return __uint_as_float(u); };
      const float v0 = ((F(z[0].x) + F(z[1].x)) + (F(z[2].x) + F(z[3].x))) + ((F(z[4].x) + F(z[5].x)) + F(z[6].x));
      const float v1 = ((F(z[0].y) + F(z[1].y)) + (F(z[2].y) + F(z[3].y))) + ((F(z[4].y) + F(z[5].y)) + F(z[6].y));
      const float v2 = ((F(z[0].z) + F(z[1].z)) + (F(z[2].z) + F(z[3].z))) + ((F(z[4].z) + F(z[5].z)) + F(z[6].z));
      const float v3 = ((F(z[0].w) + F(z[1].w)) + (F(z[2].w) + F(z[3].w))) + ((F(z[4].w) + F(z[5].w)) + F(z[6].w));
      float ya = (tok ? v1 : v0) + __shfl_xor_sync(~0u, tok ? v0 : v1, 2), yb = (tok ? v3 : v2) + __shfl_xor_sync(~0u, tok ? v2 : v3, 2);
#pragma unroll
      for (int o = 4; o < 32; o <<= 1) { ya += __shfl_xor_sync(~0u, ya, o); yb += __shfl_xor_sync(~0u, yb, o); }
      const uint32_t yp = pack_bf16(ya, yb);
      if (lane < 4) *dst = hadd2_bf(op.x, hadd2_bf(op.y, pack_bf16(bf_lo(yp) * F(op.z), bf_hi(yp) * F(op.z))));
      TL(2, 21, tid == 128);
    }
    TL(2, 20, tid == 128);
    TL_DUMP();
  }
}

typedef CUresult (*EncodeFn)(CUtensorMap*, CUtensorMapDataType, cuuint32_t, void*, const cuuint64_t*, const cuuint64_t*, const cuuint32_t*,
                             const cuuint32_t*, CUtensorMapInterleave, CUtensorMapSwizzle, CUtensorMapL2promotion, CUtensorMapFloatOOBfill);
EncodeFn g_enc = nullptr;

void map2(CUtensorMap* m, const void* ptr, uint64_t rows, uint64_t cols, uint32_t bc, uint32_t br) {
  const CUtensorMapSwizzle sw = bc == 64 ? CU_TENSOR_MAP_SWIZZLE_128B : CU_TENSOR_MAP_SWIZZLE_64B;
  cuuint64_t gd[2] = {cols, rows}, gs[1] = {cols * 2};
  cuuint32_t bd[2] = {bc, br}, es[2] = {1, 1};
  g_enc(m, CU_TENSOR_MAP_DATA_TYPE_BFLOAT16, 2, (void*)ptr, gd, gs, bd, es, CU_TENSOR_MAP_INTERLEAVE_NONE, sw,
        CU_TENSOR_MAP_L2_PROMOTION_L2_128B, CU_TENSOR_MAP_FLOAT_OOB_FILL_NONE);
}
void map3(CUtensorMap* m, const void* ptr, uint64_t rows, uint64_t cols, uint32_t br, uint32_t bch, uint32_t bc = 64) {
  cuuint64_t gd[3] = {bc, rows, cols / bc}, gs[2] = {cols * 2, bc * 2};
  cuuint32_t bd[3] = {bc, br, bch}, es[3] = {1, 1, 1};
  g_enc(m, CU_TENSOR_MAP_DATA_TYPE_BFLOAT16, 3, (void*)ptr, gd, gs, bd, es, CU_TENSOR_MAP_INTERLEAVE_NONE, bc == 64 ? CU_TENSOR_MAP_SWIZZLE_128B : CU_TENSOR_MAP_SWIZZLE_64B,
        CU_TENSOR_MAP_L2_PROMOTION_L2_128B, CU_TENSOR_MAP_FLOAT_OOB_FILL_NONE);
}

}

extern "C" void kernel_launch(void* const* d_in, const int* in_sizes, int n_in, void* d_out, int out_size) {
  const __nv_bfloat16* x = (const __nv_bfloat16*)d_in[0];
  const __nv_bfloat16* ckv = (const __nv_bfloat16*)d_in[1];
  const __nv_bfloat16* wq = (const __nv_bfloat16*)d_in[2];
  const __nv_bfloat16* wk = (const __nv_bfloat16*)d_in[3];
  const __nv_bfloat16* wv = (const __nv_bfloat16*)d_in[4];
  const __nv_bfloat16* wo = (const __nv_bfloat16*)d_in[5];
  const __nv_bfloat16* w_r = (const __nv_bfloat16*)d_in[7];
  const __nv_bfloat16* wgate = (const __nv_bfloat16*)d_in[8];
  const __nv_bfloat16* wup = (const __nv_bfloat16*)d_in[9];
  const __nv_bfloat16* wdown = (const __nv_bfloat16*)d_in[10];
  __nv_bfloat16* out = (__nv_bfloat16*)d_out;

  if (!g_enc) {
    void* fn = nullptr;
    cudaDriverEntryPointQueryResult qr;
    cudaGetDriverEntryPoint("cuTensorMapEncodeTiled", &fn, cudaEnableDefault, &qr);
    g_enc = (EncodeFn)fn;
    cudaFuncSetAttribute(fused_kernel, cudaFuncAttributeMaxDynamicSharedMemorySize, SMEM_BYTES);
  }
  void *xn, *qkv;
  cudaGetSymbolAddress(&xn, g_xn);
  cudaGetSymbolAddress(&qkv, g_qkv);

  Params p;
  map2(&p.xn, xn, SEQ, DM, 64, 128);
  map2(&p.ckv, ckv, SEQ, DC, 64, 128);
  map3(&p.wq, wq, DM, NQ, 64, 2);
  map3(&p.wk, wk, DC, NQ, 64, 2);
  map3(&p.wv, wv, DC, NQ, 64, 2);
  map3(&p.kv, qkv, 3 * SEQ, NQ, 128, 1);
  map2(&p.ctx_ld, qkv, SEQ, NQ, 64, 128);
  map3(&p.ctx_st, qkv, SEQ, NQ, 64, 1, 32);
  map3(&p.wo, wo, NQ, DM, 64, 1);
  map3(&p.x, x, SEQ, DM, 64, 1);
  map3(&p.wd, wdown, FF, DM, 32, 8);
  map2(&p.out, out, SEQ, DM, 64, 64);
  map2(&p.wg, wgate, DM, FF, 32, 128);
  map2(&p.wu, wup, DM, FF, 32, 128);
  fused_kernel<<<128, 384, SMEM_BYTES, cudaStreamPerThread>>>(x, wq, w_r, out, p);
}
```

```cpp
#include <cuda_runtime.h>
#include <cuda_bf16.h>
#include <cuda.h>
#include <stdint.h>
#include <type_traits>

#pragma nv_diag_suppress 549
namespace {

constexpr int SEQ = 2048, DM = 1024, NH = 32, HD = 128, DC = 512, NQ = NH * HD, FF = 3584;

__device__ __align__(1024) __nv_bfloat16 g_xn[SEQ * DM];
__device__ __align__(1024) __nv_bfloat16 g_qkv[3 * SEQ * NQ];
constexpr int XR_PS = 0;
constexpr int XR_KEY = 128;
constexpr int XR_FLAG = 132;
constexpr int XR_CAND = 136;
constexpr int XR_Y = 648;
constexpr int XR_SIZE = 1104;
__device__ __align__(1024) uint4 g_xr[128 * XR_SIZE];
constexpr int C_LN = 0, C_QKV = 16, C_CTX = 32, C_NUM = 64;
__device__ unsigned g_cnt[C_NUM];

#define TL(k, i, cond) do {} while (0)
#define TL_BYTES 0
#define TL_INIT() do {} while (0)
#define TL_DUMP() do {} while (0)
#define TC(g, i) do {} while (0)
#define TS(i) do {} while (0)
#undef TCLK
#define TCLK 0

__device__ __forceinline__ uint32_t s2u(const void* p) { return (uint32_t)__cvta_generic_to_shared(p); }
__device__ __forceinline__ void mbar_init(uint32_t b, uint32_t c) { asm volatile("mbarrier.init.shared::cta.b64 [%0], %1;" ::"r"(b), "r"(c) : "memory"); }
__device__ __forceinline__ void mbar_expect(uint32_t b, uint32_t bytes) { asm volatile("mbarrier.arrive.expect_tx.shared::cta.b64 _, [%0], %1;" ::"r"(b), "r"(bytes) : "memory"); }
__device__ __forceinline__ void mbar_arrive(uint32_t b) { asm volatile("mbarrier.arrive.shared::cta.b64 _, [%0];" ::"r"(b) : "memory"); }
__device__ __forceinline__ bool mbar_test(uint32_t b, uint32_t ph) {
  uint32_t ok;
  asm volatile("{\n.reg .pred p;\nmbarrier.test_wait.parity.shared::cta.b64 p, [%1], %2;\nselp.u32 %0, 1, 0, p;\n}" : "=r"(ok) : "r"(b), "r"(ph) : "memory");
  return ok;
}
__device__ __forceinline__ void mbar_wait(uint32_t b, uint32_t ph) {
  asm volatile(
      "{\n.reg .pred p;\n.reg .u32 n;\nmov.u32 n, 0;\n"
      "LW:\nmbarrier.try_wait.parity.shared::cta.b64 p, [%0], %1, 20000;\n@p bra LD;\n"
      "add.u32 n, n, 1;\nsetp.lt.u32 p, n, 0x40000;\n@p bra LW;\ntrap;\nLD:\n}" ::"r"(b), "r"(ph) : "memory");
}
__device__ __forceinline__ void mbar_wait_c(uint32_t b, uint32_t ph) {
  asm volatile(
      "{\n.reg .pred p;\n.reg .u32 n;\nmov.u32 n, 0;\n"
      "LW:\nmbarrier.try_wait.parity.shared::cta.b64 p, [%0], %1;\n@p bra LD;\n"
      "add.u32 n, n, 1;\nsetp.lt.u32 p, n, 0x100000;\n@p bra LW;\ntrap;\nLD:\n}" ::"r"(b), "r"(ph) : "memory");
}
__device__ __forceinline__ bool mbar_try(uint32_t b, uint32_t ph) {
  uint32_t ok;
  asm volatile("{\n.reg .pred p;\nmbarrier.try_wait.parity.shared::cta.b64 p, [%1], %2;\nselp.u32 %0, 1, 0, p;\n}" : "=r"(ok) : "r"(b), "r"(ph) : "memory");
  return ok;
}
#define UNLIKELY(c) __builtin_expect(!!(c), 0)
__device__ __forceinline__ uint32_t pinned(uint32_t v) { uint32_t r; asm volatile("mov.b32 %0, %1;" : "=r"(r) : "r"(v)); return r; }
__device__ __forceinline__ bool elect_one() {
  uint32_t p;
  asm volatile("{\n.reg .pred p;\nelect.sync _|p, 0xFFFFFFFF;\nselp.u32 %0, 1, 0, p;\n}" : "=r"(p));
  return p;
}
__device__ __forceinline__ int lane_id() { int r; asm volatile("mov.u32 %0, %%laneid;" : "=r"(r)); return r; }
template <bool SLEEP = false>
__device__ __forceinline__ void spin_until_ge(const unsigned* p, unsigned target) {
  asm volatile(
      "{\n.reg .pred p, q;\n.reg .u32 n, v;\nmov.u32 n, 0;\nsetp.ne.u32 q, %2, 0;\n"
      "LW:\nld.acquire.gpu.global.u32 v, [%0];\nsetp.ge.u32 p, v, %1;\n@p bra LD;\n@q nanosleep.u32 200;\n"
      "add.u32 n, n, 1;\nsetp.lt.u32 p, n, 0x400000;\n@p bra LW;\ntrap;\nLD:\n}" ::"l"(p), "r"(target), "n"((int)SLEEP) : "memory");
}
template <int N>
__device__ __forceinline__ void poll_chunks(uint4 (&v)[N], const uint4* p, int stride) {
  uint32_t m[N];
#pragma unroll
  for (int i = 0; i < N; i++) { m[i] = ~0u; v[i] = make_uint4(0, 0, 0, 0); }
#pragma unroll 1
  for (int n = 0; n < 0x400000; n++) {
    uint32_t a = 0;
#pragma unroll
    for (int i = 0; i < N; i++)
      asm volatile("{\n.reg .pred p;\nsetp.eq.u32 p, %5, 0xFFFFFFFF;\n@p ld.relaxed.gpu.global.v4.u32 {%0,%1,%2,%3}, [%4];\n}"
                   : "+r"(v[i].x), "+r"(v[i].y), "+r"(v[i].z), "+r"(v[i].w) : "l"(p + i * stride), "r"(m[i]) : "memory");
#pragma unroll
    for (int i = 0; i < N; i++) { m[i] = max(max(v[i].x, v[i].y), max(v[i].z, v[i].w)); a = max(a, m[i]); }
    if (__all_sync(~0u, a != 0xFFFFFFFFu)) break;
  }
}
__device__ __forceinline__ void fence_async_all() { asm volatile("fence.proxy.async;" ::: "memory"); }
__device__ __forceinline__ void bar_sync(int id, int n) { asm volatile("bar.sync %0, %1;" ::"r"(id), "r"(n) : "memory"); }
__device__ __forceinline__ void bar_arrive(int id, int n) { asm volatile("bar.arrive %0, %1;" ::"r"(id), "r"(n) : "memory"); }
__device__ __forceinline__ void cluster_arrive() { asm volatile("barrier.cluster.arrive.relaxed.aligned;" ::: "memory"); }
__device__ __forceinline__ void cluster_wait() { asm volatile("barrier.cluster.wait.acquire.aligned;" ::: "memory"); }
__device__ __forceinline__ void fence_gpu() { asm volatile("fence.acq_rel.gpu;" ::: "memory"); }
__device__ __forceinline__ void red_add(unsigned* p, unsigned v) { asm volatile("red.relaxed.gpu.global.add.u32 [%0], %1;" ::"l"(p), "r"(v) : "memory"); }
__device__ __forceinline__ void prefetch_tm(const CUtensorMap* m) { asm volatile("prefetch.tensormap [%0];" ::"l"(m) : "memory"); }

constexpr uint64_t EV_N = 0x1000000000000000ull, EV_F = 0x12F0000000000000ull;
__device__ __forceinline__ void tma_ld2(uint32_t dst, const CUtensorMap* m, uint32_t bar, int c0, int c1, bool ef = false) {
  asm volatile("cp.async.bulk.tensor.2d.shared::cta.global.mbarrier::complete_tx::bytes.L2::cache_hint [%0], [%1, {%3,%4}], [%2], %5;" ::"r"(dst), "l"(m), "r"(bar), "r"(c0), "r"(c1), "l"(ef ? EV_F : EV_N) : "memory");
}
__device__ __forceinline__ void tma_ld3(uint32_t dst, const CUtensorMap* m, uint32_t bar, int c0, int c1, int c2, bool ef = false) {
  asm volatile("cp.async.bulk.tensor.3d.shared::cta.global.mbarrier::complete_tx::bytes.L2::cache_hint [%0], [%1, {%3,%4,%5}], [%2], %6;" ::"r"(dst), "l"(m), "r"(bar), "r"(c0), "r"(c1), "r"(c2), "l"(ef ? EV_F : EV_N) : "memory");
}
__device__ __forceinline__ void tma_ld3_mc(uint32_t dst, const CUtensorMap* m, uint32_t bar, int c0, int c1, int c2, uint16_t mask, bool ef = false) {
  asm volatile("cp.async.bulk.tensor.3d.shared::cluster.global.mbarrier::complete_tx::bytes.multicast::cluster.L2::cache_hint [%0], [%1, {%3,%4,%5}], [%2], %6, %7;" ::"r"(dst), "l"(m), "r"(bar), "r"(c0), "r"(c1), "r"(c2), "h"(mask), "l"(ef ? EV_F : EV_N) : "memory");
}
__device__ __forceinline__ void tma_pf3(const CUtensorMap* m, int c0, int c1, int c2) {
  asm volatile("cp.async.bulk.prefetch.tensor.3d.L2.global [%0, {%1,%2,%3}];" ::"l"(m), "r"(c0), "r"(c1), "r"(c2) : "memory");
}
__device__ __forceinline__ void l2_prefetch(const void* p, uint32_t bytes) { asm volatile("cp.async.bulk.prefetch.L2.global [%0], %1;" ::"l"(p), "r"(bytes) : "memory"); }

__device__ __forceinline__ void wg_fence() { asm volatile("wgmma.fence.sync.aligned;" ::: "memory"); }
__device__ __forceinline__ void wg_commit() { asm volatile("wgmma.commit_group.sync.aligned;" ::: "memory"); }
template <int N> __device__ __forceinline__ void wg_wait() { asm volatile("wgmma.wait_group.sync.aligned %0;" ::"n"(N) : "memory"); }
template <int N> __device__ __forceinline__ void reg_alloc() { asm volatile("setmaxnreg.inc.sync.aligned.u32 %0;" ::"n"(N)); }
template <int N> __device__ __forceinline__ void reg_dealloc() { asm volatile("setmaxnreg.dec.sync.aligned.u32 %0;" ::"n"(N)); }
template <int N> __device__ __forceinline__ void fence_regs(float* d) {
#pragma unroll
  for (int i = 0; i < N; i++) asm volatile("" : "+f"(d[i])::"memory");
}
template <int N> __device__ __forceinline__ void fence_regs(uint32_t* d) {
#pragma unroll
  for (int i = 0; i < N; i++) asm volatile("" : "+r"(d[i])::"memory");
}

__device__ __forceinline__ uint64_t mk_desc(uint32_t addr, uint32_t lbo, uint32_t sbo, uint32_t swz) {
  uint32_t lo = ((addr & 0x3FFFF) >> 4) | ((lbo >> 4) << 16);
  uint32_t hi = (sbo >> 4) | (swz << 30);
  return ((uint64_t)hi << 32) | lo;
}
__device__ __forceinline__ uint64_t desc_add(uint64_t d, uint32_t bytes) {
  uint32_t lo = (uint32_t)d + (bytes >> 4);
  return (d & 0xFFFFFFFF00000000ull) | lo;
}

#define R8(b) "+f"(d[b + 0]), "+f"(d[b + 1]), "+f"(d[b + 2]), "+f"(d[b + 3]), "+f"(d[b + 4]), "+f"(d[b + 5]), "+f"(d[b + 6]), "+f"(d[b + 7])
#define REGS32 "%0,%1,%2,%3,%4,%5,%6,%7,%8,%9,%10,%11,%12,%13,%14,%15,%16,%17,%18,%19,%20,%21,%22,%23,%24,%25,%26,%27,%28,%29,%30,%31"
#define REGS64 REGS32 ",%32,%33,%34,%35,%36,%37,%38,%39,%40,%41,%42,%43,%44,%45,%46,%47,%48,%49,%50,%51,%52,%53,%54,%55,%56,%57,%58,%59,%60,%61,%62,%63"
#define REGS128 REGS64 ",%64,%65,%66,%67,%68,%69,%70,%71,%72,%73,%74,%75,%76,%77,%78,%79,%80,%81,%82,%83,%84,%85,%86,%87,%88,%89,%90,%91,%92,%93,%94,%95," \
               "%96,%97,%98,%99,%100,%101,%102,%103,%104,%105,%106,%107,%108,%109,%110,%111,%112,%113,%114,%115,%116,%117,%118,%119,%120,%121,%122,%123,%124,%125,%126,%127"

template <int TB>
__device__ __forceinline__ void mma_n256_ss(float (&d)[128], uint64_t a, uint64_t b, int acc) {
  asm volatile("{\n.reg .pred p;\nsetp.ne.b32 p, %130, 0;\n"
               "wgmma.mma_async.sync.aligned.m64n256k16.f32.bf16.bf16 {" REGS128 "}, %128, %129, p, 1, 1, 0, %131;\n}\n"
               : R8(0), R8(8), R8(16), R8(24), R8(32), R8(40), R8(48), R8(56), R8(64), R8(72), R8(80), R8(88), R8(96), R8(104), R8(112), R8(120)
               : "l"(a), "l"(b), "r"(acc), "n"(TB));
}
template <int TB>
__device__ __forceinline__ void mma_n128_ss(float* d, uint64_t a, uint64_t b, int acc) {
  asm volatile("{\n.reg .pred p;\nsetp.ne.b32 p, %66, 0;\n"
               "wgmma.mma_async.sync.aligned.m64n128k16.f32.bf16.bf16 {" REGS64 "}, %64, %65, p, 1, 1, 0, %67;\n}\n"
               : R8(0), R8(8), R8(16), R8(24), R8(32), R8(40), R8(48), R8(56)
               : "l"(a), "l"(b), "r"(acc), "n"(TB));
}
template <int TB>
__device__ __forceinline__ void mma_n128_rs(float* d, const uint32_t* a, uint64_t b, int acc) {
  asm volatile("{\n.reg .pred p;\nsetp.ne.b32 p, %69, 0;\n"
               "wgmma.mma_async.sync.aligned.m64n128k16.f32.bf16.bf16 {" REGS64 "}, {%64,%65,%66,%67}, %68, p, 1, 1, %70;\n}\n"
               : R8(0), R8(8), R8(16), R8(24), R8(32), R8(40), R8(48), R8(56)
               : "r"(a[0]), "r"(a[1]), "r"(a[2]), "r"(a[3]), "l"(b), "r"(acc), "n"(TB));
}
__device__ __forceinline__ void mma_n64_rs(float* d, const uint32_t* a, uint64_t b, int acc) {
  asm volatile("{\n.reg .pred p;\nsetp.ne.b32 p, %37, 0;\n"
               "wgmma.mma_async.sync.aligned.m64n64k16.f32.bf16.bf16 {" REGS32 "}, {%32,%33,%34,%35}, %36, p, 1, 1, 0;\n}\n"
               : R8(0), R8(8), R8(16), R8(24)
               : "r"(a[0]), "r"(a[1]), "r"(a[2]), "r"(a[3]), "l"(b), "r"(acc));
}
#define W8(b) "=f"(d[b + 0]), "=f"(d[b + 1]), "=f"(d[b + 2]), "=f"(d[b + 3]), "=f"(d[b + 4]), "=f"(d[b + 5]), "=f"(d[b + 6]), "=f"(d[b + 7])
__device__ __forceinline__ void mma_n128_rs0(float* d, const uint32_t* a, uint64_t b) {
  asm volatile("wgmma.mma_async.sync.aligned.m64n128k16.f32.bf16.bf16 {" REGS64 "}, {%64,%65,%66,%67}, %68, 0, 1, 1, 0;\n"
               : W8(0), W8(8), W8(16), W8(24), W8(32), W8(40), W8(48), W8(56)
               : "r"(a[0]), "r"(a[1]), "r"(a[2]), "r"(a[3]), "l"(b));
}
__device__ __forceinline__ void mma_n64_rs0(float* d, const uint32_t* a, uint64_t b) {
  asm volatile("wgmma.mma_async.sync.aligned.m64n64k16.f32.bf16.bf16 {" REGS32 "}, {%32,%33,%34,%35}, %36, 0, 1, 1, 0;\n"
               : W8(0), W8(8), W8(16), W8(24)
               : "r"(a[0]), "r"(a[1]), "r"(a[2]), "r"(a[3]), "l"(b));
}
__device__ __forceinline__ uint32_t pack_bf16(float lo, float hi) {
  uint32_t r;
  asm("cvt.rn.bf16x2.f32 %0, %1, %2;" : "=r"(r) : "f"(hi), "f"(lo));
  return r;
}
__device__ __forceinline__ float bf_lo(uint32_t v) { return __uint_as_float(v << 16); }
__device__ __forceinline__ float bf_hi(uint32_t v) { return __uint_as_float(v & 0xFFFF0000u); }
__device__ __forceinline__ float bf_round(float v) { return bf_lo(pack_bf16(v, v)); }
__device__ __forceinline__ void stsm4(uint32_t addr, uint32_t r0, uint32_t r1, uint32_t r2, uint32_t r3) {
  asm volatile("stmatrix.sync.aligned.m8n8.x4.shared.b16 [%0], {%1,%2,%3,%4};" ::"r"(addr), "r"(r0), "r"(r1), "r"(r2), "r"(r3) : "memory");
}
__device__ __forceinline__ uint4 lds128(uint32_t addr) {
  uint4 v;
  asm volatile("ld.shared.v4.u32 {%0,%1,%2,%3}, [%4];" : "=r"(v.x), "=r"(v.y), "=r"(v.z), "=r"(v.w) : "r"(addr));
  return v;
}
__device__ __forceinline__ float ex2(float x) {
  float y;
  asm("ex2.approx.ftz.f32 %0, %1;" : "=f"(y) : "f"(x));
  return y;
}
__device__ __forceinline__ void pin_order(float v, uint32_t dummy) {
  asm volatile("{\n.reg .pred p;\nsetp.eq.b32 p, %0, 0xFFFFFFFF;\n@p st.shared.b32 [%1], %0;\n}" ::"r"(__float_as_uint(v)), "r"(dummy) : "memory");
}
__device__ __forceinline__ float sigmoid(float x) {
  float y;
  asm("rcp.approx.ftz.f32 %0, %1;" : "=f"(y) : "f"(1.f + ex2(x * -1.4426950408889634f)));
  return y;
}
__device__ __forceinline__ void sched_fence(uint32_t dummy) {
  asm volatile("{\n.reg .pred p;\n.reg .u32 c;\nsetp.eq.b32 p, %0, 0xFFFFFFFF;\nmov.u32 c, %%clock;\n@p st.shared.b32 [%0], c;\n}" ::"r"(dummy) : "memory");
}
__device__ __forceinline__ void idle(int n) {
  asm volatile("{\n.reg .pred p;\n.reg .u32 a, b;\nmov.u32 a, %%clock;\nLI:\nmov.u32 b, %%clock;\nsub.u32 b, b, a;\nsetp.lt.u32 p, b, %0;\n@p bra LI;\n}" ::"r"(n) : "memory");
}
__device__ __forceinline__ void stage_store_128(uint32_t base, int lane, const uint32_t* pk) {
  const int row = (lane & 7) + ((lane >> 3) & 1) * 8;
  const uint32_t rb = base + row * 128;
  const int hi = lane >> 4;
#pragma unroll
  for (int j = 0; j < 8; j++) {
    const int chunk = 2 * j + hi;
    const uint32_t a = rb + (j >> 2) * 8192 + (((chunk & 7) ^ (lane & 7)) << 4);
    stsm4(a, pk[4 * j + 0], pk[4 * j + 1], pk[4 * j + 2], pk[4 * j + 3]);
  }
}
__device__ __forceinline__ void ln_round(float mean, float var, float& m_bf, float& inv_s) {
  const uint32_t mv = pack_bf16(mean, var);
  m_bf = bf_lo(mv);
  float sq, rc;
  asm("sqrt.approx.ftz.f32 %0, %1;" : "=f"(sq) : "f"(bf_round(bf_hi(mv) + 1e-5f)));
  asm("rcp.approx.ftz.f32 %0, %1;" : "=f"(rc) : "f"(bf_round(sq)));
  inv_s = rc;
}
__device__ __forceinline__ uint32_t hadd2_bf(uint32_t a, uint32_t b) {
  uint32_t r;
  asm("add.rn.bf16x2 %0, %1, %2;" : "=r"(r) : "r"(a), "r"(b));
  return r;
}
__device__ __forceinline__ uint32_t ln_apply(uint32_t h, uint32_t nm2, float inv_s) {
  const uint32_t d = hadd2_bf(h, nm2);
  return pack_bf16(bf_lo(d) * inv_s, bf_hi(d) * inv_s);
}
__device__ __forceinline__ void ldsm4(uint32_t* r, uint32_t addr) {
  asm volatile("ldmatrix.sync.aligned.m8n8.x4.shared.b16 {%0,%1,%2,%3}, [%4];" : "=r"(r[0]), "=r"(r[1]), "=r"(r[2]), "=r"(r[3]) : "r"(addr) : "memory");
}
__device__ __forceinline__ void mma16816(float* d, uint32_t a0, uint32_t a1, uint32_t a2, uint32_t a3, uint32_t b0, uint32_t b1) {
  asm volatile("mma.sync.aligned.m16n8k16.row.col.f32.bf16.bf16.f32 {%0,%1,%2,%3}, {%4,%5,%6,%7}, {%8,%9}, {%0,%1,%2,%3};"
               : "+f"(d[0]), "+f"(d[1]), "+f"(d[2]), "+f"(d[3]) : "r"(a0), "r"(a1), "r"(a2), "r"(a3), "r"(b0), "r"(b1));
}

template <class F>
__device__ __forceinline__ void unroll8(F f) {
  f(std::integral_constant<int, 0>{}); f(std::integral_constant<int, 1>{}); f(std::integral_constant<int, 2>{}); f(std::integral_constant<int, 3>{});
  f(std::integral_constant<int, 4>{}); f(std::integral_constant<int, 5>{}); f(std::integral_constant<int, 6>{}); f(std::integral_constant<int, 7>{});
}

constexpr float AT_C = 0.08838834764831845f * 1.4426950408889634f;
constexpr float AT_LO = 0x1p-40f, AT_HI = 0x1p40f;
constexpr int AT_R1 = 48;
template <int I0, int I1>
__device__ __forceinline__ void at_exp(float* S) {
#pragma unroll
  for (int i = I0; i < I1; i++) asm volatile("ex2.approx.ftz.f32 %0, %0;" : "+f"(S[i]));
}
template <int I0, int I1>
__device__ __forceinline__ void at_fin(const float* S, uint32_t* P) {
#pragma unroll
  for (int i = I0; i < I1; i += 4) {
    P[i / 2] = pack_bf16(S[i], S[i + 1]); P[i / 2 + 1] = pack_bf16(S[i + 2], S[i + 3]);
  }
}
__device__ __forceinline__ void at_sum(const uint32_t* P, bool half, float& l0, float& l1) {
  uint32_t u[4];
#pragma unroll
  for (int r = 0; r < 4; r++) {
    const uint32_t* q = P + (r >> 1) * 16 + (r & 1);
    u[r] = hadd2_bf(hadd2_bf(hadd2_bf(q[0], q[2]), hadd2_bf(q[4], q[6])), hadd2_bf(hadd2_bf(q[8], q[10]), hadd2_bf(q[12], q[14])));
  }
  u[0] = hadd2_bf(u[0], half ? 0u : u[2]);
  u[1] = hadd2_bf(u[1], half ? 0u : u[3]);
  l0 += bf_lo(u[0]) + bf_hi(u[0]);
  l1 += bf_lo(u[1]) + bf_hi(u[1]);
}
template <int j>
__device__ __forceinline__ void at_mask1(float* S, int d) {
  float dummy0 = 0.f, dummy1 = 0.f;
  float& lo0 = j < 7 ? S[4 * (j < 7 ? j + 1 : j) + 2] : dummy0;
  float& lo1 = j < 7 ? S[4 * (j < 7 ? j + 1 : j) + 3] : dummy1;
  asm("{\n.reg .pred p, q;\nsetp.lt.s32 p, %4, %5;\nsetp.le.s32 q, %4, %5;\n"
      "@p add.f32 %0, %0, 0fFF800000;\n@q add.f32 %1, %1, 0fFF800000;\n@p add.f32 %2, %2, 0fFF800000;\n@q add.f32 %3, %3, 0fFF800000;\n}"
      : "+f"(S[4 * j]), "+f"(S[4 * j + 1]), "+f"(lo0), "+f"(lo1) : "r"(d), "r"(8 * j));
}
__device__ __forceinline__ void at_mask(float* S, int r, int lane) {
  unroll8([&](auto jc) { at_mask1<decltype(jc)::value>(S, r + (lane >> 2) - (lane & 3) * 2); });
}
__device__ __forceinline__ uint32_t ldg32(const __nv_bfloat16* p) { return __ldcg(reinterpret_cast<const uint32_t*>(p)); }
__device__ __forceinline__ uint32_t ldg16x2(const __nv_bfloat16* p, int stride) {
  return (uint32_t)__ldcg(reinterpret_cast<const unsigned short*>(p)) | ((uint32_t)__ldcg(reinterpret_cast<const unsigned short*>(p + stride)) << 16);
}
__device__ __forceinline__ void slow_tile(float* O, uint32_t* Q, float& l0, float& l1, const __nv_bfloat16* wq, int row0, int head, int lane, uint32_t dummy) {
  const int r = lane >> 2, q = lane & 3;
#pragma unroll
  for (int i = 0; i < 64; i++) O[i] = 0.f;
  {
    const __nv_bfloat16* xa = g_xn + (size_t)(row0 + r) * DM + 2 * q;
    const __nv_bfloat16* wb = wq + (size_t)(2 * q) * NQ + head * HD + (r >> 1) * 8 + (r & 1);
#pragma unroll 1
    for (int k = 0; k < DM; k += 16) {
      const uint32_t a0 = ldg32(xa + k), a1 = ldg32(xa + k + 8 * DM), a2 = ldg32(xa + k + 8), a3 = ldg32(xa + k + 8 * DM + 8);
#pragma unroll
      for (int j = 0; j < 16; j++) {
        const __nv_bfloat16* wp = wb + (size_t)k * NQ + (j >> 2) * 32 + (j & 3) * 2;
        mma16816(O + 4 * j, a0, a1, a2, a3, ldg16x2(wp, NQ), ldg16x2(wp + 8 * NQ, NQ));
        if (j == 7) sched_fence(dummy);
      }
    }
  }
#pragma unroll
  for (int i = 0; i < 32; i++) Q[i] = pack_bf16(O[2 * i], O[2 * i + 1]);
#pragma unroll
  for (int i = 0; i < 64; i++) O[i] = 0.f;
  float m0 = -INFINITY, m1 = -INFINITY;
  l0 = l1 = 0.f;
#pragma unroll 1
  for (int kv = 0; kv <= row0; kv += 16) {
    float s[8] = {0.f, 0.f, 0.f, 0.f, 0.f, 0.f, 0.f, 0.f};
    const __nv_bfloat16* kp = g_qkv + (size_t)(SEQ + kv + r) * NQ + head * HD + 2 * q;
#pragma unroll
    for (int k = 0; k < 8; k++) {
      mma16816(s, Q[4 * k], Q[4 * k + 1], Q[4 * k + 2], Q[4 * k + 3], ldg32(kp + 16 * k), ldg32(kp + 16 * k + 8));
      mma16816(s + 4, Q[4 * k], Q[4 * k + 1], Q[4 * k + 2], Q[4 * k + 3], ldg32(kp + 8 * NQ + 16 * k), ldg32(kp + 8 * NQ + 16 * k + 8));
    }
#pragma unroll
    for (int i = 0; i < 8; i++)
      if (kv + (i >> 2) * 8 + 2 * q + (i & 1) > row0 + r + (i & 2) * 4) s[i] = -INFINITY;
    float a = fmaxf(fmaxf(fmaxf(s[0], s[1]), fmaxf(s[4], s[5])), m0), b = fmaxf(fmaxf(fmaxf(s[2], s[3]), fmaxf(s[6], s[7])), m1);
    a = fmaxf(a, __shfl_xor_sync(~0u, a, 1)); b = fmaxf(b, __shfl_xor_sync(~0u, b, 1));
    a = fmaxf(a, __shfl_xor_sync(~0u, a, 2)); b = fmaxf(b, __shfl_xor_sync(~0u, b, 2));
    const float c0 = ex2(m0 - a), c1 = ex2(m1 - b);
    m0 = a; m1 = b;
#pragma unroll
    for (int i = 0; i < 8; i++) s[i] = ex2(s[i] - ((i & 2) ? b : a));
    l0 = l0 * c0 + (s[0] + s[1]) + (s[4] + s[5]);
    l1 = l1 * c1 + (s[2] + s[3]) + (s[6] + s[7]);
    sched_fence(dummy);
    const uint32_t p0 = pack_bf16(s[0], s[1]), p1 = pack_bf16(s[2], s[3]), p2 = pack_bf16(s[4], s[5]), p3 = pack_bf16(s[6], s[7]);
    const __nv_bfloat16* vp = g_qkv + (size_t)(2 * SEQ + kv + 2 * q) * NQ + head * HD + r;
#pragma unroll
    for (int j = 0; j < 16; j++) {
      O[4 * j] *= c0; O[4 * j + 1] *= c0; O[4 * j + 2] *= c1; O[4 * j + 3] *= c1;
      mma16816(O + 4 * j, p0, p1, p2, p3, ldg16x2(vp + 8 * j, NQ), ldg16x2(vp + 8 * NQ + 8 * j, NQ));
      if (j == 7) sched_fence(dummy);
    }
  }
}

constexpr int P1_STAGE = 49152;
constexpr int SLOT = 32768;
constexpr int OFF_LN = 6 * SLOT, OFF_R3 = 0;
constexpr int OFF_BAR = 229376;
constexpr int OFF_MISC = OFF_BAR + 8 * 58;
constexpr int SMEM_BYTES = OFF_MISC + 2080 + TL_BYTES;
enum : int {
  B_FULL1 = 0, B_KF = 4, B_VF = 6, B_FULL3 = 8, B_XF = 14, B_LN = 15, B_DEP = 16, B_OUT2 = 22, B_FIN = 23, B_SET2 = 25, B_QP = 26, B_WF2 = 29,
  B_WF = 30, B_WR = 31,
  B_LND = 32,
  B_XE = 33, B_PUB = 34, B_OUT = 40, B_OUT3 = 41,
  B_EMPTY1 = 42, B_KE = 46, B_VE = 48, B_EMPTY3 = 50, B_WE = 56, B_NUM = 57
};
constexpr int OFF_STG = SLOT, SL_SCR = 2;
constexpr int PRE = 3;
constexpr int LN_PF = 4, LN_PFN = 2, LN_LD = 9;
constexpr int WQ_0 = 18, WQ_D = 4;
constexpr int W_G0 = 22;
constexpr int X_KB = 20, G_KB = 35;
constexpr int SL_NS = 600, SET_NS = 50;
constexpr int OUT_CLK = 500, Y_CLK = 400;
struct Params {
  CUtensorMap xn, ckv, wq, wk, wv, kv, ctx_ld, ctx_st, wo, x, wd, wg, wu, out;
};

__global__ void __cluster_dims__(2, 1, 1) __launch_bounds__(384, 1)
fused_kernel(const __nv_bfloat16* __restrict__ x, const __nv_bfloat16* __restrict__ wq, const __nv_bfloat16* __restrict__ w_r,
             __nv_bfloat16* __restrict__ out, const __grid_constant__ Params p) {
  extern __shared__ __align__(1024) uint8_t sp[];
  const uint32_t sb = s2u(sp);
  const uint32_t bar = sb + OFF_BAR;
  auto B = [&](int i) { return bar + 8 * i; };
  const int tid = threadIdx.x, warp = __shfl_sync(~0u, tid >> 5, 0), wg = warp >> 2, lane = tid & 31;
  const int cta = blockIdx.x, rank = cta & 1, cl = cta >> 1;
  const int mp = cl < 4 ? 1 : (cl < 36 ? (cl & 7) : (0x3207654 >> (4 * ((cl - 36) % 7))) & 7);
  const int gq = cl < 4 ? 4 + cl : (cl < 36 ? (cl - 4) >> 3 : 4 + (cl - 36) / 7);
  const int mt = 2 * mp + rank;
  const int ti = (gq & 3) * 2 + rank, hh = mp * 2 + (gq >> 2);
  const int rid = mt * 8 + gq;
  const int fid = mt * 7 + gq - 1;
  const bool ffn = gq > 0;
  uint4* const xr = g_xr + rid * XR_SIZE;
  TL_INIT();
  TL(0, 0, tid == 128);
  if (warp == 0) {
    if (elect_one()) {
#pragma unroll
      for (int kb = 0; kb < PRE; kb++) mbar_init(B(B_FULL1 + kb), 1);
      asm volatile("fence.mbarrier_init.release.cluster;" ::: "memory");
    }
    __syncwarp();
    cluster_arrive();
    if (elect_one()) {
#pragma unroll
      for (int kb = 0; kb < PRE; kb++) {
        mbar_expect(B(B_FULL1 + kb), P1_STAGE);
        tma_ld2(sb + kb * P1_STAGE, &p.ckv, B(B_FULL1 + kb), kb * 64, mt * 128);
        tma_ld3(sb + kb * P1_STAGE + 16384 + rank * 16384, &p.wk, B(B_FULL1 + kb), 0, kb * 64, gq * 4 + rank * 2);
        tma_ld3(sb + kb * P1_STAGE + 32768 - rank * 16384, &p.wk, B(B_FULL1 + kb), 0, kb * 64, gq * 4 + 2 - rank * 2);
      }
    }
  } else if (elect_one()) {
#pragma unroll 1
    for (int i = PRE + warp - 1; i < B_NUM; i += 11)
      mbar_init(B(i), i >= B_EMPTY1 ? 16 : (i >= B_XE ? 8 : (i == B_LND ? 3 : (i >= B_WF ? 2 : 1))));
    asm volatile("fence.mbarrier_init.release.cluster;" ::: "memory");
  }
  __syncwarp();
  if (warp) cluster_arrive();
  if (wg == 0) {
    reg_dealloc<40>();
    if (warp == 1 && elect_one()) {
      if (mt >= 2 * PRE) tma_pf3(&p.wk, 0, mp * 64, gq * 4 + rank * 2);
      if (gq >= PRE) asm volatile("cp.async.bulk.prefetch.tensor.2d.L2.global [%0, {%1,%2}];" ::"l"(&p.ckv), "r"(gq * 64), "r"(mt * 128) : "memory");
    } else if (warp == 2 && elect_one()) {
      prefetch_tm(&p.wv); prefetch_tm(&p.wq); prefetch_tm(&p.xn);
    }
    __syncwarp();
    cluster_wait();
    if (warp == 0) {
      int st = 0; uint32_t ph = 1;
#pragma unroll 1
      for (int t = 0; t < 6; t++) {
        const CUtensorMap* ma = t >= 4 ? &p.xn : &p.ckv;
        const CUtensorMap* mb = t >= 4 ? &p.wq : ((t & 1) ? &p.wv : &p.wk);
        const int nk = t >= 4 ? 16 : 8;
        const int row = (t < 4 ? mt : (t == 4 ? 15 - ti : ti)) * 128;
        const int col = t < 4 ? (gq + (t >> 1) * 8) * 4 + rank * 2 : (hh + rank * 16) * 2;
        if (t >= 4) mbar_wait(B(B_DEP + t - 4), 0);
#pragma unroll 1
        for (int kb = 0; kb < nk; kb++) {
          const uint32_t d = sb + st * P1_STAGE, fb = B(B_FULL1 + st);
          const int n = t * 8 + kb;
          if (n >= PRE) {
            mbar_wait_c(B(B_EMPTY1 + st), ph);
            if (elect_one()) {
              mbar_expect(fb, P1_STAGE);
              tma_ld2(d, ma, fb, kb * 64, row);
              tma_ld3_mc(d + 16384 + rank * 16384, mb, fb, 0, kb * 64, col, 3);
            }
          }
          if (t < 5 && elect_one()) {
            if (n >= LN_PF && n < LN_PF + LN_PFN) l2_prefetch(x + (size_t)cta * 16 * DM + (n - LN_PF) * (16 * DM / LN_PFN), 32768 / LN_PFN);
            if (n == LN_LD) {
              mbar_expect(B(B_LN), 32768);
              asm volatile("cp.async.bulk.shared::cluster.global.mbarrier::complete_tx::bytes [%0], [%1], %2, [%3];" ::"r"(sb + OFF_LN),
                           "l"(x + (size_t)cta * 16 * DM), "r"(32768), "r"(B(B_LN)) : "memory");
            }
            if (t < 3 && kb == 0) tma_pf3((t & 1) ? &p.wk : &p.wv, 0, mp * 64, (gq + ((t + 1) >> 1) * 8) * 4 + rank * 2);
            if (n >= WQ_0 && n < WQ_0 + 4 * WQ_D && (n - WQ_0) % WQ_D == 0) tma_pf3(&p.wq, 0, ((n - WQ_0) / WQ_D * 4 + (gq & 3)) * 64, (hh + rank * 16) * 2);
          }
          if (++st == 4) { st = 0; ph ^= 1; }
        }
      }
      if (elect_one()) { prefetch_tm(&p.kv); prefetch_tm(&p.ctx_ld); prefetch_tm(&p.wo); prefetch_tm(&p.wg); prefetch_tm(&p.wu); }
      auto load_kv = [&](int g, int isv) {
        const int h2 = g >= 17, sx = g - 17 * h2, n1 = h2 ? ti + 1 : 16 - ti;
        const int row = (1 + isv) * SEQ + (sx < n1 ? sx : 16 - sx) * 128, col = (hh + 16 * h2) * 2;
        const uint32_t d = sb + (isv ? 2 + 2 * (g & 1) : (g & 1)) * SLOT, fb = B(B_KF + 2 * isv + (g & 1));
        const bool ef = sx >= n1 || sx >= 8;
        const bool shared = sx != (h2 ? (ti & 6) + 1 : 15 - (ti & 6));
        const int h3 = g >= 16, s3 = g + 1 - 17 * h3;
        const int pb = ti < 2 ? (h3 ? (s3 >= 1 && s3 <= 8 ? 16 - s3 : -1) : (s3 < 16 ? s3 : -1)) : (ti >= 6 && h3 && s3 < 8 ? s3 : -1);
        mbar_wait_c(g < 2 ? B(B_EMPTY1 + (isv ? 1 + 2 * g : g)) : B(B_KE + 2 * isv + (g & 1)), g < 2 ? 1 : ((g >> 1) & 1) ^ 1);
        if (elect_one()) {
          mbar_expect(fb, SLOT);
          if (shared) {
            tma_ld3_mc(d + rank * 16384, &p.kv, fb, 0, row, col + rank, 3, ef);
          } else {
            tma_ld3(d, &p.kv, fb, 0, row, col, ef);
            tma_ld3(d + 16384, &p.kv, fb, 0, row, col + 1, ef);
          }
          if (pb >= 0) tma_pf3(&p.kv, 0, (1 + isv) * SEQ + pb * 128, (hh + 16 * h3) * 2 + rank);
        }
      };
      int nw = ffn ? 0 : 12;
      auto load_w = [&]() {
        const int c = nw < 8 ? (nw >> 2) + (nw & 2) : nw >> 1;
        if (elect_one()) {
          if (!(nw & 3)) mbar_expect(B(B_WF - (nw >> 3)), 32768);
          tma_ld2(sb + (c < 2 ? 3 : 4) * SLOT + c * 16384 + (nw & 1) * 8192, (nw & 1) ? &p.wg : &p.wu, B(B_WF - (nw >> 3)), fid * 32, c * 128, true);
        }
        nw++;
      };
#pragma unroll 1
      for (int g = 0; g < 34; g++) {
        if (g == 0 || g == 16) mbar_wait(B(B_DEP + 2 + (g > 0)), 0);
        load_kv(g, 0);
        if (g > 0) load_kv(g - 1, 1);
        if (g >= W_G0 && nw < 12 && __any_sync(~0u, mbar_test(B(B_QP + (nw >> 2)), 0))) load_w();
      }
      load_kv(33, 1);
#pragma unroll 1
      while (nw < 12) { mbar_wait(B(B_QP + (nw >> 2)), 0); load_w(); }
      if (elect_one()) { prefetch_tm(&p.wd); prefetch_tm(&p.x); prefetch_tm(&p.out); }
      auto load3 = [&](int kb, int sl) {
        if (elect_one()) {
          mbar_expect(B(B_FULL3 + sl), SLOT);
          tma_ld2(sb + OFF_R3 + sl * SLOT, &p.ctx_ld, B(B_FULL3 + sl), kb * 64, mt * 128);
          tma_ld3_mc(sb + OFF_R3 + sl * SLOT + 16384 + rank * 8192, &p.wo, B(B_FULL3 + sl), 0, kb * 64, gq * 2 + rank, 3);
        }
      };
      mbar_wait(B(B_DEP + 4), 0);
#pragma unroll
      for (int kb = 0; kb < 5; kb++) {
        mbar_wait_c(B(kb == 3 ? B_WE : (kb == 4 ? B_VE + 1 : B_KE + kb)), 0);
        load3(kb, kb);
      }
      if (elect_one()) mbar_arrive(B(B_FULL3 + 5));
#pragma unroll 1
      for (int r = 1; r < 11; r++) {
#pragma unroll
        for (int j = 0; j < 6; j++) {
          if (j == 5 && r == 10) break;
          if (j == 3 && r == 5) mbar_wait(B(B_DEP + 5), 0);
          mbar_wait_c(B(B_EMPTY3 + j), ~r & 1);
          load3(r * 6 + j - 1, j);
          if (j == 5 && r == 9 && elect_one()) l2_prefetch(xr, XR_CAND * 16);
        }
      }
      if (ffn) {
#pragma unroll
        for (int j = 1; j >= 0; j--) {
          mbar_wait(B(B_EMPTY3 + 5 * j), j);
          if (elect_one()) {
            mbar_expect(B(B_FULL3 + 5 * j), SLOT);
            tma_ld3(sb + OFF_R3 + 5 * j * SLOT, &p.wd, B(B_FULL3 + 5 * j), 0, fid * 32, 8 * j, true);
          }
        }
      }
    } else {
      if (warp >= 2) {
#pragma unroll 1
        for (int i = tid - 64; i < XR_CAND; i += 64) xr[i] = make_uint4(~0u, ~0u, ~0u, ~0u);
        if (warp == 2) { __syncwarp(); if (lane == 0) mbar_arrive(B(B_WR)); }
      }
      if (warp == 3) {
        float ws = 0.f;
#pragma unroll
        for (int j = 0; j < 4; j++) {
          const uint4 q = __ldg(reinterpret_cast<const uint4*>(w_r) + j * 32 + lane);
          ws += bf_lo(q.x) + bf_hi(q.x) + bf_lo(q.y) + bf_hi(q.y) + bf_lo(q.z) + bf_hi(q.z) + bf_lo(q.w) + bf_hi(q.w);
        }
#pragma unroll
        for (int o = 16; o; o >>= 1) ws += __shfl_xor_sync(~0u, ws, o);
        uint2* tab = reinterpret_cast<uint2*>(sp + OFF_MISC + 512);
        tab[lane] = make_uint2(0x3F803F80u, 0x3F803F80u);
        tab[32 + lane] = __ldg(reinterpret_cast<const uint2*>(w_r + gq * 128) + lane);
        if (lane == 0) *reinterpret_cast<float*>(sp + OFF_MISC + 1024) = ws;
        __syncwarp();
        if (lane == 0) mbar_arrive(B(B_WR));
      }
      if (tid == 32) TS(0);
      mbar_wait(B(B_LN), 0);
#pragma unroll 1
      for (int r = warp - 1; r < 16; r += 3) {
        uint4 v[4];
        float a0 = 0.f, a1 = 0.f, b0 = 0.f, b1 = 0.f;
#pragma unroll
        for (int j = 0; j < 4; j++) {
          v[j] = lds128(sb + OFF_LN + r * 2048 + lane * 16 + j * 512);
          const uint32_t u[4] = {v[j].x, v[j].y, v[j].z, v[j].w};
#pragma unroll
          for (int i = 0; i < 4; i++) { const float a = bf_lo(u[i]), b = bf_hi(u[i]); a0 += a; a1 += b; b0 = fmaf(a, a, b0); b1 = fmaf(b, b, b1); }
        }
        a0 += a1; b0 += b1;
#pragma unroll
        for (int o = 16; o; o >>= 1) { a0 += __shfl_xor_sync(~0u, a0, o); b0 += __shfl_xor_sync(~0u, b0, o); }
        const float mean = a0 * (1.f / DM);
        float mb, inv;
        ln_round(mean, fmaxf(fmaf(b0, 1.f / DM, -mean * mean), 0.f), mb, inv);
        inv *= AT_C;
        const uint32_t nm2 = pack_bf16(-mb, -mb);
        uint4* dst = reinterpret_cast<uint4*>(g_xn + (size_t)(cta * 16 + r) * DM) + lane;
#pragma unroll
        for (int j = 0; j < 4; j++)
          dst[j * 32] = make_uint4(ln_apply(v[j].x, nm2, inv), ln_apply(v[j].y, nm2, inv), ln_apply(v[j].z, nm2, inv), ln_apply(v[j].w, nm2, inv));
      }
      __syncwarp();
      if (lane == 0) {
        mbar_arrive(B(B_LND));
        fence_gpu();
        red_add(&g_cnt[C_LN + (cta >> 3)], 1);
      }
      TL(3, warp, lane == 0);
      __syncwarp();
      cluster_arrive();
      if (warp == 3) {
        if (lane == 0) {
#pragma unroll 1
          for (int i = 0; i < 6; i++) {
            const int c = i < 2 ? C_LN + (i ? ti : 15 - ti) : (i < 4 ? C_QKV + (i - 2) * 8 + mp : C_CTX + (i - 4) * 16 + mt);
            spin_until_ge<true>(&g_cnt[c], i < 2 ? 24 : 16);
            fence_async_all();
            mbar_arrive(B(B_DEP + i));
            TL(3, 4 + i, true);
          }
        }
      } else if (warp == 1 && elect_one()) {
        mbar_wait(B(B_WR), 0);
#pragma unroll 1
        for (int i = 0; i < 6; i++) {
          const int c = i < 2 ? C_QKV + gq + i * 8 : C_CTX + (i >> 2) * 16 + ((i == 3 || i == 4) ? ti : 15 - ti);
          mbar_wait(B(B_PUB + i), 0);
          if (i >= 2 && i < 5) {
            asm volatile("fence.proxy.async.shared::cta;" ::: "memory");
#pragma unroll 1
            for (int n = 0; n < 8; n++) {
              const int h = n >> 2, a = n & 3;
              asm volatile("cp.async.bulk.tensor.3d.global.shared::cta.bulk_group [%0, {%2,%3,%4}], [%1];" ::"l"(&p.ctx_st),
                           "r"(sb + (i == 4 ? 6 * SLOT + h * 16384 : (3 + 2 * h) * SLOT + (i - 2) * 16384) + a * 4096),
                           "r"(0), "r"((i == 2 ? 15 - ti : ti) * 128 + h * 64), "r"((hh + (i >> 2) * 16) * 4 + a) : "memory");
              asm volatile("cp.async.bulk.commit_group;\ncp.async.bulk.wait_group.read 0;" ::: "memory");
            }
            mbar_arrive(B(B_QP + i - 2));
            asm volatile("cp.async.bulk.wait_group 0;" ::: "memory");
          }
          fence_gpu();
          red_add(&g_cnt[c], 1);
          TS(1 + i);
        }
      }
      if (warp == 2) {
#pragma unroll 1
        for (int n = 0; n < 8; n++) {
          if (!(n & 3)) mbar_wait(B(B_XE), n >> 2);
          if ((n < 4 || ffn) && elect_one()) {
            const uint32_t fb = B(n < 4 ? B_XF : B_WF2), d = sb + 6 * SLOT + (n & 3) * 8192;
            if (!(n & 3)) mbar_expect(fb, 32768);
            if (n < 4) tma_ld3(d, &p.x, fb, 0, mt * 128 + (n >> 1) * 64, gq * 2 + (n & 1), true);
            else tma_ld2(d, (n & 1) ? &p.wg : &p.wu, fb, fid * 32, (4 + (n >> 1)) * 128, true);
          }
          __nanosleep(SL_NS);
        }
#pragma unroll 1
        for (int i = XR_CAND + lane; i < XR_SIZE; i += 32) { xr[i] = make_uint4(~0u, ~0u, ~0u, ~0u); __nanosleep(SET_NS); }
        __syncwarp();
        if (lane == 0) { fence_gpu(); mbar_arrive(B(B_SET2)); }
        TL(2, 26, lane == 0);
        __syncwarp();
      }
      __syncwarp();
      if (warp == 3) {
        mbar_wait(B(B_OUT), 0);
        uint4 kv[2];
        poll_chunks(kv, g_xr + ((lane >> 1) * 8 + gq) * XR_SIZE + XR_KEY + (lane & 1) * 2, 1);
        const uint32_t a1 = max(kv[0].x, kv[0].z), a2 = max(min(kv[0].x, kv[0].z), max(kv[0].y, kv[0].w));
        const uint32_t b1 = max(kv[1].x, kv[1].z), b2 = max(min(kv[1].x, kv[1].z), max(kv[1].y, kv[1].w));
        const uint32_t k1 = max(a1, b1), k2 = max(min(a1, b1), max(a2, b2));
        const uint32_t m1 = __reduce_max_sync(~0u, k1);
        const uint32_t m2 = __reduce_max_sync(~0u, k1 == m1 ? k2 : k1);
        auto cand = [&](uint32_t k) { return (((~k >> 7) & 15) * (8 * XR_SIZE) + ((~k >> 4) & 7) * 64) * 16; };
        const uint32_t o1 = cand(m1), o2 = cand(m2) + (((m1 ^ m2) & 0x7FF0) ? 0 : 256);
        if (lane == 0) {
          *reinterpret_cast<uint4*>(sp + OFF_MISC) = make_uint4(m1, m2, o1, o2);
          mbar_arrive(B(B_OUT2));
        }
        const uint32_t key = (lane & 4) ? m2 : m1;
        const uint4* src = g_xr + (((~key >> 7) & 15) * 8 + (rid >> 4)) * XR_SIZE;
        poll_chunks(kv, g_xr + (((lane & 4) ? o2 : o1) >> 4) + (rid >> 4) * XR_SIZE + XR_CAND + (rid & 12) + (lane & 3), 32);
        uint32_t u = key >> 16;
        u = (u & 0x8000u) ? (u & 0x7FFFu) : (~u & 0xFFFFu);
        const float rs = bf_round(sigmoid(__uint_as_float(u << 16)));
        if (lane < 8)
          *reinterpret_cast<uint4*>(sp + OFF_MISC + 128 + lane * 16) = make_uint4((rid & 2) ? ((rid & 1) ? kv[0].w : kv[0].z) : ((rid & 1) ? kv[0].y : kv[0].x),
              (rid & 2) ? ((rid & 1) ? kv[1].w : kv[1].z) : ((rid & 1) ? kv[1].y : kv[1].x), __float_as_uint(rs), 0);
#pragma unroll 1
        for (int n = 0; n < 0x400000; n++) {
          uint32_t v;
          asm volatile("ld.acquire.gpu.global.u32 %0, [%1];" : "=r"(v) : "l"(src + XR_FLAG) : "memory");
          if (__all_sync(~0u, v == 0)) break;
        }
        if (lane == 0) mbar_arrive(B(B_FIN));
      }
      if (warp == 1 && elect_one()) {
        mbar_wait(B(B_OUT3), 0);
        auto owner = [&]() {
          uint2 top;
          asm volatile("ld.shared.v2.u32 {%0,%1}, [%2];" : "=r"(top.x), "=r"(top.y) : "r"(sb + OFF_MISC) : "memory");
          return (0x7FFF - (top.x & 0x7FFF)) >> 7 == mt || (0x7FFF - (top.y & 0x7FFF)) >> 7 == mt;
        };
#pragma unroll 1
        for (int n = 0; n < 4; n++) {
          if (n && !(mbar_test(B(B_OUT2), 0) && owner())) idle(OUT_CLK);
          asm volatile("cp.async.bulk.tensor.2d.global.shared::cta.bulk_group [%0, {%2,%3}], [%1];" ::"l"(&p.out), "r"(sb + OFF_STG + n * 8192),
                       "r"(gq * 128 + (n & 1) * 64), "r"(mt * 128 + (n >> 1) * 64) : "memory");
        }
        asm volatile("cp.async.bulk.commit_group;" ::: "memory");
        mbar_wait(B(B_OUT2), 0);
        if (owner()) {
          asm volatile("cp.async.bulk.wait_group 0;" ::: "memory");
          asm volatile("st.release.gpu.global.u32 [%0], 0;" ::"l"(xr + XR_FLAG) : "memory");
        } else {
          asm volatile("cp.async.bulk.wait_group.read 0;" ::: "memory");
        }
        TL(2, 25, true);
      }
    }
    __syncwarp();
    if (warp == 0) cluster_arrive();
    cluster_wait();
    TL_DUMP();
    if (tid == 32) TS(8);
  } else {
    reg_alloc<232>();
    cluster_wait();
    const int w = wg - 1, cw = warp - 4;
    int lane = lane_id();
    const uint32_t stg = sb + OFF_STG + w * 16384 + (cw & 3) * 2048;
    auto publish = [&](int i) { __syncwarp(); if (lane == 0) mbar_arrive(B(B_PUB + i)); };
    uint32_t rbar;
    asm("mapa.shared::cluster.u32 %0, %1, %2;" : "=r"(rbar) : "r"(bar), "r"(lane & 1));
    auto release2 = [&](int i) { if (lane < 2) asm volatile("mbarrier.arrive.shared::cluster.b64 _, [%0];" ::"r"(rbar + 8 * i) : "memory"); };
    float R[128];
    float O[64], acc[64];
    uint32_t pk[64];
    uint32_t* const Q = pk;
    uint32_t P[32];
    auto packed = [&](int i) {
      const float* v = R + 16 * (i >> 1) + 2 * (i & 1);
      return make_uint4(pack_bf16(v[0], v[1]), pack_bf16(v[4], v[5]), pack_bf16(v[8], v[9]), pack_bf16(v[12], v[13]));
    };
    const uint32_t q_st = sb + (cw & 3) * 1024 + (lane >> 2) * 64 + (((lane & 3) ^ (lane >> 3)) << 4);
    const uint32_t q_ld = sb + (cw & 3) * 1024 + (lane & 15) * 64 + (((lane >> 4) ^ ((lane >> 1) & 3)) << 4);
    auto park = [&](uint32_t off, int i, uint4 v) {
      asm volatile("st.shared.v4.u32 [%0], {%1,%2,%3,%4};" ::"r"(q_st + off + (i >> 1) * 4096 + (i & 1) * 512), "r"(v.x), "r"(v.y), "r"(v.z), "r"(v.w) : "memory");
    };
    auto load_q = [&](uint32_t off, int k) { ldsm4(Q + 4 * k, ((q_ld + off) ^ ((k & 1) << 5)) + (k >> 1) * 4096); };
    {
      TL(0, 1, tid == 128);
      __nv_bfloat16* pdst = g_qkv;
      auto put2 = [&](int j) {
#pragma unroll
        for (int i = (j >> 1) * 4 + (j & 1); i < (j >> 1) * 4 + 4; i += 2)
          __stcs(reinterpret_cast<uint4*>(pdst + (i & 1) * 8 * NQ + (i >> 1) * 32), make_uint4(pk[4 * i], pk[4 * i + 1], pk[4 * i + 2], pk[4 * i + 3]));
      };
      const uint64_t da0 = mk_desc(sb + w * 8192, 16, 1024, 1);
      const uint64_t db0 = mk_desc(sb + 16384, 8192, 1024, 1);
      int st = 0; uint32_t ph = 0;
      auto issue = [&](int accum, auto between) {
        mbar_wait_c(B(B_FULL1 + st), ph);
        const uint64_t da = desc_add(da0, st * P1_STAGE), db = desc_add(db0, st * P1_STAGE);
        between();
        wg_fence();
#pragma unroll
        for (int k = 0; k < 4; k++) mma_n256_ss<1>(R, desc_add(da, k * 32), desc_add(db, k * 2048), k == 0 ? accum : 1);
        wg_commit();
      };
      issue(0, []() {});
#pragma unroll 1
      for (int t = 0;; t++) {
        const int nk = t >= 4 ? 16 : 8;
        const bool tr = t > 0 && t < 5;
        TL(0, 2 + 2 * t + 16 * w, (tid & 127) == 0);
        int prev = st;
        if (++st == 4) { st = 0; ph ^= 1; }
#pragma unroll 1
        for (int kb = 1; kb < nk; kb++) {
          if (kb == nk - 1 && w == 1) bar_sync(5, 256);
          issue(1, []() {});
          if (kb == nk - 1 && w == 0) bar_arrive(5, 256);
          if (tr) {
#pragma unroll
            for (int i = 1; i < 8; i++) if (kb == i) put2(i);
            if (kb == 7 && !(t & 1)) publish((t >> 1) - 1);
          } else if (t == 5) {
            if (kb == 2) {
              mbar_wait_c(B(B_LND), 0);
#pragma unroll
              for (int i = 0; i < 8; i++) park(6 * SLOT + w * 16384, i, make_uint4(pk[4 * i], pk[4 * i + 1], pk[4 * i + 2], pk[4 * i + 3]));
              __syncwarp();
            }
            if (kb == 4) {
#pragma unroll
              for (int k = 0; k < 8; k++) load_q(6 * SLOT + w * 16384, k);
              __syncwarp();
            }
            if (kb == 6) {
#pragma unroll
              for (int i = 0; i < 8; i++) park(6 * SLOT + w * 16384, i, make_uint4(pk[32 + 4 * i], pk[33 + 4 * i], pk[34 + 4 * i], pk[35 + 4 * i]));
            }
          }
          wg_wait<1>();
          release2(B_EMPTY1 + prev);
          prev = st;
          if (++st == 4) { st = 0; ph ^= 1; }
        }
        if (t == 5) break;
        issue(0, [&]() {
          sched_fence(q_st);
          wg_wait<0>();
          fence_regs<128>(R);
          TL(0, 3 + 2 * t + 16 * w, (tid & 127) == 0);
#pragma unroll
          for (int i = 0; i < 16; i++) { const uint4 v = packed(i); pk[4 * i] = v.x; pk[4 * i + 1] = v.y; pk[4 * i + 2] = v.z; pk[4 * i + 3] = v.w; }
          release2(B_EMPTY1 + prev);
          fence_regs<128>(R);
        });
        if (w == 1) bar_arrive(4, 256);
        sched_fence(q_st);
        pdst = g_qkv + (size_t)(((t & 1) + 1) * SEQ + mt * 128 + cw * 16 + (lane >> 2)) * NQ + (gq + (t >> 1) * 8) * 256 + (lane & 3) * 8;
        if (t < 4) put2(0);
        if (w == 0) bar_sync(4, 256);
      }
      if (w == 1) bar_arrive(6, 256);
      mbar_wait_c(B(B_KF), 0);
      sched_fence(q_st);
      wg_wait<0>();
      fence_regs<128>(R);
      release2(B_EMPTY1 + 3);
      TL(0, 13 + 16 * w, (tid & 127) == 0);
    }
    auto issue3 = [&](int st, uint32_t ph, int accum) {
      mbar_wait_c(B(B_FULL3 + st), ph);
      const uint64_t da = mk_desc(sb + OFF_R3 + w * 8192 + st * SLOT, 16, 1024, 1), db = mk_desc(sb + OFF_R3 + 16384 + st * SLOT, 8192, 1024, 1);
      wg_fence();
#pragma unroll
      for (int k = 0; k < 4; k++) mma_n128_ss<1>(acc, desc_add(da, k * 32), desc_add(db, k * 2048), k == 0 ? accum : 1);
      wg_commit();
    };
    uint32_t wf[128];
    auto w_addr = [&](uint32_t off, int m) {
      const uint32_t w_ld = sb + ((lane >> 3) & 1) * 8192 + ((cw >> 1) * 32 + (lane & 7) + (lane >> 4) * 8) * 64 + ((((cw & 1) * 2) ^ ((lane >> 1) & 3)) << 4);
      return ((w_ld + off) ^ ((m & 1) << 4)) + (m >> 2) * 16384 + ((m >> 1) & 1) * 1024;
    };
    auto grab = [&](uint32_t* d, uint32_t off, int m0, int m1) {
#pragma unroll
      for (int m = m0; m < m1; m++)
        asm volatile("ldmatrix.sync.aligned.m8n8.x4.trans.shared.b16 {%0,%1,%2,%3}, [%4];"
                     : "=r"(d[4 * m]), "=r"(d[4 * m + 1]), "=r"(d[4 * m + 2]), "=r"(d[4 * m + 3]) : "r"(w_addr(off, m)) : "memory");
    };
    float inv[2] = {0.f, 0.f};
    auto scaled = [&](int i) {
      const float* o = O + 16 * (i >> 1) + 2 * (i & 1);
      const float c = inv[i & 1];
      return make_uint4(pack_bf16(o[0] * c, o[1] * c), pack_bf16(o[4] * c, o[5] * c), pack_bf16(o[8] * c, o[9] * c), pack_bf16(o[12] * c, o[13] * c));
    };
    {
      const int wrow = cw * 16;
      const uint64_t dk0 = mk_desc(sb, 16, 1024, 1);
      const uint64_t dv0 = mk_desc(sb + 2 * SLOT, 16384, 1024, 1);
      const uint32_t pin = sb + OFF_MISC + 1028;
      float l0 = 0.f, l1 = 0.f;
      int g = 0, t = 0;
      uint32_t fail = 0;
      auto piece = [&](int tt) { return (uint32_t)(tt == 3 ? 6 * SLOT + w * 16384 : (3 + 2 * w) * SLOT + (tt - 1) * 16384); };
      uint32_t par = 0;
      auto issue_s = [&](float* S) {
        const uint64_t dk = desc_add(dk0, par * 16);
        mma_n128_rs0(S, Q, dk);
#pragma unroll
        for (int k = 1; k < 8; k++) mma_n128_rs<0>(S, Q + 4 * k, desc_add(dk, (k >> 2) * 16384 + (k & 3) * 32), 1);
        wg_commit();
      };
      auto issue_pv = [&](bool half, int accum) {
        const uint64_t dv = desc_add(dv0, ((g - 1) & 1) * 2 * SLOT);
        wg_fence();
#pragma unroll
        for (int k = 0; k < 4; k++) mma_n128_rs<1>(O, P + 4 * k, desc_add(dv, k * 2048), k == 0 ? accum : 1);
        wg_commit();
        if (UNLIKELY(half)) {
          wg_fence();
          wg_commit();
        } else {
          wg_fence();
#pragma unroll
          for (int k = 4; k < 8; k++) mma_n128_rs<1>(O, P + 4 * k, desc_add(dv, k * 2048), 1);
          wg_commit();
        }
        bar_arrive(2 - w, 256);
        wg_wait<2>();
        fence_regs<32>(Q);
      };
      auto release_k = [&]() { release2(B_KE); rbar ^= 8; };
      auto pv_done = [&]() {
        TC(g, 3);
        sched_fence(q_st);
        wg_wait<0>();
        fence_regs<64>(O); fence_regs<32>(P);
        TC(g, 4);
        release2(B_VE);
      };
      auto row_inv = [&](bool go) {
        float a = l0 + __shfl_xor_sync(~0u, l0, 1), b = l1 + __shfl_xor_sync(~0u, l1, 1);
        a += __shfl_xor_sync(~0u, a, 2); b += __shfl_xor_sync(~0u, b, 2);
        const bool ok = __all_sync(~0u, a >= AT_LO && a <= AT_HI && b >= AT_LO && b <= AT_HI) != 0;
        asm("rcp.approx.ftz.f32 %0, %1;" : "=f"(inv[0]) : "f"(a));
        asm("rcp.approx.ftz.f32 %0, %1;" : "=f"(inv[1]) : "f"(b));
        fail |= (uint32_t)(go && !ok) << t;
        l0 = go ? 0.f : l0; l1 = go ? 0.f : l1;
        t += go;
      };
      const uint64_t m_first = 1ull | (1ull << (16 - ti)) | (1ull << 17) | (1ull << (18 + ti));
      const uint64_t m_diag = (3ull << (15 - ti)) | (3ull << (17 + ti));
      enum { F_FIRST = 1, F_DIAG = 2, F_LAST = 4, F_PFIRST = 8, F_PHALF = 16, F_STOP = 32 };
      auto kind = [&](int gn) {
        const uint32_t a = (uint32_t)((m_first << 1) >> gn), d = (uint32_t)((m_diag << 1) >> gn);
        return ((a >> 1) & 1) * F_FIRST | ((d >> 1) & 1) * F_DIAG | ((a >> 2) & 1) * F_LAST | (a & 1) * F_PFIRST |
               (w == 0 ? (d & 1) * F_PHALF | ((d >> 1) & 1) * F_STOP : 0) | (gn == 34 ? F_STOP : 0);
      };
      uint32_t kinds;
      {
        uint32_t qt[64];
#pragma unroll
        for (int i = 0; i < 16; i++) { const uint4 v = packed(i); qt[4 * i] = v.x; qt[4 * i + 1] = v.y; qt[4 * i + 2] = v.z; qt[4 * i + 3] = v.w; }
        fence_regs<64>(qt);
        sched_fence(q_st);
        float S[64];
        wg_fence();
        issue_s(S);
        bar_arrive(w ? 1 : 7, 256);
        bar_sync(6 + w, 256);
        sched_fence(q_st);
        TL(1, 0, tid == 128);
#pragma unroll
        for (int i = 0; i < 16; i++) park(piece(1), i, make_uint4(qt[4 * i], qt[4 * i + 1], qt[4 * i + 2], qt[4 * i + 3]));
        kinds = pinned(kind(lane + 3));
        sched_fence(q_st);
        wg_wait<0>();
        fence_regs<64>(S);
        release_k();
        TL(1, 1, tid == 128);
        const bool kok = mbar_try(B(B_KF + 1), 0);
        at_exp<0, 32>(S);
        sched_fence(q_st);
        at_exp<32, 64>(S); at_fin<0, 64>(S, P);
        if (UNLIKELY(!kok)) mbar_wait_c(B(B_KF + 1), 0);
        TL(1, 2, tid == 128);
      }
      uint32_t f = F_PFIRST, fn;
      auto shadow = [&]() {
        const bool vok = mbar_try(B(B_VF + ((g - 1) & 1)), ((g - 1) >> 1) & 1);
        at_sum(P, f & F_PHALF, l0, l1);
        fn = __shfl_sync(~0u, kinds, max(g - 2, 0));
        if (UNLIKELY(!vok)) mbar_wait_c(B(B_VF + ((g - 1) & 1)), ((g - 1) >> 1) & 1);
      };
      auto hand_over = [&]() { __syncwarp(); if (lane == 0 && !((fail >> (t - 1)) & 1)) mbar_arrive(B(B_PUB + 1 + t)); };
      auto exp_q = [&](float* S, auto kc, auto nc) {
        constexpr int k = decltype(kc)::value, n = decltype(nc)::value;
        asm volatile("{\n.reg .pred p;\nsetp.ne.b32 p, %5, 0;\n@p ldmatrix.sync.aligned.m8n8.x4.shared.b16 {%0,%1,%2,%3}, [%4];\n}"
                     : "+r"(Q[4 * k]), "+r"(Q[4 * k + 1]), "+r"(Q[4 * k + 2]), "+r"(Q[4 * k + 3])
                     : "r"(((q_ld + piece(t + 1)) ^ ((k & 1) << 5)) + (k >> 1) * 4096), "r"(f & F_LAST) : "memory");
        at_exp<n * k, n * k + n>(S);
      };
      g = 1; par = SLOT / 16;
#pragma unroll 1
      for (;;) {
        {
          TC(g, 0);
          bar_sync(1 + w, 256);
          fence_regs<32>(Q);
          float S[64];
          wg_fence();
          issue_s(S);
          sched_fence(q_st);
          TC(g, 1);
          shadow();
          fence_regs<64>(O); fence_regs<32>(P);
          issue_pv(f & F_PHALF, ~f & F_PFIRST);
          fence_regs<64>(S);
          TC(g, 2);
          release_k();
          at_exp<0, 8>(S);
          const bool first = f & F_FIRST;
          if (UNLIKELY(f & (F_FIRST | F_LAST))) {
            row_inv(first);
            at_mask(S + 32, (f & F_DIAG) ? wrow - 64 : 64, lane);
            unroll8([&](auto kc) { exp_q(S + 8, kc, std::integral_constant<int, AT_R1 / 8 - 1>{}); });
          } else {
            at_exp<8, AT_R1>(S);
          }
          pv_done();
          g = pinned(g + 1); par = pinned(par ^ (SLOT / 16)); f = fn;
          const bool kok = mbar_try(B(B_KF + (g & 1)), g < 34 ? (g >> 1) & 1 : 0);
          if (UNLIKELY(first)) {
            unroll8([&](auto ic) {
              constexpr int i = decltype(ic)::value, n = (64 - AT_R1) / 8;
              at_exp<AT_R1 + n * i, AT_R1 + n * i + n>(S);
              park(piece(t), i, scaled(i));
            });
            at_fin<0, 64>(S, P);
            hand_over();
          } else {
            at_exp<AT_R1, 64>(S); at_fin<0, 64>(S, P);
          }
          TC(g - 1, 5);
          if (!TCLK) TL(1, 1 + g, tid == 128);
          if (kok && !(f & F_STOP)) continue;
          if (UNLIKELY(!kok)) mbar_wait_c(B(B_KF + (g & 1)), (g >> 1) & 1);
          if (g == 34) break;
        }
#pragma unroll 1
        while (f & F_STOP) {
          TC(g, 0);
          bar_sync(1, 256);
          fence_regs<64>(O); fence_regs<32>(Q); fence_regs<32>(P);
          float S[32];
          const uint64_t dk = desc_add(dk0, par * 16);
          wg_fence();
          mma_n64_rs0(S, Q, dk);
#pragma unroll
          for (int k = 1; k < 8; k++) mma_n64_rs(S, Q + 4 * k, desc_add(dk, (k >> 2) * 16384 + (k & 3) * 32), 1);
          wg_commit();
          TC(g, 1);
          mbar_wait_c(B(B_VF + ((g - 1) & 1)), ((g - 1) >> 1) & 1);
          issue_pv(f & F_PHALF, ~f & F_PFIRST);
          fence_regs<32>(S);
          TC(g, 2);
          release_k();
          const bool first = f & F_FIRST;
          at_sum(P, f & F_PHALF, l0, l1);
          fn = __shfl_sync(~0u, kinds, g - 2);
          row_inv(first);
          pv_done();
          sched_fence(q_st);
          at_mask(S, wrow, lane);
          unroll8([&](auto kc) { exp_q(S, kc, std::integral_constant<int, 4>{}); });
          g++; par ^= SLOT / 16; f = fn;
          at_fin<0, 32>(S, P);
          if (first) {
#pragma unroll
            for (int i = 0; i < 8; i++) park(piece(t), i, scaled(i));
            hand_over();
          }
          TC(g - 1, 5);
          if (!TCLK) TL(1, 1 + g, tid == 128);
          mbar_wait_c(B(B_KF + (g & 1)), (g >> 1) & 1);
        }
      }
      const bool wok = mbar_test(B(ffn ? B_WF : B_QP + 1), 0);
      grab(wf, 3 * SLOT, 0, 8);
      mbar_wait_c(B(B_VF + 1), 0);
      bar_sync(1 + w, 256);
      fence_regs<64>(O); fence_regs<32>(P);
      wg_fence();
#pragma unroll
      for (int k = 0; k < 8; k++) mma_n128_rs<1>(O, P + 4 * k, desc_add(dv0, 2 * SLOT + k * 2048), 1);
      wg_commit();
      if (w == 0) bar_arrive(2, 256);
      pin_order(__uint_as_float(wf[28] & wf[24]), pin);
      __syncwarp();
      if (wok) release2(B_WE);
      TL(3, 12 + 16 * w, (tid & 127) == 0);
      sched_fence(q_st);
      at_sum(P, false, l0, l1);
      row_inv(true);
      sched_fence(q_st);
      wg_wait<0>();
      fence_regs<64>(O); fence_regs<32>(P);
      release2(B_VE + 1);
      if (UNLIKELY(!wok || fail != 0)) {
#pragma unroll 1
        for (int tt = 0; tt < 4; tt++) {
          if (!((tt < 3 ? fail >> tt : fail != 0) & 1)) continue;
          slow_tile(O, P, l0, l1, wq, (((tt + 1) & 2) ? ti : 15 - ti) * 128 + wrow, hh + (tt & 2) * 8, lane, q_st);
          row_inv(false);
          if (tt < 3) {
#pragma unroll
            for (int i = 0; i < 8; i++) park(piece(tt + 1), i, scaled(i));
            publish(2 + tt);
          }
        }
        if (!wok) {
          mbar_wait_c(B(ffn ? B_WF : B_QP + 1), 0);
          grab(wf, 3 * SLOT, 0, 8);
          pin_order(__uint_as_float(wf[28] & wf[24]), pin);
          __syncwarp();
          release2(B_WE);
        }
      }
      TL(3, 13 + 16 * w, (tid & 127) == 0);
      issue3(0, 0, 0);
      TL(3, 14 + 16 * w, (tid & 127) == 0);
      TL(1, 36, tid == 128);
    }
    uint32_t hp[32];
    lane = lane_id();
    {
      int st = 1, prev = 0; uint32_t ph = 0;
      __nv_bfloat16* dst = g_qkv + (size_t)((15 - ti) * 128 + cw * 16 + (lane >> 2)) * NQ + (hh + 16) * 128 + (lane & 3) * 8;
      auto kblock = [&](auto between, int lim = 6) {
        issue3(st, ph, 1);
        between();
        wg_wait<1>();
        release2(B_EMPTY3 + prev);
        prev = st;
        if (++st == lim) { st = 0; ph ^= 1; }
      };
      uint4 ob[8];
      kblock([&]() { sched_fence(rbar); ob[0] = scaled(0); ob[1] = scaled(2); ob[2] = scaled(1); ob[3] = scaled(3); sched_fence(rbar); });
      kblock([&]() { sched_fence(rbar); ob[4] = scaled(4); ob[5] = scaled(6); ob[6] = scaled(5); ob[7] = scaled(7); sched_fence(rbar); grab(wf + 32, 5 * SLOT, 0, 8); });
#pragma unroll 1
      for (int kb = 3; kb < 11; kb++) {
        kblock([&]() {
          sched_fence(rbar);
#pragma unroll
          for (int i = 0; i < 8; i++)
            if (kb == 3 + i) *reinterpret_cast<uint4*>(dst + (i & 2) * 4 * NQ + (i & 1) * 32 + (i & 4) * 16) = ob[i];
          TL(3, 14 + kb + 16 * w, (tid & 127) == 0);
          if (kb == 8) TL(2, 2, tid == 128);
        }, kb == 4 ? 5 : 6);
        if (kb == 4) release2(B_EMPTY3 + 5);
      }
      publish(5);
      kblock([&]() { mbar_wait_c(B(ffn ? B_WF2 : B_QP + 2), 0); grab(wf + 32, 5 * SLOT, 8, 16); });
#pragma unroll 1
      for (int kb = 12; kb < G_KB; kb++) {
        kblock([&]() { if ((kb & 7) == 0) TL(2, 1 + (kb >> 3), tid == 128); });
        if (kb == X_KB && lane == 0) mbar_arrive(B(B_XE));
      }
      kblock([&]() {
        mbar_wait_c(B(B_XF), 0);
#pragma unroll
        for (int i = 0; i < 8; i++)
          ldsm4(hp + 4 * i, sb + 6 * SLOT + w * 16384 + ((cw & 3) * 16 + (lane & 15)) * 128 + (i >> 2) * 8192 + ((((i & 3) * 2 + (lane >> 4)) ^ (lane & 7)) << 4));
      });
#pragma unroll 1
      for (int kb = G_KB + 1; kb < 64; kb++) {
        kblock([&]() { if ((kb & 7) == 0) TL(2, 1 + (kb >> 3), tid == 128); });
        if (kb == G_KB + 2 && lane == 0) mbar_arrive(B(B_XE));
      }
    }
    lane = lane_id();
    const int r0 = lane >> 2, q4 = lane & 3, ct = cw * 32 + lane;
    uint32_t tb[16];
    mbar_wait_c(B(B_WR), 0);
#pragma unroll
    for (int i = 0; i < 4; i++) ldsm4(tb + 4 * i, sb + OFF_MISC + 512 + (lane & 1) * 256 + (lane >> 3) * 16 + i * 64);
    mbar_wait_c(B(B_SET2), 0);
    float4* const psd = reinterpret_cast<float4*>(xr + XR_PS + cw * 16 + r0);
    const uint4* const pss = g_xr + (mt * 8 + (ct & 1) * 4) * XR_SIZE + XR_PS + (ct >> 1);
    sched_fence(stg);
    wg_wait<0>();
    fence_regs<64>(acc);
    TL(2, 10, tid == 128);
    {
      float d[2][4] = {}, qa[2][4] = {}, qb[2][4] = {};
#pragma unroll
      for (int j = 0; j < 16; j++) {
        hp[2 * j] = hadd2_bf(hp[2 * j], pack_bf16(acc[4 * j], acc[4 * j + 1]));
        hp[2 * j + 1] = hadd2_bf(hp[2 * j + 1], pack_bf16(acc[4 * j + 2], acc[4 * j + 3]));
        if (j & 1) {
          mma16816(d[(j >> 1) & 1], hp[2 * j - 2], hp[2 * j - 1], hp[2 * j], hp[2 * j + 1], tb[j - 1], tb[j]);
          mma16816(qa[(j >> 1) & 1], hp[2 * j - 2], hp[2 * j - 1], hp[2 * j], hp[2 * j + 1], hp[2 * j - 2], hp[2 * j]);
          mma16816(qb[(j >> 1) & 1], hp[2 * j - 2], hp[2 * j - 1], hp[2 * j], hp[2 * j + 1], hp[2 * j - 1], hp[2 * j + 1]);
        }
      }
      if (q4 == (r0 >> 1)) {
        __stcg(psd, make_float4(d[0][0] + d[1][0], (r0 & 1) ? qa[0][1] + qa[1][1] : qa[0][0] + qa[1][0], d[0][1] + d[1][1], 0.f));
        __stcg(psd + 8, make_float4(d[0][2] + d[1][2], (r0 & 1) ? qb[0][3] + qb[1][3] : qb[0][2] + qb[1][2], d[0][3] + d[1][3], 0.f));
      }
    }
    TL(2, 11, tid == 128);
    mbar_wait_c(B(B_EMPTY3 + 1), 0);
    stage_store_128(stg, lane, hp);
    if (ffn) mbar_wait_c(B(B_WF2), 1);
    grab(wf + 96, 6 * SLOT, 0, 8);
    const float wsum = *reinterpret_cast<const float*>(sp + OFF_MISC + 1024);
    __syncwarp();
    {
      uint4 ps[4];
      poll_chunks(ps, pss, XR_SIZE);
      TL(2, 12, tid == 128);
      auto F = [](uint32_t u) { return __uint_as_float(u); };
      float s1 = (F(ps[0].x) + F(ps[1].x)) + (F(ps[2].x) + F(ps[3].x)), s2 = (F(ps[0].y) + F(ps[1].y)) + (F(ps[2].y) + F(ps[3].y));
      float s3 = (F(ps[0].z) + F(ps[1].z)) + (F(ps[2].z) + F(ps[3].z));
      __syncwarp();
      s1 += __shfl_xor_sync(~0u, s1, 1); s2 += __shfl_xor_sync(~0u, s2, 1); s3 += __shfl_xor_sync(~0u, s3, 1);
      const float mean = s1 * (1.f / DM);
      float mb, inv;
      ln_round(mean, fmaxf(fmaf(s2, 1.f / DM, -mean * mean), 0.f), mb, inv);
      const uint32_t u = pack_bf16(0.f, fmaf(s3 - mb * wsum, inv, 0.f));
      const uint32_t key = (u ^ ((((int)u >> 31) & 0x7FFF0000u) | 0x80000000u)) | (0x7FFFu - (mt * 128 + (ct >> 1)));
      const uint32_t nm2 = pack_bf16(-mb, -mb);
      const uint32_t c1 = __reduce_max_sync(~0u, key);
      const uint32_t c2 = __reduce_max_sync(~0u, key == c1 ? 0u : key);
      if (lane == 0) {
        __stcg(reinterpret_cast<uint2*>(psd) + (XR_KEY - XR_PS) * 2 - cw * 31, make_uint2(c1, c2));
        mbar_arrive(B(B_OUT));
      }
      TL(2, 13, tid == 128);
      const int row = (0x7FFF - (((lane >> 4) ? c2 : c1) & 0x7FFF)) & 15;
      const uint32_t rn = __shfl_sync(~0u, nm2, row * 2);
      const float ri = __shfl_sync(~0u, inv, row * 2);
      uint32_t v[4];
#pragma unroll
      for (int i = 0; i < 4; i++)
        asm volatile("ld.shared.u32 %0, [%1];" : "=r"(v[i]) : "r"(stg + ((lane >> 3) & 1) * 8192 + row * 128 + ((((lane & 4) + i) ^ (row & 7)) << 4) + q4 * 4) : "memory");
      __stcg(xr + XR_CAND + cw * 64 + 32 + lane, make_uint4(ln_apply(v[0], rn, ri), ln_apply(v[1], rn, ri), ln_apply(v[2], rn, ri), ln_apply(v[3], rn, ri)));
      __stcg(xr + XR_CAND + cw * 64 + lane, make_uint4(v[0], v[1], v[2], v[3]));
      sched_fence(stg);
      const uint32_t na = __shfl_sync(~0u, nm2, r0 * 2), nb = __shfl_sync(~0u, nm2, r0 * 2 + 16);
      const float ia = __shfl_sync(~0u, inv, r0 * 2), ib = __shfl_sync(~0u, inv, r0 * 2 + 16);
#pragma unroll
      for (int i = 0; i < 32; i++) hp[i] = hadd2_bf(hp[i], ln_apply(hp[i], (i & 1) ? nb : na, (i & 1) ? ib : ia));
      __syncwarp();
      stage_store_128(stg, lane, hp);
      asm volatile("fence.proxy.async.shared::cta;" ::: "memory");
      publish(B_OUT3 - B_PUB);
    }
    uint32_t wd[16][4];
    sched_fence(stg);
    if (ffn) mbar_wait_c(B(B_FULL3 + 5 * w), 1 - w);
    auto load_wd = [&](int h) {
#pragma unroll
      for (int i = h; i < 16; i += 2)
        asm volatile("ldmatrix.sync.aligned.m8n8.x4.trans.shared.b16 {%0,%1,%2,%3}, [%4];"
                     : "=r"(wd[i][0]), "=r"(wd[i][1]), "=r"(wd[i][2]), "=r"(wd[i][3])
                     : "r"(sb + OFF_R3 + 5 * w * SLOT + (2 * (cw & 3) + (i >> 3)) * 4096 + (h * 16 + (lane & 7) + (lane >> 4) * 8) * 128 +
                           (((2 * ((i >> 1) & 3) + ((lane >> 3) & 1)) ^ (lane & 7)) << 4)) : "memory");
    };
    load_wd(0);
    __syncwarp();
    cluster_arrive();
    const char* xsrc = reinterpret_cast<const char*>(g_xr + (r0 >> 1) * XR_SIZE + XR_CAND + 32 + (cw >> 1) * 4 + q4);
    asm volatile("" : "+l"(xsrc));
    sched_fence(stg);
    TL(2, 22, tid == 128);
    mbar_wait_c(B(B_OUT2), 0);
    TL(2, 14, tid == 128);
    if (ffn) {
      uint4 xb[2];
      poll_chunks(xb, reinterpret_cast<const uint4*>(xsrc + *reinterpret_cast<const uint32_t*>(sp + OFF_MISC + 8 + (r0 & 1) * 4)), 4 * XR_SIZE);
      __syncwarp();
      TL(2, 15, tid == 128);
      float d[8][4] = {};
#pragma unroll
      for (int n = 0; n < 32; n++) {
        if (n == 8) { sched_fence(stg); load_wd(1); }
        const int s = (n >> 4) * 4 + ((n >> 1) & 3), m = ((n >> 3) & 1) * 2 + (n & 1);
        const uint32_t* a = wf + 16 * s + 4 * m;
        mma16816(d[n & 7], a[0], a[1], a[2], a[3], (m & 2) ? xb[s >> 2].z : xb[s >> 2].x, (m & 2) ? xb[s >> 2].w : xb[s >> 2].y);
      }
      float v[8];
#pragma unroll
      for (int i = 0; i < 8; i++) {
        const float lo = (q4 & 1) ? d[2 + (i >> 2)][i & 3] : d[i >> 2][i & 3], hi = (q4 & 1) ? d[6 + (i >> 2)][i & 3] : d[4 + (i >> 2)][i & 3];
        v[i] = (q4 & 2) ? hi : lo;
      }
#pragma unroll
      for (int i = 0; i < 4; i++) v[i] = ((q4 & 2) ? v[i + 4] : v[i]) + __shfl_xor_sync(~0u, (q4 & 2) ? v[i] : v[i + 4], 2);
#pragma unroll
      for (int i = 0; i < 2; i++) v[i] = ((q4 & 1) ? v[i + 2] : v[i]) + __shfl_xor_sync(~0u, (q4 & 1) ? v[i] : v[i + 2], 1);
      float4* red = reinterpret_cast<float4*>(sp + SL_SCR * SLOT);
      reinterpret_cast<float2*>(red + cw * 16 + (q4 >> 1) * 8 + r0)[q4 & 1] = make_float2(v[0], v[1]);
      bar_sync(3, 256);
      TL(2, 16, tid == 128);
      const float4 z0 = red[lane], z1 = red[32 + lane], z2 = red[64 + lane], z3 = red[96 + lane];
      const uint32_t ub = pack_bf16((z0.x + z1.x) + (z2.x + z3.x), (z0.y + z1.y) + (z2.y + z3.y));
      const uint32_t gb = pack_bf16((z0.z + z1.z) + (z2.z + z3.z), (z0.w + z1.w) + (z2.w + z3.w));
      const float g0 = bf_lo(gb), g1 = bf_hi(gb);
      const uint32_t sg = pack_bf16(g0 * sigmoid(g0), g1 * sigmoid(g1));
      const uint32_t act = pack_bf16(bf_lo(sg) * bf_lo(ub), bf_hi(sg) * bf_hi(ub));
      const uint32_t pr = __byte_perm(act, __shfl_xor_sync(~0u, act, 1), (lane & 1) ? 0x3276 : 0x5410);
      const int src = q4 * 2 + (r0 & 1);
      const uint32_t a0 = __shfl_sync(~0u, pr, src), a1 = __shfl_sync(~0u, pr, src + 8), a2 = __shfl_sync(~0u, pr, src + 16), a3 = __shfl_sync(~0u, pr, src + 24);
      TL(2, 17, tid == 128);
      float y[8][4] = {};
#pragma unroll
      for (int i = 0; i < 8; i++) mma16816(y[i], wd[2 * i][0], wd[2 * i][1], wd[2 * i][2], wd[2 * i][3], a0, a1);
#pragma unroll
      for (int i = 0; i < 8; i++) mma16816(y[i], wd[2 * i + 1][0], wd[2 * i + 1][1], wd[2 * i + 1][2], wd[2 * i + 1][3], a2, a3);
      float2* yd = reinterpret_cast<float2*>(g_xr + (cw * 16 + 2 * q4) * XR_SIZE + XR_Y + fid * 4) + r0;
#pragma unroll
      for (int j = 0; j < 2; j++) {
        float v[4];
#pragma unroll
        for (int e = 0; e < 4; e++) {
          const float lo = (q4 & 1) ? y[4 * j + 1][e] : y[4 * j][e], hi = (q4 & 1) ? y[4 * j + 3][e] : y[4 * j + 2][e];
          v[e] = (q4 & 2) ? hi : lo;
        }
        __stcg(yd + j * 16 * XR_SIZE, make_float2(v[0], v[1]));
        __stcg(yd + j * 16 * XR_SIZE + 2 * XR_SIZE, make_float2(v[2], v[3]));
      }
    }
    TL(2, 18, tid == 128);
    cluster_wait();
    if (rid == 127 && ct < C_NUM) g_cnt[ct] = 0;
    if (cw < 2) {
      const int tok = (lane >> 1) & 1, pair = cw * 2 + (lane & 1);
      uint32_t* const dst = reinterpret_cast<uint32_t*>(out + (size_t)(~*reinterpret_cast<const uint32_t*>(sp + OFF_MISC + tok * 4) & 0x7FF) * DM) + rid * 4 + pair;
      idle(ffn ? Y_CLK : Y_CLK + 2000);
      const bool fin = mbar_test(B(B_FIN), 0);
      uint4 op = lds128(sb + OFF_MISC + 128 + (tok * 4 + pair) * 16);
      uint4 z[7];
      poll_chunks(z, xr + XR_Y + (lane >> 1) * 4 + pair, 64);
      __syncwarp();
      TL(2, 19, tid == 128);
      if (!fin) { mbar_wait_c(B(B_FIN), 0); op = lds128(sb + OFF_MISC + 128 + (tok * 4 + pair) * 16); }
      auto F = [](uint32_t u) { return __uint_as_float(u); };
      const float v0 = ((F(z[0].x) + F(z[1].x)) + (F(z[2].x) + F(z[3].x))) + ((F(z[4].x) + F(z[5].x)) + F(z[6].x));
      const float v1 = ((F(z[0].y) + F(z[1].y)) + (F(z[2].y) + F(z[3].y))) + ((F(z[4].y) + F(z[5].y)) + F(z[6].y));
      const float v2 = ((F(z[0].z) + F(z[1].z)) + (F(z[2].z) + F(z[3].z))) + ((F(z[4].z) + F(z[5].z)) + F(z[6].z));
      const float v3 = ((F(z[0].w) + F(z[1].w)) + (F(z[2].w) + F(z[3].w))) + ((F(z[4].w) + F(z[5].w)) + F(z[6].w));
      float ya = (tok ? v1 : v0) + __shfl_xor_sync(~0u, tok ? v0 : v1, 2), yb = (tok ? v3 : v2) + __shfl_xor_sync(~0u, tok ? v2 : v3, 2);
#pragma unroll
      for (int o = 4; o < 32; o <<= 1) { ya += __shfl_xor_sync(~0u, ya, o); yb += __shfl_xor_sync(~0u, yb, o); }
      const uint32_t yp = pack_bf16(ya, yb);
      if (lane < 4) *dst = hadd2_bf(op.x, hadd2_bf(op.y, pack_bf16(bf_lo(yp) * F(op.z), bf_hi(yp) * F(op.z))));
      TL(2, 21, tid == 128);
    }
    TL(2, 20, tid == 128);
    TL_DUMP();
  }
}

typedef CUresult (*EncodeFn)(CUtensorMap*, CUtensorMapDataType, cuuint32_t, void*, const cuuint64_t*, const cuuint64_t*, const cuuint32_t*,
                             const cuuint32_t*, CUtensorMapInterleave, CUtensorMapSwizzle, CUtensorMapL2promotion, CUtensorMapFloatOOBfill);
EncodeFn g_enc = nullptr;

void map2(CUtensorMap* m, const void* ptr, uint64_t rows, uint64_t cols, uint32_t bc, uint32_t br) {
  const CUtensorMapSwizzle sw = bc == 64 ? CU_TENSOR_MAP_SWIZZLE_128B : CU_TENSOR_MAP_SWIZZLE_64B;
  cuuint64_t gd[2] = {cols, rows}, gs[1] = {cols * 2};
  cuuint32_t bd[2] = {bc, br}, es[2] = {1, 1};
  g_enc(m, CU_TENSOR_MAP_DATA_TYPE_BFLOAT16, 2, (void*)ptr, gd, gs, bd, es, CU_TENSOR_MAP_INTERLEAVE_NONE, sw,
        CU_TENSOR_MAP_L2_PROMOTION_L2_128B, CU_TENSOR_MAP_FLOAT_OOB_FILL_NONE);
}
void map3(CUtensorMap* m, const void* ptr, uint64_t rows, uint64_t cols, uint32_t br, uint32_t bch, uint32_t bc = 64) {
  cuuint64_t gd[3] = {bc, rows, cols / bc}, gs[2] = {cols * 2, bc * 2};
  cuuint32_t bd[3] = {bc, br, bch}, es[3] = {1, 1, 1};
  g_enc(m, CU_TENSOR_MAP_DATA_TYPE_BFLOAT16, 3, (void*)ptr, gd, gs, bd, es, CU_TENSOR_MAP_INTERLEAVE_NONE, bc == 64 ? CU_TENSOR_MAP_SWIZZLE_128B : CU_TENSOR_MAP_SWIZZLE_64B,
        CU_TENSOR_MAP_L2_PROMOTION_L2_128B, CU_TENSOR_MAP_FLOAT_OOB_FILL_NONE);
}

}

extern "C" void kernel_launch(void* const* d_in, const int* in_sizes, int n_in, void* d_out, int out_size) {
  const __nv_bfloat16* x = (const __nv_bfloat16*)d_in[0];
  const __nv_bfloat16* ckv = (const __nv_bfloat16*)d_in[1];
  const __nv_bfloat16* wq = (const __nv_bfloat16*)d_in[2];
  const __nv_bfloat16* wk = (const __nv_bfloat16*)d_in[3];
  const __nv_bfloat16* wv = (const __nv_bfloat16*)d_in[4];
  const __nv_bfloat16* wo = (const __nv_bfloat16*)d_in[5];
  const __nv_bfloat16* w_r = (const __nv_bfloat16*)d_in[7];
  const __nv_bfloat16* wgate = (const __nv_bfloat16*)d_in[8];
  const __nv_bfloat16* wup = (const __nv_bfloat16*)d_in[9];
  const __nv_bfloat16* wdown = (const __nv_bfloat16*)d_in[10];
  __nv_bfloat16* out = (__nv_bfloat16*)d_out;

  if (!g_enc) {
    void* fn = nullptr;
    cudaDriverEntryPointQueryResult qr;
    cudaGetDriverEntryPoint("cuTensorMapEncodeTiled", &fn, cudaEnableDefault, &qr);
    g_enc = (EncodeFn)fn;
    cudaFuncSetAttribute(fused_kernel, cudaFuncAttributeMaxDynamicSharedMemorySize, SMEM_BYTES);
  }
  void *xn, *qkv;
  cudaGetSymbolAddress(&xn, g_xn);
  cudaGetSymbolAddress(&qkv, g_qkv);

  Params p;
  map2(&p.xn, xn, SEQ, DM, 64, 128);
  map2(&p.ckv, ckv, SEQ, DC, 64, 128);
  map3(&p.wq, wq, DM, NQ, 64, 2);
  map3(&p.wk, wk, DC, NQ, 64, 2);
  map3(&p.wv, wv, DC, NQ, 64, 2);
  map3(&p.kv, qkv, 3 * SEQ, NQ, 128, 1);
  map2(&p.ctx_ld, qkv, SEQ, NQ, 64, 128);
  map3(&p.ctx_st, qkv, SEQ, NQ, 64, 1, 32);
  map3(&p.wo, wo, NQ, DM, 64, 1);
  map3(&p.x, x, SEQ, DM, 64, 1);
  map3(&p.wd, wdown, FF, DM, 32, 8);
  map2(&p.out, out, SEQ, DM, 64, 64);
  map2(&p.wg, wgate, DM, FF, 32, 128);
  map2(&p.wu, wup, DM, FF, 32, 128);
  fused_kernel<<<128, 384, SMEM_BYTES, cudaStreamPerThread>>>(x, wq, w_r, out, p);
}
```

```cpp
#include <cuda_runtime.h>
#include <cuda_bf16.h>
#include <cuda.h>
#include <stdint.h>
#include <type_traits>

#pragma nv_diag_suppress 549
namespace {

constexpr int SEQ = 2048, DM = 1024, NH = 32, HD = 128, DC = 512, NQ = NH * HD, FF = 3584;

__device__ __align__(1024) __nv_bfloat16 g_xn[SEQ * DM];
__device__ __align__(1024) __nv_bfloat16 g_qkv[3 * SEQ * NQ];
constexpr int XR_PS = 0;
constexpr int XR_KEY = 128;
constexpr int XR_FLAG = 132;
constexpr int XR_CAND = 136;
constexpr int XR_Y = 648;
constexpr int XR_SIZE = 1104;
__device__ __align__(1024) uint4 g_xr[128 * XR_SIZE];
constexpr int C_LN = 0, C_QKV = 16, C_CTX = 32, C_NUM = 64;
__device__ unsigned g_cnt[C_NUM];

#define TL(k, i, cond) do {} while (0)
#define TL_BYTES 0
#define TL_INIT() do {} while (0)
#define TL_DUMP() do {} while (0)
#define TC(g, i) do {} while (0)
#define TS(i) do {} while (0)
#undef TCLK
#define TCLK 0

__device__ __forceinline__ uint32_t s2u(const void* p) { return (uint32_t)__cvta_generic_to_shared(p); }
__device__ __forceinline__ void mbar_init(uint32_t b, uint32_t c) { asm volatile("mbarrier.init.shared::cta.b64 [%0], %1;" ::"r"(b), "r"(c) : "memory"); }
__device__ __forceinline__ void mbar_expect(uint32_t b, uint32_t bytes) { asm volatile("mbarrier.arrive.expect_tx.shared::cta.b64 _, [%0], %1;" ::"r"(b), "r"(bytes) : "memory"); }
__device__ __forceinline__ void mbar_arrive(uint32_t b) { asm volatile("mbarrier.arrive.shared::cta.b64 _, [%0];" ::"r"(b) : "memory"); }
__device__ __forceinline__ bool mbar_test(uint32_t b, uint32_t ph) {
  uint32_t ok;
  asm volatile("{\n.reg .pred p;\nmbarrier.test_wait.parity.shared::cta.b64 p, [%1], %2;\nselp.u32 %0, 1, 0, p;\n}" : "=r"(ok) : "r"(b), "r"(ph) : "memory");
  return ok;
}
__device__ __forceinline__ void mbar_wait(uint32_t b, uint32_t ph) {
  asm volatile(
      "{\n.reg .pred p;\n.reg .u32 n;\nmov.u32 n, 0;\n"
      "LW:\nmbarrier.try_wait.parity.shared::cta.b64 p, [%0], %1, 20000;\n@p bra LD;\n"
      "add.u32 n, n, 1;\nsetp.lt.u32 p, n, 0x40000;\n@p bra LW;\ntrap;\nLD:\n}" ::"r"(b), "r"(ph) : "memory");
}
__device__ __forceinline__ void mbar_wait_c(uint32_t b, uint32_t ph) {
  asm volatile(
      "{\n.reg .pred p;\n.reg .u32 n;\nmov.u32 n, 0;\n"
      "LW:\nmbarrier.try_wait.parity.shared::cta.b64 p, [%0], %1;\n@p bra LD;\n"
      "add.u32 n, n, 1;\nsetp.lt.u32 p, n, 0x100000;\n@p bra LW;\ntrap;\nLD:\n}" ::"r"(b), "r"(ph) : "memory");
}
__device__ __forceinline__ bool mbar_try(uint32_t b, uint32_t ph) {
  uint32_t ok;
  asm volatile("{\n.reg .pred p;\nmbarrier.try_wait.parity.shared::cta.b64 p, [%1], %2;\nselp.u32 %0, 1, 0, p;\n}" : "=r"(ok) : "r"(b), "r"(ph) : "memory");
  return ok;
}
#define UNLIKELY(c) __builtin_expect(!!(c), 0)
__device__ __forceinline__ uint32_t pinned(uint32_t v) { uint32_t r; asm volatile("mov.b32 %0, %1;" : "=r"(r) : "r"(v)); return r; }
__device__ __forceinline__ bool elect_one() {
  uint32_t p;
  asm volatile("{\n.reg .pred p;\nelect.sync _|p, 0xFFFFFFFF;\nselp.u32 %0, 1, 0, p;\n}" : "=r"(p));
  return p;
}
__device__ __forceinline__ int lane_id() { int r; asm volatile("mov.u32 %0, %%laneid;" : "=r"(r)); return r; }
template <bool SLEEP = false>
__device__ __forceinline__ void spin_until_ge(const unsigned* p, unsigned target) {
  asm volatile(
      "{\n.reg .pred p, q;\n.reg .u32 n, v;\nmov.u32 n, 0;\nsetp.ne.u32 q, %2, 0;\n"
      "LW:\nld.acquire.gpu.global.u32 v, [%0];\nsetp.ge.u32 p, v, %1;\n@p bra LD;\n@q nanosleep.u32 200;\n"
      "add.u32 n, n, 1;\nsetp.lt.u32 p, n, 0x400000;\n@p bra LW;\ntrap;\nLD:\n}" ::"l"(p), "r"(target), "n"((int)SLEEP) : "memory");
}
template <int N>
__device__ __forceinline__ void poll_chunks(uint4 (&v)[N], const uint4* p, int stride) {
  uint32_t m[N];
#pragma unroll
  for (int i = 0; i < N; i++) { m[i] = ~0u; v[i] = make_uint4(0, 0, 0, 0); }
#pragma unroll 1
  for (int n = 0; n < 0x400000; n++) {
    uint32_t a = 0;
#pragma unroll
    for (int i = 0; i < N; i++)
      asm volatile("{\n.reg .pred p;\nsetp.eq.u32 p, %5, 0xFFFFFFFF;\n@p ld.relaxed.gpu.global.v4.u32 {%0,%1,%2,%3}, [%4];\n}"
                   : "+r"(v[i].x), "+r"(v[i].y), "+r"(v[i].z), "+r"(v[i].w) : "l"(p + i * stride), "r"(m[i]) : "memory");
#pragma unroll
    for (int i = 0; i < N; i++) { m[i] = max(max(v[i].x, v[i].y), max(v[i].z, v[i].w)); a = max(a, m[i]); }
    if (__all_sync(~0u, a != 0xFFFFFFFFu)) break;
  }
}
__device__ __forceinline__ void fence_async_all() { asm volatile("fence.proxy.async;" ::: "memory"); }
__device__ __forceinline__ void bar_sync(int id, int n) { asm volatile("bar.sync %0, %1;" ::"r"(id), "r"(n) : "memory"); }
__device__ __forceinline__ void bar_arrive(int id, int n) { asm volatile("bar.arrive %0, %1;" ::"r"(id), "r"(n) : "memory"); }
__device__ __forceinline__ void cluster_arrive() { asm volatile("barrier.cluster.arrive.relaxed.aligned;" ::: "memory"); }
__device__ __forceinline__ void cluster_wait() { asm volatile("barrier.cluster.wait.acquire.aligned;" ::: "memory"); }
__device__ __forceinline__ void fence_gpu() { asm volatile("fence.acq_rel.gpu;" ::: "memory"); }
__device__ __forceinline__ void red_add(unsigned* p, unsigned v) { asm volatile("red.relaxed.gpu.global.add.u32 [%0], %1;" ::"l"(p), "r"(v) : "memory"); }
__device__ __forceinline__ void prefetch_tm(const CUtensorMap* m) { asm volatile("prefetch.tensormap [%0];" ::"l"(m) : "memory"); }

constexpr uint64_t EV_N = 0x1000000000000000ull, EV_F = 0x12F0000000000000ull;
__device__ __forceinline__ void tma_ld2(uint32_t dst, const CUtensorMap* m, uint32_t bar, int c0, int c1, bool ef = false) {
  asm volatile("cp.async.bulk.tensor.2d.shared::cta.global.mbarrier::complete_tx::bytes.L2::cache_hint [%0], [%1, {%3,%4}], [%2], %5;" ::"r"(dst), "l"(m), "r"(bar), "r"(c0), "r"(c1), "l"(ef ? EV_F : EV_N) : "memory");
}
__device__ __forceinline__ void tma_ld3(uint32_t dst, const CUtensorMap* m, uint32_t bar, int c0, int c1, int c2, bool ef = false) {
  asm volatile("cp.async.bulk.tensor.3d.shared::cta.global.mbarrier::complete_tx::bytes.L2::cache_hint [%0], [%1, {%3,%4,%5}], [%2], %6;" ::"r"(dst), "l"(m), "r"(bar), "r"(c0), "r"(c1), "r"(c2), "l"(ef ? EV_F : EV_N) : "memory");
}
__device__ __forceinline__ void tma_ld3_mc(uint32_t dst, const CUtensorMap* m, uint32_t bar, int c0, int c1, int c2, uint16_t mask, bool ef = false) {
  asm volatile("cp.async.bulk.tensor.3d.shared::cluster.global.mbarrier::complete_tx::bytes.multicast::cluster.L2::cache_hint [%0], [%1, {%3,%4,%5}], [%2], %6, %7;" ::"r"(dst), "l"(m), "r"(bar), "r"(c0), "r"(c1), "r"(c2), "h"(mask), "l"(ef ? EV_F : EV_N) : "memory");
}
__device__ __forceinline__ void tma_pf3(const CUtensorMap* m, int c0, int c1, int c2) {
  asm volatile("cp.async.bulk.prefetch.tensor.3d.L2.global [%0, {%1,%2,%3}];" ::"l"(m), "r"(c0), "r"(c1), "r"(c2) : "memory");
}
__device__ __forceinline__ void l2_prefetch(const void* p, uint32_t bytes) { asm volatile("cp.async.bulk.prefetch.L2.global [%0], %1;" ::"l"(p), "r"(bytes) : "memory"); }

__device__ __forceinline__ void wg_fence() { asm volatile("wgmma.fence.sync.aligned;" ::: "memory"); }
__device__ __forceinline__ void wg_commit() { asm volatile("wgmma.commit_group.sync.aligned;" ::: "memory"); }
template <int N> __device__ __forceinline__ void wg_wait() { asm volatile("wgmma.wait_group.sync.aligned %0;" ::"n"(N) : "memory"); }
template <int N> __device__ __forceinline__ void reg_alloc() { asm volatile("setmaxnreg.inc.sync.aligned.u32 %0;" ::"n"(N)); }
template <int N> __device__ __forceinline__ void reg_dealloc() { asm volatile("setmaxnreg.dec.sync.aligned.u32 %0;" ::"n"(N)); }
template <int N> __device__ __forceinline__ void fence_regs(float* d) {
#pragma unroll
  for (int i = 0; i < N; i++) asm volatile("" : "+f"(d[i])::"memory");
}
template <int N> __device__ __forceinline__ void fence_regs(uint32_t* d) {
#pragma unroll
  for (int i = 0; i < N; i++) asm volatile("" : "+r"(d[i])::"memory");
}

__device__ __forceinline__ uint64_t mk_desc(uint32_t addr, uint32_t lbo, uint32_t sbo, uint32_t swz) {
  uint32_t lo = ((addr & 0x3FFFF) >> 4) | ((lbo >> 4) << 16);
  uint32_t hi = (sbo >> 4) | (swz << 30);
  return ((uint64_t)hi << 32) | lo;
}
__device__ __forceinline__ uint64_t desc_add(uint64_t d, uint32_t bytes) {
  uint32_t lo = (uint32_t)d + (bytes >> 4);
  return (d & 0xFFFFFFFF00000000ull) | lo;
}

#define R8(b) "+f"(d[b + 0]), "+f"(d[b + 1]), "+f"(d[b + 2]), "+f"(d[b + 3]), "+f"(d[b + 4]), "+f"(d[b + 5]), "+f"(d[b + 6]), "+f"(d[b + 7])
#define REGS32 "%0,%1,%2,%3,%4,%5,%6,%7,%8,%9,%10,%11,%12,%13,%14,%15,%16,%17,%18,%19,%20,%21,%22,%23,%24,%25,%26,%27,%28,%29,%30,%31"
#define REGS64 REGS32 ",%32,%33,%34,%35,%36,%37,%38,%39,%40,%41,%42,%43,%44,%45,%46,%47,%48,%49,%50,%51,%52,%53,%54,%55,%56,%57,%58,%59,%60,%61,%62,%63"
#define REGS128 REGS64 ",%64,%65,%66,%67,%68,%69,%70,%71,%72,%73,%74,%75,%76,%77,%78,%79,%80,%81,%82,%83,%84,%85,%86,%87,%88,%89,%90,%91,%92,%93,%94,%95," \
               "%96,%97,%98,%99,%100,%101,%102,%103,%104,%105,%106,%107,%108,%109,%110,%111,%112,%113,%114,%115,%116,%117,%118,%119,%120,%121,%122,%123,%124,%125,%126,%127"

template <int TB>
__device__ __forceinline__ void mma_n256_ss(float (&d)[128], uint64_t a, uint64_t b, int acc) {
  asm volatile("{\n.reg .pred p;\nsetp.ne.b32 p, %130, 0;\n"
               "wgmma.mma_async.sync.aligned.m64n256k16.f32.bf16.bf16 {" REGS128 "}, %128, %129, p, 1, 1, 0, %131;\n}\n"
               : R8(0), R8(8), R8(16), R8(24), R8(32), R8(40), R8(48), R8(56), R8(64), R8(72), R8(80), R8(88), R8(96), R8(104), R8(112), R8(120)
               : "l"(a), "l"(b), "r"(acc), "n"(TB));
}
template <int TB>
__device__ __forceinline__ void mma_n128_ss(float* d, uint64_t a, uint64_t b, int acc) {
  asm volatile("{\n.reg .pred p;\nsetp.ne.b32 p, %66, 0;\n"
               "wgmma.mma_async.sync.aligned.m64n128k16.f32.bf16.bf16 {" REGS64 "}, %64, %65, p, 1, 1, 0, %67;\n}\n"
               : R8(0), R8(8), R8(16), R8(24), R8(32), R8(40), R8(48), R8(56)
               : "l"(a), "l"(b), "r"(acc), "n"(TB));
}
template <int TB>
__device__ __forceinline__ void mma_n128_rs(float* d, const uint32_t* a, uint64_t b, int acc) {
  asm volatile("{\n.reg .pred p;\nsetp.ne.b32 p, %69, 0;\n"
               "wgmma.mma_async.sync.aligned.m64n128k16.f32.bf16.bf16 {" REGS64 "}, {%64,%65,%66,%67}, %68, p, 1, 1, %70;\n}\n"
               : R8(0), R8(8), R8(16), R8(24), R8(32), R8(40), R8(48), R8(56)
               : "r"(a[0]), "r"(a[1]), "r"(a[2]), "r"(a[3]), "l"(b), "r"(acc), "n"(TB));
}
__device__ __forceinline__ void mma_n64_rs(float* d, const uint32_t* a, uint64_t b, int acc) {
  asm volatile("{\n.reg .pred p;\nsetp.ne.b32 p, %37, 0;\n"
               "wgmma.mma_async.sync.aligned.m64n64k16.f32.bf16.bf16 {" REGS32 "}, {%32,%33,%34,%35}, %36, p, 1, 1, 0;\n}\n"
               : R8(0), R8(8), R8(16), R8(24)
               : "r"(a[0]), "r"(a[1]), "r"(a[2]), "r"(a[3]), "l"(b), "r"(acc));
}
#define W8(b) "=f"(d[b + 0]), "=f"(d[b + 1]), "=f"(d[b + 2]), "=f"(d[b + 3]), "=f"(d[b + 4]), "=f"(d[b + 5]), "=f"(d[b + 6]), "=f"(d[b + 7])
__device__ __forceinline__ void mma_n128_rs0(float* d, const uint32_t* a, uint64_t b) {
  asm volatile("wgmma.mma_async.sync.aligned.m64n128k16.f32.bf16.bf16 {" REGS64 "}, {%64,%65,%66,%67}, %68, 0, 1, 1, 0;\n"
               : W8(0), W8(8), W8(16), W8(24), W8(32), W8(40), W8(48), W8(56)
               : "r"(a[0]), "r"(a[1]), "r"(a[2]), "r"(a[3]), "l"(b));
}
__device__ __forceinline__ void mma_n64_rs0(float* d, const uint32_t* a, uint64_t b) {
  asm volatile("wgmma.mma_async.sync.aligned.m64n64k16.f32.bf16.bf16 {" REGS32 "}, {%32,%33,%34,%35}, %36, 0, 1, 1, 0;\n"
               : W8(0), W8(8), W8(16), W8(24)
               : "r"(a[0]), "r"(a[1]), "r"(a[2]), "r"(a[3]), "l"(b));
}
__device__ __forceinline__ uint32_t pack_bf16(float lo, float hi) {
  uint32_t r;
  asm("cvt.rn.bf16x2.f32 %0, %1, %2;" : "=r"(r) : "f"(hi), "f"(lo));
  return r;
}
__device__ __forceinline__ float bf_lo(uint32_t v) { return __uint_as_float(v << 16); }
__device__ __forceinline__ float bf_hi(uint32_t v) { return __uint_as_float(v & 0xFFFF0000u); }
__device__ __forceinline__ float bf_round(float v) { return bf_lo(pack_bf16(v, v)); }
__device__ __forceinline__ void stsm4(uint32_t addr, uint32_t r0, uint32_t r1, uint32_t r2, uint32_t r3) {
  asm volatile("stmatrix.sync.aligned.m8n8.x4.shared.b16 [%0], {%1,%2,%3,%4};" ::"r"(addr), "r"(r0), "r"(r1), "r"(r2), "r"(r3) : "memory");
}
__device__ __forceinline__ uint4 lds128(uint32_t addr) {
  uint4 v;
  asm volatile("ld.shared.v4.u32 {%0,%1,%2,%3}, [%4];" : "=r"(v.x), "=r"(v.y), "=r"(v.z), "=r"(v.w) : "r"(addr));
  return v;
}
__device__ __forceinline__ float ex2(float x) {
  float y;
  asm("ex2.approx.ftz.f32 %0, %1;" : "=f"(y) : "f"(x));
  return y;
}
__device__ __forceinline__ void pin_order(float v, uint32_t dummy) {
  asm volatile("{\n.reg .pred p;\nsetp.eq.b32 p, %0, 0xFFFFFFFF;\n@p st.shared.b32 [%1], %0;\n}" ::"r"(__float_as_uint(v)), "r"(dummy) : "memory");
}
__device__ __forceinline__ float sigmoid(float x) {
  float y;
  asm("rcp.approx.ftz.f32 %0, %1;" : "=f"(y) : "f"(1.f + ex2(x * -1.4426950408889634f)));
  return y;
}
__device__ __forceinline__ void sched_fence(uint32_t dummy) {
  asm volatile("{\n.reg .pred p;\n.reg .u32 c;\nsetp.eq.b32 p, %0, 0xFFFFFFFF;\nmov.u32 c, %%clock;\n@p st.shared.b32 [%0], c;\n}" ::"r"(dummy) : "memory");
}
__device__ __forceinline__ void idle(int n) {
  asm volatile("{\n.reg .pred p;\n.reg .u32 a, b;\nmov.u32 a, %%clock;\nLI:\nmov.u32 b, %%clock;\nsub.u32 b, b, a;\nsetp.lt.u32 p, b, %0;\n@p bra LI;\n}" ::"r"(n) : "memory");
}
__device__ __forceinline__ void stage_store_128(uint32_t base, int lane, const uint32_t* pk) {
  const int row = (lane & 7) + ((lane >> 3) & 1) * 8;
  const uint32_t rb = base + row * 128;
  const int hi = lane >> 4;
#pragma unroll
  for (int j = 0; j < 8; j++) {
    const int chunk = 2 * j + hi;
    const uint32_t a = rb + (j >> 2) * 8192 + (((chunk & 7) ^ (lane & 7)) << 4);
    stsm4(a, pk[4 * j + 0], pk[4 * j + 1], pk[4 * j + 2], pk[4 * j + 3]);
  }
}
__device__ __forceinline__ void ln_round(float mean, float var, float& m_bf, float& inv_s) {
  const uint32_t mv = pack_bf16(mean, var);
  m_bf = bf_lo(mv);
  float sq, rc;
  asm("sqrt.approx.ftz.f32 %0, %1;" : "=f"(sq) : "f"(bf_round(bf_hi(mv) + 1e-5f)));
  asm("rcp.approx.ftz.f32 %0, %1;" : "=f"(rc) : "f"(bf_round(sq)));
  inv_s = rc;
}
__device__ __forceinline__ uint32_t hadd2_bf(uint32_t a, uint32_t b) {
  uint32_t r;
  asm("add.rn.bf16x2 %0, %1, %2;" : "=r"(r) : "r"(a), "r"(b));
  return r;
}
__device__ __forceinline__ uint32_t ln_apply(uint32_t h, uint32_t nm2, float inv_s) {
  const uint32_t d = hadd2_bf(h, nm2);
  return pack_bf16(bf_lo(d) * inv_s, bf_hi(d) * inv_s);
}
__device__ __forceinline__ void ldsm4(uint32_t* r, uint32_t addr) {
  asm volatile("ldmatrix.sync.aligned.m8n8.x4.shared.b16 {%0,%1,%2,%3}, [%4];" : "=r"(r[0]), "=r"(r[1]), "=r"(r[2]), "=r"(r[3]) : "r"(addr) : "memory");
}
__device__ __forceinline__ void mma16816(float* d, uint32_t a0, uint32_t a1, uint32_t a2, uint32_t a3, uint32_t b0, uint32_t b1) {
  asm volatile("mma.sync.aligned.m16n8k16.row.col.f32.bf16.bf16.f32 {%0,%1,%2,%3}, {%4,%5,%6,%7}, {%8,%9}, {%0,%1,%2,%3};"
               : "+f"(d[0]), "+f"(d[1]), "+f"(d[2]), "+f"(d[3]) : "r"(a0), "r"(a1), "r"(a2), "r"(a3), "r"(b0), "r"(b1));
}

template <class F>
__device__ __forceinline__ void unroll8(F f) {
  f(std::integral_constant<int, 0>{}); f(std::integral_constant<int, 1>{}); f(std::integral_constant<int, 2>{}); f(std::integral_constant<int, 3>{});
  f(std::integral_constant<int, 4>{}); f(std::integral_constant<int, 5>{}); f(std::integral_constant<int, 6>{}); f(std::integral_constant<int, 7>{});
}

constexpr float AT_C = 0.08838834764831845f * 1.4426950408889634f;
constexpr float AT_LO = 0x1p-40f, AT_HI = 0x1p40f;
constexpr int AT_R1 = 48;
template <int I0, int I1>
__device__ __forceinline__ void at_exp(float* S) {
#pragma unroll
  for (int i = I0; i < I1; i++) asm volatile("ex2.approx.ftz.f32 %0, %0;" : "+f"(S[i]));
}
template <int I0, int I1>
__device__ __forceinline__ void at_fin(const float* S, uint32_t* P) {
#pragma unroll
  for (int i = I0; i < I1; i += 4) {
    P[i / 2] = pack_bf16(S[i], S[i + 1]); P[i / 2 + 1] = pack_bf16(S[i + 2], S[i + 3]);
  }
}
__device__ __forceinline__ void at_sum(const uint32_t* P, bool half, float& l0, float& l1) {
  uint32_t u[4];
#pragma unroll
  for (int r = 0; r < 4; r++) {
    const uint32_t* q = P + (r >> 1) * 16 + (r & 1);
    u[r] = hadd2_bf(hadd2_bf(hadd2_bf(q[0], q[2]), hadd2_bf(q[4], q[6])), hadd2_bf(hadd2_bf(q[8], q[10]), hadd2_bf(q[12], q[14])));
  }
  u[0] = hadd2_bf(u[0], half ? 0u : u[2]);
  u[1] = hadd2_bf(u[1], half ? 0u : u[3]);
  l0 += bf_lo(u[0]) + bf_hi(u[0]);
  l1 += bf_lo(u[1]) + bf_hi(u[1]);
}
template <int j>
__device__ __forceinline__ void at_mask1(float* S, int d) {
  float dummy0 = 0.f, dummy1 = 0.f;
  float& lo0 = j < 7 ? S[4 * (j < 7 ? j + 1 : j) + 2] : dummy0;
  float& lo1 = j < 7 ? S[4 * (j < 7 ? j + 1 : j) + 3] : dummy1;
  asm("{\n.reg .pred p, q;\nsetp.lt.s32 p, %4, %5;\nsetp.le.s32 q, %4, %5;\n"
      "@p add.f32 %0, %0, 0fFF800000;\n@q add.f32 %1, %1, 0fFF800000;\n@p add.f32 %2, %2, 0fFF800000;\n@q add.f32 %3, %3, 0fFF800000;\n}"
      : "+f"(S[4 * j]), "+f"(S[4 * j + 1]), "+f"(lo0), "+f"(lo1) : "r"(d), "r"(8 * j));
}
__device__ __forceinline__ void at_mask(float* S, int r, int lane) {
  unroll8([&](auto jc) { at_mask1<decltype(jc)::value>(S, r + (lane >> 2) - (lane & 3) * 2); });
}
__device__ __forceinline__ uint32_t ldg32(const __nv_bfloat16* p) { return __ldcg(reinterpret_cast<const uint32_t*>(p)); }
__device__ __forceinline__ uint32_t ldg16x2(const __nv_bfloat16* p, int stride) {
  return (uint32_t)__ldcg(reinterpret_cast<const unsigned short*>(p)) | ((uint32_t)__ldcg(reinterpret_cast<const unsigned short*>(p + stride)) << 16);
}
__device__ __forceinline__ void slow_tile(float* O, uint32_t* Q, float& l0, float& l1, const __nv_bfloat16* wq, int row0, int head, int lane, uint32_t dummy) {
  const int r = lane >> 2, q = lane & 3;
#pragma unroll
  for (int i = 0; i < 64; i++) O[i] = 0.f;
  {
    const __nv_bfloat16* xa = g_xn + (size_t)(row0 + r) * DM + 2 * q;
    const __nv_bfloat16* wb = wq + (size_t)(2 * q) * NQ + head * HD + (r >> 1) * 8 + (r & 1);
#pragma unroll 1
    for (int k = 0; k < DM; k += 16) {
      const uint32_t a0 = ldg32(xa + k), a1 = ldg32(xa + k + 8 * DM), a2 = ldg32(xa + k + 8), a3 = ldg32(xa + k + 8 * DM + 8);
#pragma unroll
      for (int j = 0; j < 16; j++) {
        const __nv_bfloat16* wp = wb + (size_t)k * NQ + (j >> 2) * 32 + (j & 3) * 2;
        mma16816(O + 4 * j, a0, a1, a2, a3, ldg16x2(wp, NQ), ldg16x2(wp + 8 * NQ, NQ));
        if (j == 7) sched_fence(dummy);
      }
    }
  }
#pragma unroll
  for (int i = 0; i < 32; i++) Q[i] = pack_bf16(O[2 * i], O[2 * i + 1]);
#pragma unroll
  for (int i = 0; i < 64; i++) O[i] = 0.f;
  float m0 = -INFINITY, m1 = -INFINITY;
  l0 = l1 = 0.f;
#pragma unroll 1
  for (int kv = 0; kv <= row0; kv += 16) {
    float s[8] = {0.f, 0.f, 0.f, 0.f, 0.f, 0.f, 0.f, 0.f};
    const __nv_bfloat16* kp = g_qkv + (size_t)(SEQ + kv + r) * NQ + head * HD + 2 * q;
#pragma unroll
    for (int k = 0; k < 8; k++) {
      mma16816(s, Q[4 * k], Q[4 * k + 1], Q[4 * k + 2], Q[4 * k + 3], ldg32(kp + 16 * k), ldg32(kp + 16 * k + 8));
      mma16816(s + 4, Q[4 * k], Q[4 * k + 1], Q[4 * k + 2], Q[4 * k + 3], ldg32(kp + 8 * NQ + 16 * k), ldg32(kp + 8 * NQ + 16 * k + 8));
    }
#pragma unroll
    for (int i = 0; i < 8; i++)
      if (kv + (i >> 2) * 8 + 2 * q + (i & 1) > row0 + r + (i & 2) * 4) s[i] = -INFINITY;
    float a = fmaxf(fmaxf(fmaxf(s[0], s[1]), fmaxf(s[4], s[5])), m0), b = fmaxf(fmaxf(fmaxf(s[2], s[3]), fmaxf(s[6], s[7])), m1);
    a = fmaxf(a, __shfl_xor_sync(~0u, a, 1)); b = fmaxf(b, __shfl_xor_sync(~0u, b, 1));
    a = fmaxf(a, __shfl_xor_sync(~0u, a, 2)); b = fmaxf(b, __shfl_xor_sync(~0u, b, 2));
    const float c0 = ex2(m0 - a), c1 = ex2(m1 - b);
    m0 = a; m1 = b;
#pragma unroll
    for (int i = 0; i < 8; i++) s[i] = ex2(s[i] - ((i & 2) ? b : a));
    l0 = l0 * c0 + (s[0] + s[1]) + (s[4] + s[5]);
    l1 = l1 * c1 + (s[2] + s[3]) + (s[6] + s[7]);
    sched_fence(dummy);
    const uint32_t p0 = pack_bf16(s[0], s[1]), p1 = pack_bf16(s[2], s[3]), p2 = pack_bf16(s[4], s[5]), p3 = pack_bf16(s[6], s[7]);
    const __nv_bfloat16* vp = g_qkv + (size_t)(2 * SEQ + kv + 2 * q) * NQ + head * HD + r;
#pragma unroll
    for (int j = 0; j < 16; j++) {
      O[4 * j] *= c0; O[4 * j + 1] *= c0; O[4 * j + 2] *= c1; O[4 * j + 3] *= c1;
      mma16816(O + 4 * j, p0, p1, p2, p3, ldg16x2(vp + 8 * j, NQ), ldg16x2(vp + 8 * NQ + 8 * j, NQ));
      if (j == 7) sched_fence(dummy);
    }
  }
}

constexpr int P1_STAGE = 49152;
constexpr int SLOT = 32768;
constexpr int OFF_R3 = 0;
constexpr int OFF_BAR = 229376;
constexpr int OFF_MISC = OFF_BAR + 8 * 58;
constexpr int SMEM_BYTES = OFF_MISC + 2080 + TL_BYTES;
enum : int {
  B_FULL1 = 0, B_KF = 4, B_VF = 6, B_FULL3 = 8, B_XF = 14, B_LN = 15, B_DEP = 16, B_OUT2 = 22, B_FIN = 23, B_SET2 = 25, B_QP = 26, B_WF2 = 29,
  B_WF = 30, B_WR = 31,
  B_XE = 33, B_PUB = 34, B_OUT = 40, B_OUT3 = 41,
  B_EMPTY1 = 42, B_KE = 46, B_VE = 48, B_EMPTY3 = 50, B_WE = 56, B_NUM = 57
};
constexpr int OFF_STG = SLOT, SL_SCR = 2;
constexpr int PRE = 3;
constexpr int LN_PF = 5, LN_PFN = 2, LN_LD = 4;
constexpr int WQ_0 = 18, WQ_D = 2;
constexpr int W_G0 = 22;
constexpr int X_KB = 20, G_KB = 35;
constexpr int SL_NS = 600, SET_NS = 50;
constexpr int OUT_CLK = 500, Y_CLK = 400;
struct Params {
  CUtensorMap xn, ckv, wq, wk, wv, kv, ctx_ld, ctx_st, wo, x, wd, wg, wu, out;
};

__global__ void __cluster_dims__(2, 1, 1) __launch_bounds__(384, 1)
fused_kernel(const __nv_bfloat16* __restrict__ x, const __nv_bfloat16* __restrict__ wq, const __nv_bfloat16* __restrict__ w_r,
             __nv_bfloat16* __restrict__ out, const __grid_constant__ Params p) {
  extern __shared__ __align__(1024) uint8_t sp[];
  const uint32_t sb = s2u(sp);
  const uint32_t bar = sb + OFF_BAR;
  auto B = [&](int i) { return bar + 8 * i; };
  const int tid = threadIdx.x, warp = __shfl_sync(~0u, tid >> 5, 0), wg = warp >> 2, lane = tid & 31;
  const int cta = blockIdx.x, rank = cta & 1, cl = cta >> 1;
  const int mp = cl < 4 ? 1 : (cl < 36 ? (cl & 7) : (0x3207654 >> (4 * ((cl - 36) % 7))) & 7);
  const int gq = cl < 4 ? 4 + cl : (cl < 36 ? (cl - 4) >> 3 : 4 + (cl - 36) / 7);
  const int mt = 2 * mp + rank;
  const int ti = (gq & 3) * 2 + rank, hh = mp * 2 + (gq >> 2);
  const int rid = mt * 8 + gq;
  const int fid = mt * 7 + gq - 1;
  const bool ffn = gq > 0;
  uint4* const xr = g_xr + rid * XR_SIZE;
  TL_INIT();
  TL(0, 0, tid == 128);
  if (warp == 0) {
    if (elect_one()) {
#pragma unroll
      for (int kb = 0; kb < PRE; kb++) mbar_init(B(B_FULL1 + kb), 1);
      asm volatile("fence.mbarrier_init.release.cluster;" ::: "memory");
    }
    __syncwarp();
    cluster_arrive();
    if (elect_one()) {
#pragma unroll
      for (int kb = 0; kb < PRE; kb++) {
        mbar_expect(B(B_FULL1 + kb), P1_STAGE);
        tma_ld2(sb + kb * P1_STAGE, &p.ckv, B(B_FULL1 + kb), kb * 64, mt * 128);
        tma_ld3(sb + kb * P1_STAGE + 16384 + rank * 16384, &p.wk, B(B_FULL1 + kb), 0, kb * 64, gq * 4 + rank * 2);
        tma_ld3(sb + kb * P1_STAGE + 32768 - rank * 16384, &p.wk, B(B_FULL1 + kb), 0, kb * 64, gq * 4 + 2 - rank * 2);
      }
    }
  } else if (elect_one()) {
#pragma unroll 1
    for (int i = PRE + warp - 1; i < B_NUM; i += 11)
      mbar_init(B(i), i >= B_EMPTY1 ? 16 : (i >= B_XE ? 8 : (i >= B_WF ? 2 : 1)));
    asm volatile("fence.mbarrier_init.release.cluster;" ::: "memory");
  }
  __syncwarp();
  if (warp) cluster_arrive();
  if (wg == 0) {
    reg_dealloc<40>();
    if (warp == 1 && elect_one()) {
      if (mt >= 2 * PRE) tma_pf3(&p.wk, 0, mp * 64, gq * 4 + rank * 2);
      if (gq >= PRE) asm volatile("cp.async.bulk.prefetch.tensor.2d.L2.global [%0, {%1,%2}];" ::"l"(&p.ckv), "r"(gq * 64), "r"(mt * 128) : "memory");
    } else if (warp == 2 && elect_one()) {
      prefetch_tm(&p.wv); prefetch_tm(&p.wq); prefetch_tm(&p.xn);
    }
    __syncwarp();
    cluster_wait();
    if (warp == 0) {
      int st = PRE; uint32_t ph = 1;
#pragma unroll 1
      for (int t = 0; t < 6; t++) {
        const CUtensorMap* ma = t >= 4 ? &p.xn : &p.ckv;
        const CUtensorMap* mb = t >= 4 ? &p.wq : ((t & 1) ? &p.wv : &p.wk);
        const int nk = t >= 4 ? 16 : 8;
        const int row = (t < 4 ? mt : (t == 4 ? 15 - ti : ti)) * 128;
        const int col = t < 4 ? (gq + (t >> 1) * 8) * 4 + rank * 2 : (hh + rank * 16) * 2;
        if (t >= 4) mbar_wait(B(B_DEP + t - 4), 0);
#pragma unroll 1
        for (int kb = t ? 0 : PRE; kb < nk; kb++) {
          const uint32_t d = sb + st * P1_STAGE, fb = B(B_FULL1 + st);
          const int n = t * 8 + kb;
          mbar_wait_c(B(B_EMPTY1 + st), ph);
          if (elect_one()) {
            const bool la = t == 0 || t >= 4 || (kb & 1);
            mbar_expect(fb, la ? P1_STAGE : 32768);
            if (la) tma_ld2(t == 0 && (kb & 5) == 4 ? sb + 6 * SLOT + (kb & 2) * 8192 : d, ma, fb, kb * 64, row);
            tma_ld3_mc(d + 16384 + rank * 16384, mb, fb, 0, kb * 64, col, 3);
          }
          if (t < 5 && elect_one()) {
            if (n >= LN_PF && n < LN_PF + LN_PFN) l2_prefetch(x + (size_t)cta * 16 * DM + (n - LN_PF) * (16 * DM / LN_PFN), 32768 / LN_PFN);
            if (n == LN_LD) mbar_arrive(B(B_LN));
            if (t < 3 && kb == (t ? 0 : 4)) tma_pf3((t & 1) ? &p.wk : &p.wv, 0, mp * 64, (gq + ((t + 1) >> 1) * 8) * 4 + rank * 2);
            if (n >= WQ_0 && n < WQ_0 + 4 * WQ_D && (n - WQ_0) % WQ_D == 0) tma_pf3(&p.wq, 0, ((n - WQ_0) / WQ_D * 4 + (gq & 3)) * 64, (hh + rank * 16) * 2);
          }
          if (++st == 4) { st = 0; ph ^= 1; }
        }
      }
      if (elect_one()) { prefetch_tm(&p.kv); prefetch_tm(&p.ctx_ld); prefetch_tm(&p.wo); prefetch_tm(&p.wg); prefetch_tm(&p.wu); }
      auto load_kv = [&](int g, int isv) {
        const int h2 = g >= 17, sx = g - 17 * h2, n1 = h2 ? ti + 1 : 16 - ti;
        const int row = (1 + isv) * SEQ + (sx < n1 ? sx : 16 - sx) * 128, col = (hh + 16 * h2) * 2;
        const uint32_t d = sb + (isv ? 2 + 2 * (g & 1) : (g & 1)) * SLOT, fb = B(B_KF + 2 * isv + (g & 1));
        const bool ef = sx >= n1 || sx >= 8;
        const bool shared = sx != (h2 ? (ti & 6) + 1 : 15 - (ti & 6));
        const int h3 = g >= 16, s3 = g + 1 - 17 * h3;
        const int pb = ti < 2 ? (h3 ? (s3 >= 1 && s3 <= 8 ? 16 - s3 : -1) : (s3 < 16 ? s3 : -1)) : (ti >= 6 && h3 && s3 < 8 ? s3 : -1);
        mbar_wait_c(g < 2 ? B(B_EMPTY1 + (isv ? 1 + 2 * g : g)) : B(B_KE + 2 * isv + (g & 1)), g < 2 ? 1 : ((g >> 1) & 1) ^ 1);
        if (elect_one()) {
          mbar_expect(fb, SLOT);
          if (shared) {
            tma_ld3_mc(d + rank * 16384, &p.kv, fb, 0, row, col + rank, 3, ef);
          } else {
            tma_ld3(d, &p.kv, fb, 0, row, col, ef);
            tma_ld3(d + 16384, &p.kv, fb, 0, row, col + 1, ef);
          }
          if (pb >= 0) tma_pf3(&p.kv, 0, (1 + isv) * SEQ + pb * 128, (hh + 16 * h3) * 2 + rank);
        }
      };
      int nw = ffn ? 0 : 12;
      auto load_w = [&]() {
        const int c = nw < 8 ? (nw >> 2) + (nw & 2) : nw >> 1;
        if (elect_one()) {
          if (!(nw & 3)) mbar_expect(B(B_WF - (nw >> 3)), 32768);
          tma_ld2(sb + (c < 2 ? 3 : 4) * SLOT + c * 16384 + (nw & 1) * 8192, (nw & 1) ? &p.wg : &p.wu, B(B_WF - (nw >> 3)), fid * 32, c * 128, true);
        }
        nw++;
      };
#pragma unroll 1
      for (int g = 0; g < 34; g++) {
        if (g == 0 || g == 16) mbar_wait(B(B_DEP + 2 + (g > 0)), 0);
        load_kv(g, 0);
        if (g > 0) load_kv(g - 1, 1);
        if (g >= W_G0 && nw < 12 && __any_sync(~0u, mbar_test(B(B_QP + (nw >> 2)), 0))) load_w();
      }
      load_kv(33, 1);
#pragma unroll 1
      while (nw < 12) { mbar_wait(B(B_QP + (nw >> 2)), 0); load_w(); }
      if (elect_one()) { prefetch_tm(&p.wd); prefetch_tm(&p.x); prefetch_tm(&p.out); }
      auto load3 = [&](int kb, int sl) {
        if (elect_one()) {
          mbar_expect(B(B_FULL3 + sl), SLOT);
          tma_ld2(sb + OFF_R3 + sl * SLOT, &p.ctx_ld, B(B_FULL3 + sl), kb * 64, mt * 128);
          tma_ld3_mc(sb + OFF_R3 + sl * SLOT + 16384 + rank * 8192, &p.wo, B(B_FULL3 + sl), 0, kb * 64, gq * 2 + rank, 3);
        }
      };
      mbar_wait(B(B_DEP + 4), 0);
#pragma unroll
      for (int kb = 0; kb < 5; kb++) {
        mbar_wait_c(B(kb == 3 ? B_WE : (kb == 4 ? B_VE + 1 : B_KE + kb)), 0);
        load3(kb, kb);
      }
      if (elect_one()) mbar_arrive(B(B_FULL3 + 5));
#pragma unroll 1
      for (int r = 1; r < 11; r++) {
#pragma unroll
        for (int j = 0; j < 6; j++) {
          if (j == 5 && r == 10) break;
          if (j == 3 && r == 5) mbar_wait(B(B_DEP + 5), 0);
          mbar_wait_c(B(B_EMPTY3 + j), ~r & 1);
          load3(r * 6 + j - 1, j);
          if (j == 5 && r == 9 && elect_one()) l2_prefetch(xr, XR_CAND * 16);
        }
      }
      if (ffn) {
#pragma unroll
        for (int j = 1; j >= 0; j--) {
          mbar_wait(B(B_EMPTY3 + 5 * j), j);
          if (elect_one()) {
            mbar_expect(B(B_FULL3 + 5 * j), SLOT);
            tma_ld3(sb + OFF_R3 + 5 * j * SLOT, &p.wd, B(B_FULL3 + 5 * j), 0, fid * 32, 8 * j, true);
          }
        }
      }
    } else {
      if (warp >= 2) {
#pragma unroll 1
        for (int i = tid - 64; i < XR_CAND; i += 64) xr[i] = make_uint4(~0u, ~0u, ~0u, ~0u);
        if (warp == 2) { __syncwarp(); if (lane == 0) mbar_arrive(B(B_WR)); }
      }
      if (warp == 3) {
        float ws = 0.f;
#pragma unroll
        for (int j = 0; j < 4; j++) {
          const uint4 q = __ldg(reinterpret_cast<const uint4*>(w_r) + j * 32 + lane);
          ws += bf_lo(q.x) + bf_hi(q.x) + bf_lo(q.y) + bf_hi(q.y) + bf_lo(q.z) + bf_hi(q.z) + bf_lo(q.w) + bf_hi(q.w);
        }
#pragma unroll
        for (int o = 16; o; o >>= 1) ws += __shfl_xor_sync(~0u, ws, o);
        uint2* tab = reinterpret_cast<uint2*>(sp + OFF_MISC + 512);
        tab[lane] = make_uint2(0x3F803F80u, 0x3F803F80u);
        tab[32 + lane] = __ldg(reinterpret_cast<const uint2*>(w_r + gq * 128) + lane);
        if (lane == 0) *reinterpret_cast<float*>(sp + OFF_MISC + 1024) = ws;
        __syncwarp();
        if (lane == 0) mbar_arrive(B(B_WR));
      }
      if (tid == 32) TS(0);
      mbar_wait(B(B_LN), 0);
      const uint4* src = reinterpret_cast<const uint4*>(x + (size_t)(cta * 16 + warp - 1) * DM) + lane;
      uint4* dst = reinterpret_cast<uint4*>(g_xn + (size_t)(cta * 16 + warp - 1) * DM) + lane;
      uint4 v[4];
#pragma unroll
      for (int j = 0; j < 4; j++) v[j] = __ldcs(src + j * 32);
#pragma unroll 1
      for (int r = warp - 1; r < 16; r += 3) {
        float a0 = 0.f, a1 = 0.f, b0 = 0.f, b1 = 0.f;
#pragma unroll
        for (int j = 0; j < 4; j++) {
          const uint32_t u[4] = {v[j].x, v[j].y, v[j].z, v[j].w};
#pragma unroll
          for (int i = 0; i < 4; i++) { const float a = bf_lo(u[i]), b = bf_hi(u[i]); a0 += a; a1 += b; b0 = fmaf(a, a, b0); b1 = fmaf(b, b, b1); }
        }
        a0 += a1; b0 += b1;
#pragma unroll
        for (int o = 16; o; o >>= 1) { a0 += __shfl_xor_sync(~0u, a0, o); b0 += __shfl_xor_sync(~0u, b0, o); }
        const float mean = a0 * (1.f / DM);
        float mb, inv;
        ln_round(mean, fmaxf(fmaf(b0, 1.f / DM, -mean * mean), 0.f), mb, inv);
        inv *= AT_C;
        const uint32_t nm2 = pack_bf16(-mb, -mb);
        if (r < 13) src += 384;
#pragma unroll
        for (int j = 0; j < 4; j++) {
          dst[j * 32] = make_uint4(ln_apply(v[j].x, nm2, inv), ln_apply(v[j].y, nm2, inv), ln_apply(v[j].z, nm2, inv), ln_apply(v[j].w, nm2, inv));
          sched_fence(sb + lane);
          v[j] = __ldcs(src + j * 32);
        }
        dst += 384;
      }
      __syncwarp();
      if (lane == 0) {
        fence_gpu();
        red_add(&g_cnt[C_LN + (cta >> 3)], 1);
      }
      TL(3, warp, lane == 0);
      __syncwarp();
      cluster_arrive();
      if (warp == 3) {
        if (lane == 0) {
#pragma unroll 1
          for (int i = 0; i < 6; i++) {
            const int c = i < 2 ? C_LN + (i ? ti : 15 - ti) : (i < 4 ? C_QKV + (i - 2) * 8 + mp : C_CTX + (i - 4) * 16 + mt);
            spin_until_ge<true>(&g_cnt[c], i < 2 ? 24 : 16);
            fence_async_all();
            mbar_arrive(B(B_DEP + i));
            TL(3, 4 + i, true);
          }
        }
      } else if (warp == 1 && elect_one()) {
        mbar_wait(B(B_WR), 0);
#pragma unroll 1
        for (int i = 0; i < 6; i++) {
          const int c = i < 2 ? C_QKV + gq + i * 8 : C_CTX + (i >> 2) * 16 + ((i == 3 || i == 4) ? ti : 15 - ti);
          mbar_wait(B(B_PUB + i), 0);
          if (i >= 2 && i < 5) {
            asm volatile("fence.proxy.async.shared::cta;" ::: "memory");
#pragma unroll 1
            for (int n = 0; n < 8; n++) {
              const int h = n >> 2, a = n & 3;
              asm volatile("cp.async.bulk.tensor.3d.global.shared::cta.bulk_group [%0, {%2,%3,%4}], [%1];" ::"l"(&p.ctx_st),
                           "r"(sb + (i == 4 ? 6 * SLOT + h * 16384 : (3 + 2 * h) * SLOT + (i - 2) * 16384) + a * 4096),
                           "r"(0), "r"((i == 2 ? 15 - ti : ti) * 128 + h * 64), "r"((hh + (i >> 2) * 16) * 4 + a) : "memory");
              asm volatile("cp.async.bulk.commit_group;\ncp.async.bulk.wait_group.read 0;" ::: "memory");
            }
            mbar_arrive(B(B_QP + i - 2));
            asm volatile("cp.async.bulk.wait_group 0;" ::: "memory");
          }
          fence_gpu();
          red_add(&g_cnt[c], 1);
          TS(1 + i);
        }
      }
      if (warp == 2) {
#pragma unroll 1
        for (int n = 0; n < 8; n++) {
          if (!(n & 3)) mbar_wait(B(B_XE), n >> 2);
          if ((n < 4 || ffn) && elect_one()) {
            const uint32_t fb = B(n < 4 ? B_XF : B_WF2), d = sb + 6 * SLOT + (n & 3) * 8192;
            if (!(n & 3)) mbar_expect(fb, 32768);
            if (n < 4) tma_ld3(d, &p.x, fb, 0, mt * 128 + (n >> 1) * 64, gq * 2 + (n & 1), true);
            else tma_ld2(d, (n & 1) ? &p.wg : &p.wu, fb, fid * 32, (4 + (n >> 1)) * 128, true);
          }
          __nanosleep(SL_NS);
        }
#pragma unroll 1
        for (int i = XR_CAND + lane; i < XR_SIZE; i += 32) { xr[i] = make_uint4(~0u, ~0u, ~0u, ~0u); __nanosleep(SET_NS); }
        __syncwarp();
        if (lane == 0) { fence_gpu(); mbar_arrive(B(B_SET2)); }
        TL(2, 26, lane == 0);
        __syncwarp();
      }
      __syncwarp();
      if (warp == 3) {
        mbar_wait(B(B_OUT), 0);
        uint4 kv[2];
        poll_chunks(kv, g_xr + ((lane >> 1) * 8 + gq) * XR_SIZE + XR_KEY + (lane & 1) * 2, 1);
        const uint32_t a1 = max(kv[0].x, kv[0].z), a2 = max(min(kv[0].x, kv[0].z), max(kv[0].y, kv[0].w));
        const uint32_t b1 = max(kv[1].x, kv[1].z), b2 = max(min(kv[1].x, kv[1].z), max(kv[1].y, kv[1].w));
        const uint32_t k1 = max(a1, b1), k2 = max(min(a1, b1), max(a2, b2));
        const uint32_t m1 = __reduce_max_sync(~0u, k1);
        const uint32_t m2 = __reduce_max_sync(~0u, k1 == m1 ? k2 : k1);
        auto cand = [&](uint32_t k) { return (((~k >> 7) & 15) * (8 * XR_SIZE) + ((~k >> 4) & 7) * 64) * 16; };
        const uint32_t o1 = cand(m1), o2 = cand(m2) + (((m1 ^ m2) & 0x7FF0) ? 0 : 256);
        if (lane == 0) {
          *reinterpret_cast<uint4*>(sp + OFF_MISC) = make_uint4(m1, m2, o1, o2);
          mbar_arrive(B(B_OUT2));
        }
        const uint32_t key = (lane & 4) ? m2 : m1;
        const uint4* src = g_xr + (((~key >> 7) & 15) * 8 + (rid >> 4)) * XR_SIZE;
        poll_chunks(kv, g_xr + (((lane & 4) ? o2 : o1) >> 4) + (rid >> 4) * XR_SIZE + XR_CAND + (rid & 12) + (lane & 3), 32);
        uint32_t u = key >> 16;
        u = (u & 0x8000u) ? (u & 0x7FFFu) : (~u & 0xFFFFu);
        const float rs = bf_round(sigmoid(__uint_as_float(u << 16)));
        if (lane < 8)
          *reinterpret_cast<uint4*>(sp + OFF_MISC + 128 + lane * 16) = make_uint4((rid & 2) ? ((rid & 1) ? kv[0].w : kv[0].z) : ((rid & 1) ? kv[0].y : kv[0].x),
              (rid & 2) ? ((rid & 1) ? kv[1].w : kv[1].z) : ((rid & 1) ? kv[1].y : kv[1].x), __float_as_uint(rs), 0);
#pragma unroll 1
        for (int n = 0; n < 0x400000; n++) {
          uint32_t v;
          asm volatile("ld.acquire.gpu.global.u32 %0, [%1];" : "=r"(v) : "l"(src + XR_FLAG) : "memory");
          if (__all_sync(~0u, v == 0)) break;
        }
        if (lane == 0) mbar_arrive(B(B_FIN));
      }
      if (warp == 1 && elect_one()) {
        mbar_wait(B(B_OUT3), 0);
        auto owner = [&]() {
          uint2 top;
          asm volatile("ld.shared.v2.u32 {%0,%1}, [%2];" : "=r"(top.x), "=r"(top.y) : "r"(sb + OFF_MISC) : "memory");
          return (0x7FFF - (top.x & 0x7FFF)) >> 7 == mt || (0x7FFF - (top.y & 0x7FFF)) >> 7 == mt;
        };
#pragma unroll 1
        for (int n = 0; n < 4; n++) {
          if (n && !(mbar_test(B(B_OUT2), 0) && owner())) idle(OUT_CLK);
          asm volatile("cp.async.bulk.tensor.2d.global.shared::cta.bulk_group [%0, {%2,%3}], [%1];" ::"l"(&p.out), "r"(sb + OFF_STG + n * 8192),
                       "r"(gq * 128 + (n & 1) * 64), "r"(mt * 128 + (n >> 1) * 64) : "memory");
        }
        asm volatile("cp.async.bulk.commit_group;" ::: "memory");
        mbar_wait(B(B_OUT2), 0);
        if (owner()) {
          asm volatile("cp.async.bulk.wait_group 0;" ::: "memory");
          asm volatile("st.release.gpu.global.u32 [%0], 0;" ::"l"(xr + XR_FLAG) : "memory");
        } else {
          asm volatile("cp.async.bulk.wait_group.read 0;" ::: "memory");
        }
        TL(2, 25, true);
      }
    }
    __syncwarp();
    if (warp == 0) cluster_arrive();
    cluster_wait();
    TL_DUMP();
    if (tid == 32) TS(8);
  } else {
    reg_alloc<232>();
    cluster_wait();
    const int w = wg - 1, cw = warp - 4;
    int lane = lane_id();
    const uint32_t stg = sb + OFF_STG + w * 16384 + (cw & 3) * 2048;
    auto publish = [&](int i) { __syncwarp(); if (lane == 0) mbar_arrive(B(B_PUB + i)); };
    uint32_t rbar;
    asm("mapa.shared::cluster.u32 %0, %1, %2;" : "=r"(rbar) : "r"(bar), "r"(lane & 1));
    auto release2 = [&](int i) { if (lane < 2) asm volatile("mbarrier.arrive.shared::cluster.b64 _, [%0];" ::"r"(rbar + 8 * i) : "memory"); };
    float R[128];
    float O[64], acc[64];
    uint32_t pk[64];
    uint32_t* const Q = pk;
    uint32_t P[32];
    auto packed = [&](int i) {
      const float* v = R + 16 * (i >> 1) + 2 * (i & 1);
      return make_uint4(pack_bf16(v[0], v[1]), pack_bf16(v[4], v[5]), pack_bf16(v[8], v[9]), pack_bf16(v[12], v[13]));
    };
    const uint32_t q_st = sb + (cw & 3) * 1024 + (lane >> 2) * 64 + (((lane & 3) ^ (lane >> 3)) << 4);
    const uint32_t q_ld = sb + (cw & 3) * 1024 + (lane & 15) * 64 + (((lane >> 4) ^ ((lane >> 1) & 3)) << 4);
    auto park = [&](uint32_t off, int i, uint4 v) {
      asm volatile("st.shared.v4.u32 [%0], {%1,%2,%3,%4};" ::"r"(q_st + off + (i >> 1) * 4096 + (i & 1) * 512), "r"(v.x), "r"(v.y), "r"(v.z), "r"(v.w) : "memory");
    };
    auto load_q = [&](uint32_t off, int k) { ldsm4(Q + 4 * k, ((q_ld + off) ^ ((k & 1) << 5)) + (k >> 1) * 4096); };
    {
      TL(0, 1, tid == 128);
      __nv_bfloat16* pdst = g_qkv;
      auto put2 = [&](int j) {
#pragma unroll
        for (int i = (j >> 1) * 4 + (j & 1); i < (j >> 1) * 4 + 4; i += 2)
          __stcs(reinterpret_cast<uint4*>(pdst + (i & 1) * 8 * NQ + (i >> 1) * 32), make_uint4(pk[4 * i], pk[4 * i + 1], pk[4 * i + 2], pk[4 * i + 3]));
      };
      const uint64_t da0 = mk_desc(sb + w * 8192, 16, 1024, 1);
      const uint64_t db0 = mk_desc(sb + 16384, 8192, 1024, 1);
      int st = 0; uint32_t ph = 0;
      auto issue = [&](int accum, auto between, bool res = false) {
        mbar_wait_c(B(B_FULL1 + st), ph);
        const uint64_t da = desc_add(da0, res ? 6 * SLOT + st * 8192 : st * P1_STAGE), db = desc_add(db0, st * P1_STAGE);
        between();
        wg_fence();
#pragma unroll
        for (int k = 0; k < 4; k++) mma_n256_ss<1>(R, desc_add(da, k * 32), desc_add(db, k * 2048), k == 0 ? accum : 1);
        wg_commit();
      };
      issue(0, []() {});
#pragma unroll 1
      for (int t = 0;; t++) {
        const int nk = t >= 4 ? 16 : 8;
        const bool tr = t > 0 && t < 5;
        TL(0, 2 + 2 * t + 16 * w, (tid & 127) == 0);
        int prev = st;
        if (++st == 4) { st = 0; ph ^= 1; }
#pragma unroll 1
        for (int kb = 1; kb < nk; kb++) {
          if (kb == nk - 1 && w == 1) bar_sync(5, 256);
          issue(1, []() {}, t < 4 && (kb & 5) == 4);
          if (kb == nk - 1 && w == 0) bar_arrive(5, 256);
          if (tr) {
#pragma unroll
            for (int i = 1; i < 8; i++) if (kb == i) put2(i);
            if (kb == 7 && !(t & 1)) publish((t >> 1) - 1);
          } else if (t == 5) {
            if (kb == 2) {
#pragma unroll
              for (int i = 0; i < 8; i++) park(6 * SLOT + w * 16384, i, make_uint4(pk[4 * i], pk[4 * i + 1], pk[4 * i + 2], pk[4 * i + 3]));
              __syncwarp();
            }
            if (kb == 4) {
#pragma unroll
              for (int k = 0; k < 8; k++) load_q(6 * SLOT + w * 16384, k);
              __syncwarp();
            }
            if (kb == 6) {
#pragma unroll
              for (int i = 0; i < 8; i++) park(6 * SLOT + w * 16384, i, make_uint4(pk[32 + 4 * i], pk[33 + 4 * i], pk[34 + 4 * i], pk[35 + 4 * i]));
            }
          }
          wg_wait<1>();
          release2(B_EMPTY1 + prev);
          prev = st;
          if (++st == 4) { st = 0; ph ^= 1; }
        }
        if (t == 5) break;
        issue(0, [&]() {
          sched_fence(q_st);
          wg_wait<0>();
          fence_regs<128>(R);
          TL(0, 3 + 2 * t + 16 * w, (tid & 127) == 0);
#pragma unroll
          for (int i = 0; i < 16; i++) { const uint4 v = packed(i); pk[4 * i] = v.x; pk[4 * i + 1] = v.y; pk[4 * i + 2] = v.z; pk[4 * i + 3] = v.w; }
          release2(B_EMPTY1 + prev);
          fence_regs<128>(R);
        });
        if (w == 1) bar_arrive(4, 256);
        sched_fence(q_st);
        pdst = g_qkv + (size_t)(((t & 1) + 1) * SEQ + mt * 128 + cw * 16 + (lane >> 2)) * NQ + (gq + (t >> 1) * 8) * 256 + (lane & 3) * 8;
        if (t < 4) put2(0);
        if (w == 0) bar_sync(4, 256);
      }
      if (w == 1) bar_arrive(6, 256);
      mbar_wait_c(B(B_KF), 0);
      sched_fence(q_st);
      wg_wait<0>();
      fence_regs<128>(R);
      release2(B_EMPTY1 + 3);
      TL(0, 13 + 16 * w, (tid & 127) == 0);
    }
    auto issue3 = [&](int st, uint32_t ph, int accum) {
      mbar_wait_c(B(B_FULL3 + st), ph);
      const uint64_t da = mk_desc(sb + OFF_R3 + w * 8192 + st * SLOT, 16, 1024, 1), db = mk_desc(sb + OFF_R3 + 16384 + st * SLOT, 8192, 1024, 1);
      wg_fence();
#pragma unroll
      for (int k = 0; k < 4; k++) mma_n128_ss<1>(acc, desc_add(da, k * 32), desc_add(db, k * 2048), k == 0 ? accum : 1);
      wg_commit();
    };
    uint32_t wf[128];
    auto w_addr = [&](uint32_t off, int m) {
      const uint32_t w_ld = sb + ((lane >> 3) & 1) * 8192 + ((cw >> 1) * 32 + (lane & 7) + (lane >> 4) * 8) * 64 + ((((cw & 1) * 2) ^ ((lane >> 1) & 3)) << 4);
      return ((w_ld + off) ^ ((m & 1) << 4)) + (m >> 2) * 16384 + ((m >> 1) & 1) * 1024;
    };
    auto grab = [&](uint32_t* d, uint32_t off, int m0, int m1) {
#pragma unroll
      for (int m = m0; m < m1; m++)
        asm volatile("ldmatrix.sync.aligned.m8n8.x4.trans.shared.b16 {%0,%1,%2,%3}, [%4];"
                     : "=r"(d[4 * m]), "=r"(d[4 * m + 1]), "=r"(d[4 * m + 2]), "=r"(d[4 * m + 3]) : "r"(w_addr(off, m)) : "memory");
    };
    float inv[2] = {0.f, 0.f};
    auto scaled = [&](int i) {
      const float* o = O + 16 * (i >> 1) + 2 * (i & 1);
      const float c = inv[i & 1];
      return make_uint4(pack_bf16(o[0] * c, o[1] * c), pack_bf16(o[4] * c, o[5] * c), pack_bf16(o[8] * c, o[9] * c), pack_bf16(o[12] * c, o[13] * c));
    };
    {
      const int wrow = cw * 16;
      const uint64_t dk0 = mk_desc(sb, 16, 1024, 1);
      const uint64_t dv0 = mk_desc(sb + 2 * SLOT, 16384, 1024, 1);
      const uint32_t pin = sb + OFF_MISC + 1028;
      float l0 = 0.f, l1 = 0.f;
      int g = 0, t = 0;
      uint32_t fail = 0;
      auto piece = [&](int tt) { return (uint32_t)(tt == 3 ? 6 * SLOT + w * 16384 : (3 + 2 * w) * SLOT + (tt - 1) * 16384); };
      uint32_t par = 0;
      auto issue_s = [&](float* S) {
        const uint64_t dk = desc_add(dk0, par * 16);
        mma_n128_rs0(S, Q, dk);
#pragma unroll
        for (int k = 1; k < 8; k++) mma_n128_rs<0>(S, Q + 4 * k, desc_add(dk, (k >> 2) * 16384 + (k & 3) * 32), 1);
        wg_commit();
      };
      auto issue_pv = [&](bool half, int accum) {
        const uint64_t dv = desc_add(dv0, ((g - 1) & 1) * 2 * SLOT);
        wg_fence();
#pragma unroll
        for (int k = 0; k < 4; k++) mma_n128_rs<1>(O, P + 4 * k, desc_add(dv, k * 2048), k == 0 ? accum : 1);
        wg_commit();
        if (UNLIKELY(half)) {
          wg_fence();
          wg_commit();
        } else {
          wg_fence();
#pragma unroll
          for (int k = 4; k < 8; k++) mma_n128_rs<1>(O, P + 4 * k, desc_add(dv, k * 2048), 1);
          wg_commit();
        }
        bar_arrive(2 - w, 256);
        wg_wait<2>();
        fence_regs<32>(Q);
      };
      auto release_k = [&]() { release2(B_KE); rbar ^= 8; };
      auto pv_done = [&]() {
        TC(g, 3);
        sched_fence(q_st);
        wg_wait<0>();
        fence_regs<64>(O); fence_regs<32>(P);
        TC(g, 4);
        release2(B_VE);
      };
      auto row_inv = [&](bool go) {
        float a = l0 + __shfl_xor_sync(~0u, l0, 1), b = l1 + __shfl_xor_sync(~0u, l1, 1);
        a += __shfl_xor_sync(~0u, a, 2); b += __shfl_xor_sync(~0u, b, 2);
        const bool ok = __all_sync(~0u, a >= AT_LO && a <= AT_HI && b >= AT_LO && b <= AT_HI) != 0;
        asm("rcp.approx.ftz.f32 %0, %1;" : "=f"(inv[0]) : "f"(a));
        asm("rcp.approx.ftz.f32 %0, %1;" : "=f"(inv[1]) : "f"(b));
        fail |= (uint32_t)(go && !ok) << t;
        l0 = go ? 0.f : l0; l1 = go ? 0.f : l1;
        t += go;
      };
      const uint64_t m_first = 1ull | (1ull << (16 - ti)) | (1ull << 17) | (1ull << (18 + ti));
      const uint64_t m_diag = (3ull << (15 - ti)) | (3ull << (17 + ti));
      enum { F_FIRST = 1, F_DIAG = 2, F_LAST = 4, F_PFIRST = 8, F_PHALF = 16, F_STOP = 32 };
      auto kind = [&](int gn) {
        const uint32_t a = (uint32_t)((m_first << 1) >> gn), d = (uint32_t)((m_diag << 1) >> gn);
        return ((a >> 1) & 1) * F_FIRST | ((d >> 1) & 1) * F_DIAG | ((a >> 2) & 1) * F_LAST | (a & 1) * F_PFIRST |
               (w == 0 ? (d & 1) * F_PHALF | ((d >> 1) & 1) * F_STOP : 0) | (gn == 34 ? F_STOP : 0);
      };
      uint32_t kinds;
      {
        uint32_t qt[64];
#pragma unroll
        for (int i = 0; i < 16; i++) { const uint4 v = packed(i); qt[4 * i] = v.x; qt[4 * i + 1] = v.y; qt[4 * i + 2] = v.z; qt[4 * i + 3] = v.w; }
        fence_regs<64>(qt);
        sched_fence(q_st);
        float S[64];
        wg_fence();
        issue_s(S);
        bar_arrive(w ? 1 : 7, 256);
        bar_sync(6 + w, 256);
        sched_fence(q_st);
        TL(1, 0, tid == 128);
#pragma unroll
        for (int i = 0; i < 16; i++) park(piece(1), i, make_uint4(qt[4 * i], qt[4 * i + 1], qt[4 * i + 2], qt[4 * i + 3]));
        kinds = pinned(kind(lane + 3));
        sched_fence(q_st);
        wg_wait<0>();
        fence_regs<64>(S);
        release_k();
        TL(1, 1, tid == 128);
        const bool kok = mbar_try(B(B_KF + 1), 0);
        at_exp<0, 32>(S);
        sched_fence(q_st);
        at_exp<32, 64>(S); at_fin<0, 64>(S, P);
        if (UNLIKELY(!kok)) mbar_wait_c(B(B_KF + 1), 0);
        TL(1, 2, tid == 128);
      }
      uint32_t f = F_PFIRST, fn;
      auto shadow = [&]() {
        const bool vok = mbar_try(B(B_VF + ((g - 1) & 1)), ((g - 1) >> 1) & 1);
        at_sum(P, f & F_PHALF, l0, l1);
        fn = __shfl_sync(~0u, kinds, max(g - 2, 0));
        if (UNLIKELY(!vok)) mbar_wait_c(B(B_VF + ((g - 1) & 1)), ((g - 1) >> 1) & 1);
      };
      auto hand_over = [&]() { __syncwarp(); if (lane == 0 && !((fail >> (t - 1)) & 1)) mbar_arrive(B(B_PUB + 1 + t)); };
      auto exp_q = [&](float* S, auto kc, auto nc) {
        constexpr int k = decltype(kc)::value, n = decltype(nc)::value;
        asm volatile("{\n.reg .pred p;\nsetp.ne.b32 p, %5, 0;\n@p ldmatrix.sync.aligned.m8n8.x4.shared.b16 {%0,%1,%2,%3}, [%4];\n}"
                     : "+r"(Q[4 * k]), "+r"(Q[4 * k + 1]), "+r"(Q[4 * k + 2]), "+r"(Q[4 * k + 3])
                     : "r"(((q_ld + piece(t + 1)) ^ ((k & 1) << 5)) + (k >> 1) * 4096), "r"(f & F_LAST) : "memory");
        at_exp<n * k, n * k + n>(S);
      };
      g = 1; par = SLOT / 16;
#pragma unroll 1
      for (;;) {
        {
          TC(g, 0);
          bar_sync(1 + w, 256);
          fence_regs<32>(Q);
          float S[64];
          wg_fence();
          issue_s(S);
          sched_fence(q_st);
          TC(g, 1);
          shadow();
          fence_regs<64>(O); fence_regs<32>(P);
          issue_pv(f & F_PHALF, ~f & F_PFIRST);
          fence_regs<64>(S);
          TC(g, 2);
          release_k();
          at_exp<0, 8>(S);
          const bool first = f & F_FIRST;
          if (UNLIKELY(f & (F_FIRST | F_LAST))) {
            row_inv(first);
            at_mask(S + 32, (f & F_DIAG) ? wrow - 64 : 64, lane);
            unroll8([&](auto kc) { exp_q(S + 8, kc, std::integral_constant<int, AT_R1 / 8 - 1>{}); });
          } else {
            at_exp<8, AT_R1>(S);
          }
          pv_done();
          g = pinned(g + 1); par = pinned(par ^ (SLOT / 16)); f = fn;
          const bool kok = mbar_try(B(B_KF + (g & 1)), g < 34 ? (g >> 1) & 1 : 0);
          if (UNLIKELY(first)) {
            unroll8([&](auto ic) {
              constexpr int i = decltype(ic)::value, n = (64 - AT_R1) / 8;
              at_exp<AT_R1 + n * i, AT_R1 + n * i + n>(S);
              park(piece(t), i, scaled(i));
            });
            at_fin<0, 64>(S, P);
            hand_over();
          } else {
            at_exp<AT_R1, 64>(S); at_fin<0, 64>(S, P);
          }
          TC(g - 1, 5);
          if (!TCLK) TL(1, 1 + g, tid == 128);
          if (kok && !(f & F_STOP)) continue;
          if (UNLIKELY(!kok)) mbar_wait_c(B(B_KF + (g & 1)), (g >> 1) & 1);
          if (g == 34) break;
        }
#pragma unroll 1
        while (f & F_STOP) {
          TC(g, 0);
          bar_sync(1, 256);
          fence_regs<64>(O); fence_regs<32>(Q); fence_regs<32>(P);
          float S[32];
          const uint64_t dk = desc_add(dk0, par * 16);
          wg_fence();
          mma_n64_rs0(S, Q, dk);
#pragma unroll
          for (int k = 1; k < 8; k++) mma_n64_rs(S, Q + 4 * k, desc_add(dk, (k >> 2) * 16384 + (k & 3) * 32), 1);
          wg_commit();
          TC(g, 1);
          mbar_wait_c(B(B_VF + ((g - 1) & 1)), ((g - 1) >> 1) & 1);
          issue_pv(f & F_PHALF, ~f & F_PFIRST);
          fence_regs<32>(S);
          TC(g, 2);
          release_k();
          const bool first = f & F_FIRST;
          at_sum(P, f & F_PHALF, l0, l1);
          fn = __shfl_sync(~0u, kinds, g - 2);
          row_inv(first);
          pv_done();
          sched_fence(q_st);
          at_mask(S, wrow, lane);
          unroll8([&](auto kc) { exp_q(S, kc, std::integral_constant<int, 4>{}); });
          g++; par ^= SLOT / 16; f = fn;
          at_fin<0, 32>(S, P);
          if (first) {
#pragma unroll
            for (int i = 0; i < 8; i++) park(piece(t), i, scaled(i));
            hand_over();
          }
          TC(g - 1, 5);
          if (!TCLK) TL(1, 1 + g, tid == 128);
          mbar_wait_c(B(B_KF + (g & 1)), (g >> 1) & 1);
        }
      }
      const bool wok = mbar_test(B(ffn ? B_WF : B_QP + 1), 0);
      grab(wf, 3 * SLOT, 0, 8);
      mbar_wait_c(B(B_VF + 1), 0);
      bar_sync(1 + w, 256);
      fence_regs<64>(O); fence_regs<32>(P);
      wg_fence();
#pragma unroll
      for (int k = 0; k < 8; k++) mma_n128_rs<1>(O, P + 4 * k, desc_add(dv0, 2 * SLOT + k * 2048), 1);
      wg_commit();
      if (w == 0) bar_arrive(2, 256);
      pin_order(__uint_as_float(wf[28] & wf[24]), pin);
      __syncwarp();
      if (wok) release2(B_WE);
      TL(3, 12 + 16 * w, (tid & 127) == 0);
      sched_fence(q_st);
      at_sum(P, false, l0, l1);
      row_inv(true);
      sched_fence(q_st);
      wg_wait<0>();
      fence_regs<64>(O); fence_regs<32>(P);
      release2(B_VE + 1);
      if (UNLIKELY(!wok || fail != 0)) {
#pragma unroll 1
        for (int tt = 0; tt < 4; tt++) {
          if (!((tt < 3 ? fail >> tt : fail != 0) & 1)) continue;
          slow_tile(O, P, l0, l1, wq, (((tt + 1) & 2) ? ti : 15 - ti) * 128 + wrow, hh + (tt & 2) * 8, lane, q_st);
          row_inv(false);
          if (tt < 3) {
#pragma unroll
            for (int i = 0; i < 8; i++) park(piece(tt + 1), i, scaled(i));
            publish(2 + tt);
          }
        }
        if (!wok) {
          mbar_wait_c(B(ffn ? B_WF : B_QP + 1), 0);
          grab(wf, 3 * SLOT, 0, 8);
          pin_order(__uint_as_float(wf[28] & wf[24]), pin);
          __syncwarp();
          release2(B_WE);
        }
      }
      TL(3, 13 + 16 * w, (tid & 127) == 0);
      issue3(0, 0, 0);
      TL(3, 14 + 16 * w, (tid & 127) == 0);
      TL(1, 36, tid == 128);
    }
    uint32_t hp[32];
    lane = lane_id();
    {
      int st = 1, prev = 0; uint32_t ph = 0;
      __nv_bfloat16* dst = g_qkv + (size_t)((15 - ti) * 128 + cw * 16 + (lane >> 2)) * NQ + (hh + 16) * 128 + (lane & 3) * 8;
      auto kblock = [&](auto between, int lim = 6) {
        issue3(st, ph, 1);
        between();
        wg_wait<1>();
        release2(B_EMPTY3 + prev);
        prev = st;
        if (++st == lim) { st = 0; ph ^= 1; }
      };
      uint4 ob[8];
      kblock([&]() { sched_fence(rbar); ob[0] = scaled(0); ob[1] = scaled(2); ob[2] = scaled(1); ob[3] = scaled(3); sched_fence(rbar); });
      kblock([&]() { sched_fence(rbar); ob[4] = scaled(4); ob[5] = scaled(6); ob[6] = scaled(5); ob[7] = scaled(7); sched_fence(rbar); grab(wf + 32, 5 * SLOT, 0, 8); });
#pragma unroll 1
      for (int kb = 3; kb < 11; kb++) {
        kblock([&]() {
          sched_fence(rbar);
#pragma unroll
          for (int i = 0; i < 8; i++)
            if (kb == 3 + i) *reinterpret_cast<uint4*>(dst + (i & 2) * 4 * NQ + (i & 1) * 32 + (i & 4) * 16) = ob[i];
          TL(3, 14 + kb + 16 * w, (tid & 127) == 0);
          if (kb == 8) TL(2, 2, tid == 128);
        }, kb == 4 ? 5 : 6);
        if (kb == 4) release2(B_EMPTY3 + 5);
      }
      publish(5);
      kblock([&]() { mbar_wait_c(B(ffn ? B_WF2 : B_QP + 2), 0); grab(wf + 32, 5 * SLOT, 8, 16); });
#pragma unroll 1
      for (int kb = 12; kb < G_KB; kb++) {
        kblock([&]() { if ((kb & 7) == 0) TL(2, 1 + (kb >> 3), tid == 128); });
        if (kb == X_KB && lane == 0) mbar_arrive(B(B_XE));
      }
      kblock([&]() {
        mbar_wait_c(B(B_XF), 0);
#pragma unroll
        for (int i = 0; i < 8; i++)
          ldsm4(hp + 4 * i, sb + 6 * SLOT + w * 16384 + ((cw & 3) * 16 + (lane & 15)) * 128 + (i >> 2) * 8192 + ((((i & 3) * 2 + (lane >> 4)) ^ (lane & 7)) << 4));
      });
#pragma unroll 1
      for (int kb = G_KB + 1; kb < 64; kb++) {
        kblock([&]() { if ((kb & 7) == 0) TL(2, 1 + (kb >> 3), tid == 128); });
        if (kb == G_KB + 2 && lane == 0) mbar_arrive(B(B_XE));
      }
    }
    lane = lane_id();
    const int r0 = lane >> 2, q4 = lane & 3, ct = cw * 32 + lane;
    uint32_t tb[16];
    mbar_wait_c(B(B_WR), 0);
#pragma unroll
    for (int i = 0; i < 4; i++) ldsm4(tb + 4 * i, sb + OFF_MISC + 512 + (lane & 1) * 256 + (lane >> 3) * 16 + i * 64);
    mbar_wait_c(B(B_SET2), 0);
    float4* const psd = reinterpret_cast<float4*>(xr + XR_PS + cw * 16 + r0);
    const uint4* const pss = g_xr + (mt * 8 + (ct & 1) * 4) * XR_SIZE + XR_PS + (ct >> 1);
    sched_fence(stg);
    wg_wait<0>();
    fence_regs<64>(acc);
    TL(2, 10, tid == 128);
    {
      float d[2][4] = {}, qa[2][4] = {}, qb[2][4] = {};
#pragma unroll
      for (int j = 0; j < 16; j++) {
        hp[2 * j] = hadd2_bf(hp[2 * j], pack_bf16(acc[4 * j], acc[4 * j + 1]));
        hp[2 * j + 1] = hadd2_bf(hp[2 * j + 1], pack_bf16(acc[4 * j + 2], acc[4 * j + 3]));
        if (j & 1) {
          mma16816(d[(j >> 1) & 1], hp[2 * j - 2], hp[2 * j - 1], hp[2 * j], hp[2 * j + 1], tb[j - 1], tb[j]);
          mma16816(qa[(j >> 1) & 1], hp[2 * j - 2], hp[2 * j - 1], hp[2 * j], hp[2 * j + 1], hp[2 * j - 2], hp[2 * j]);
          mma16816(qb[(j >> 1) & 1], hp[2 * j - 2], hp[2 * j - 1], hp[2 * j], hp[2 * j + 1], hp[2 * j - 1], hp[2 * j + 1]);
        }
      }
      if (q4 == (r0 >> 1)) {
        __stcg(psd, make_float4(d[0][0] + d[1][0], (r0 & 1) ? qa[0][1] + qa[1][1] : qa[0][0] + qa[1][0], d[0][1] + d[1][1], 0.f));
        __stcg(psd + 8, make_float4(d[0][2] + d[1][2], (r0 & 1) ? qb[0][3] + qb[1][3] : qb[0][2] + qb[1][2], d[0][3] + d[1][3], 0.f));
      }
    }
    TL(2, 11, tid == 128);
    mbar_wait_c(B(B_EMPTY3 + 1), 0);
    stage_store_128(stg, lane, hp);
    if (ffn) mbar_wait_c(B(B_WF2), 1);
    grab(wf + 96, 6 * SLOT, 0, 8);
    const float wsum = *reinterpret_cast<const float*>(sp + OFF_MISC + 1024);
    __syncwarp();
    {
      uint4 ps[4];
      poll_chunks(ps, pss, XR_SIZE);
      TL(2, 12, tid == 128);
      auto F = [](uint32_t u) { return __uint_as_float(u); };
      float s1 = (F(ps[0].x) + F(ps[1].x)) + (F(ps[2].x) + F(ps[3].x)), s2 = (F(ps[0].y) + F(ps[1].y)) + (F(ps[2].y) + F(ps[3].y));
      float s3 = (F(ps[0].z) + F(ps[1].z)) + (F(ps[2].z) + F(ps[3].z));
      __syncwarp();
      s1 += __shfl_xor_sync(~0u, s1, 1); s2 += __shfl_xor_sync(~0u, s2, 1); s3 += __shfl_xor_sync(~0u, s3, 1);
      const float mean = s1 * (1.f / DM);
      float mb, inv;
      ln_round(mean, fmaxf(fmaf(s2, 1.f / DM, -mean * mean), 0.f), mb, inv);
      const uint32_t u = pack_bf16(0.f, fmaf(s3 - mb * wsum, inv, 0.f));
      const uint32_t key = (u ^ ((((int)u >> 31) & 0x7FFF0000u) | 0x80000000u)) | (0x7FFFu - (mt * 128 + (ct >> 1)));
      const uint32_t nm2 = pack_bf16(-mb, -mb);
      const uint32_t c1 = __reduce_max_sync(~0u, key);
      const uint32_t c2 = __reduce_max_sync(~0u, key == c1 ? 0u : key);
      if (lane == 0) {
        __stcg(reinterpret_cast<uint2*>(psd) + (XR_KEY - XR_PS) * 2 - cw * 31, make_uint2(c1, c2));
        mbar_arrive(B(B_OUT));
      }
      TL(2, 13, tid == 128);
      const int row = (0x7FFF - (((lane >> 4) ? c2 : c1) & 0x7FFF)) & 15;
      const uint32_t rn = __shfl_sync(~0u, nm2, row * 2);
      const float ri = __shfl_sync(~0u, inv, row * 2);
      uint32_t v[4];
#pragma unroll
      for (int i = 0; i < 4; i++)
        asm volatile("ld.shared.u32 %0, [%1];" : "=r"(v[i]) : "r"(stg + ((lane >> 3) & 1) * 8192 + row * 128 + ((((lane & 4) + i) ^ (row & 7)) << 4) + q4 * 4) : "memory");
      __stcg(xr + XR_CAND + cw * 64 + 32 + lane, make_uint4(ln_apply(v[0], rn, ri), ln_apply(v[1], rn, ri), ln_apply(v[2], rn, ri), ln_apply(v[3], rn, ri)));
      __stcg(xr + XR_CAND + cw * 64 + lane, make_uint4(v[0], v[1], v[2], v[3]));
      sched_fence(stg);
      const uint32_t na = __shfl_sync(~0u, nm2, r0 * 2), nb = __shfl_sync(~0u, nm2, r0 * 2 + 16);
      const float ia = __shfl_sync(~0u, inv, r0 * 2), ib = __shfl_sync(~0u, inv, r0 * 2 + 16);
#pragma unroll
      for (int i = 0; i < 32; i++) hp[i] = hadd2_bf(hp[i], ln_apply(hp[i], (i & 1) ? nb : na, (i & 1) ? ib : ia));
      __syncwarp();
      stage_store_128(stg, lane, hp);
      asm volatile("fence.proxy.async.shared::cta;" ::: "memory");
      publish(B_OUT3 - B_PUB);
    }
    uint32_t wd[16][4];
    sched_fence(stg);
    if (ffn) mbar_wait_c(B(B_FULL3 + 5 * w), 1 - w);
    auto load_wd = [&](int h) {
#pragma unroll
      for (int i = h; i < 16; i += 2)
        asm volatile("ldmatrix.sync.aligned.m8n8.x4.trans.shared.b16 {%0,%1,%2,%3}, [%4];"
                     : "=r"(wd[i][0]), "=r"(wd[i][1]), "=r"(wd[i][2]), "=r"(wd[i][3])
                     : "r"(sb + OFF_R3 + 5 * w * SLOT + (2 * (cw & 3) + (i >> 3)) * 4096 + (h * 16 + (lane & 7) + (lane >> 4) * 8) * 128 +
                           (((2 * ((i >> 1) & 3) + ((lane >> 3) & 1)) ^ (lane & 7)) << 4)) : "memory");
    };
    load_wd(0);
    __syncwarp();
    cluster_arrive();
    const char* xsrc = reinterpret_cast<const char*>(g_xr + (r0 >> 1) * XR_SIZE + XR_CAND + 32 + (cw >> 1) * 4 + q4);
    asm volatile("" : "+l"(xsrc));
    sched_fence(stg);
    TL(2, 22, tid == 128);
    mbar_wait_c(B(B_OUT2), 0);
    TL(2, 14, tid == 128);
    if (ffn) {
      uint4 xb[2];
      poll_chunks(xb, reinterpret_cast<const uint4*>(xsrc + *reinterpret_cast<const uint32_t*>(sp + OFF_MISC + 8 + (r0 & 1) * 4)), 4 * XR_SIZE);
      __syncwarp();
      TL(2, 15, tid == 128);
      float d[8][4] = {};
#pragma unroll
      for (int n = 0; n < 32; n++) {
        if (n == 8) { sched_fence(stg); load_wd(1); }
        const int s = (n >> 4) * 4 + ((n >> 1) & 3), m = ((n >> 3) & 1) * 2 + (n & 1);
        const uint32_t* a = wf + 16 * s + 4 * m;
        mma16816(d[n & 7], a[0], a[1], a[2], a[3], (m & 2) ? xb[s >> 2].z : xb[s >> 2].x, (m & 2) ? xb[s >> 2].w : xb[s >> 2].y);
      }
      float v[8];
#pragma unroll
      for (int i = 0; i < 8; i++) {
        const float lo = (q4 & 1) ? d[2 + (i >> 2)][i & 3] : d[i >> 2][i & 3], hi = (q4 & 1) ? d[6 + (i >> 2)][i & 3] : d[4 + (i >> 2)][i & 3];
        v[i] = (q4 & 2) ? hi : lo;
      }
#pragma unroll
      for (int i = 0; i < 4; i++) v[i] = ((q4 & 2) ? v[i + 4] : v[i]) + __shfl_xor_sync(~0u, (q4 & 2) ? v[i] : v[i + 4], 2);
#pragma unroll
      for (int i = 0; i < 2; i++) v[i] = ((q4 & 1) ? v[i + 2] : v[i]) + __shfl_xor_sync(~0u, (q4 & 1) ? v[i] : v[i + 2], 1);
      float4* red = reinterpret_cast<float4*>(sp + SL_SCR * SLOT);
      reinterpret_cast<float2*>(red + cw * 16 + (q4 >> 1) * 8 + r0)[q4 & 1] = make_float2(v[0], v[1]);
      bar_sync(3, 256);
      TL(2, 16, tid == 128);
      const float4 z0 = red[lane], z1 = red[32 + lane], z2 = red[64 + lane], z3 = red[96 + lane];
      const uint32_t ub = pack_bf16((z0.x + z1.x) + (z2.x + z3.x), (z0.y + z1.y) + (z2.y + z3.y));
      const uint32_t gb = pack_bf16((z0.z + z1.z) + (z2.z + z3.z), (z0.w + z1.w) + (z2.w + z3.w));
      const float g0 = bf_lo(gb), g1 = bf_hi(gb);
      const uint32_t sg = pack_bf16(g0 * sigmoid(g0), g1 * sigmoid(g1));
      const uint32_t act = pack_bf16(bf_lo(sg) * bf_lo(ub), bf_hi(sg) * bf_hi(ub));
      const uint32_t pr = __byte_perm(act, __shfl_xor_sync(~0u, act, 1), (lane & 1) ? 0x3276 : 0x5410);
      const int src = q4 * 2 + (r0 & 1);
      const uint32_t a0 = __shfl_sync(~0u, pr, src), a1 = __shfl_sync(~0u, pr, src + 8), a2 = __shfl_sync(~0u, pr, src + 16), a3 = __shfl_sync(~0u, pr, src + 24);
      TL(2, 17, tid == 128);
      float y[8][4] = {};
#pragma unroll
      for (int i = 0; i < 8; i++) mma16816(y[i], wd[2 * i][0], wd[2 * i][1], wd[2 * i][2], wd[2 * i][3], a0, a1);
#pragma unroll
      for (int i = 0; i < 8; i++) mma16816(y[i], wd[2 * i + 1][0], wd[2 * i + 1][1], wd[2 * i + 1][2], wd[2 * i + 1][3], a2, a3);
      float2* yd = reinterpret_cast<float2*>(g_xr + (cw * 16 + 2 * q4) * XR_SIZE + XR_Y + fid * 4) + r0;
#pragma unroll
      for (int j = 0; j < 2; j++) {
        float v[4];
#pragma unroll
        for (int e = 0; e < 4; e++) {
          const float lo = (q4 & 1) ? y[4 * j + 1][e] : y[4 * j][e], hi = (q4 & 1) ? y[4 * j + 3][e] : y[4 * j + 2][e];
          v[e] = (q4 & 2) ? hi : lo;
        }
        __stcg(yd + j * 16 * XR_SIZE, make_float2(v[0], v[1]));
        __stcg(yd + j * 16 * XR_SIZE + 2 * XR_SIZE, make_float2(v[2], v[3]));
      }
    }
    TL(2, 18, tid == 128);
    cluster_wait();
    if (rid == 127 && ct < C_NUM) g_cnt[ct] = 0;
    if (cw < 2) {
      const int tok = (lane >> 1) & 1, pair = cw * 2 + (lane & 1);
      uint32_t* const dst = reinterpret_cast<uint32_t*>(out + (size_t)(~*reinterpret_cast<const uint32_t*>(sp + OFF_MISC + tok * 4) & 0x7FF) * DM) + rid * 4 + pair;
      idle(ffn ? Y_CLK : Y_CLK + 2000);
      const bool fin = mbar_test(B(B_FIN), 0);
      uint4 op = lds128(sb + OFF_MISC + 128 + (tok * 4 + pair) * 16);
      uint4 z[7];
      poll_chunks(z, xr + XR_Y + (lane >> 1) * 4 + pair, 64);
      __syncwarp();
      TL(2, 19, tid == 128);
      if (!fin) { mbar_wait_c(B(B_FIN), 0); op = lds128(sb + OFF_MISC + 128 + (tok * 4 + pair) * 16); }
      auto F = [](uint32_t u) { return __uint_as_float(u); };
      const float v0 = ((F(z[0].x) + F(z[1].x)) + (F(z[2].x) + F(z[3].x))) + ((F(z[4].x) + F(z[5].x)) + F(z[6].x));
      const float v1 = ((F(z[0].y) + F(z[1].y)) + (F(z[2].y) + F(z[3].y))) + ((F(z[4].y) + F(z[5].y)) + F(z[6].y));
      const float v2 = ((F(z[0].z) + F(z[1].z)) + (F(z[2].z) + F(z[3].z))) + ((F(z[4].z) + F(z[5].z)) + F(z[6].z));
      const float v3 = ((F(z[0].w) + F(z[1].w)) + (F(z[2].w) + F(z[3].w))) + ((F(z[4].w) + F(z[5].w)) + F(z[6].w));
      float ya = (tok ? v1 : v0) + __shfl_xor_sync(~0u, tok ? v0 : v1, 2), yb = (tok ? v3 : v2) + __shfl_xor_sync(~0u, tok ? v2 : v3, 2);
#pragma unroll
      for (int o = 4; o < 32; o <<= 1) { ya += __shfl_xor_sync(~0u, ya, o); yb += __shfl_xor_sync(~0u, yb, o); }
      const uint32_t yp = pack_bf16(ya, yb);
      if (lane < 4) *dst = hadd2_bf(op.x, hadd2_bf(op.y, pack_bf16(bf_lo(yp) * F(op.z), bf_hi(yp) * F(op.z))));
      TL(2, 21, tid == 128);
    }
    TL(2, 20, tid == 128);
    TL_DUMP();
  }
}

typedef CUresult (*EncodeFn)(CUtensorMap*, CUtensorMapDataType, cuuint32_t, void*, const cuuint64_t*, const cuuint64_t*, const cuuint32_t*,
                             const cuuint32_t*, CUtensorMapInterleave, CUtensorMapSwizzle, CUtensorMapL2promotion, CUtensorMapFloatOOBfill);
EncodeFn g_enc = nullptr;

void map2(CUtensorMap* m, const void* ptr, uint64_t rows, uint64_t cols, uint32_t bc, uint32_t br) {
  const CUtensorMapSwizzle sw = bc == 64 ? CU_TENSOR_MAP_SWIZZLE_128B : CU_TENSOR_MAP_SWIZZLE_64B;
  cuuint64_t gd[2] = {cols, rows}, gs[1] = {cols * 2};
  cuuint32_t bd[2] = {bc, br}, es[2] = {1, 1};
  g_enc(m, CU_TENSOR_MAP_DATA_TYPE_BFLOAT16, 2, (void*)ptr, gd, gs, bd, es, CU_TENSOR_MAP_INTERLEAVE_NONE, sw,
        CU_TENSOR_MAP_L2_PROMOTION_L2_128B, CU_TENSOR_MAP_FLOAT_OOB_FILL_NONE);
}
void map3(CUtensorMap* m, const void* ptr, uint64_t rows, uint64_t cols, uint32_t br, uint32_t bch, uint32_t bc = 64) {
  cuuint64_t gd[3] = {bc, rows, cols / bc}, gs[2] = {cols * 2, bc * 2};
  cuuint32_t bd[3] = {bc, br, bch}, es[3] = {1, 1, 1};
  g_enc(m, CU_TENSOR_MAP_DATA_TYPE_BFLOAT16, 3, (void*)ptr, gd, gs, bd, es, CU_TENSOR_MAP_INTERLEAVE_NONE, bc == 64 ? CU_TENSOR_MAP_SWIZZLE_128B : CU_TENSOR_MAP_SWIZZLE_64B,
        CU_TENSOR_MAP_L2_PROMOTION_L2_128B, CU_TENSOR_MAP_FLOAT_OOB_FILL_NONE);
}

}

extern "C" void kernel_launch(void* const* d_in, const int* in_sizes, int n_in, void* d_out, int out_size) {
  const __nv_bfloat16* x = (const __nv_bfloat16*)d_in[0];
  const __nv_bfloat16* ckv = (const __nv_bfloat16*)d_in[1];
  const __nv_bfloat16* wq = (const __nv_bfloat16*)d_in[2];
  const __nv_bfloat16* wk = (const __nv_bfloat16*)d_in[3];
  const __nv_bfloat16* wv = (const __nv_bfloat16*)d_in[4];
  const __nv_bfloat16* wo = (const __nv_bfloat16*)d_in[5];
  const __nv_bfloat16* w_r = (const __nv_bfloat16*)d_in[7];
  const __nv_bfloat16* wgate = (const __nv_bfloat16*)d_in[8];
  const __nv_bfloat16* wup = (const __nv_bfloat16*)d_in[9];
  const __nv_bfloat16* wdown = (const __nv_bfloat16*)d_in[10];
  __nv_bfloat16* out = (__nv_bfloat16*)d_out;

  if (!g_enc) {
    void* fn = nullptr;
    cudaDriverEntryPointQueryResult qr;
    cudaGetDriverEntryPoint("cuTensorMapEncodeTiled", &fn, cudaEnableDefault, &qr);
    g_enc = (EncodeFn)fn;
    cudaFuncSetAttribute(fused_kernel, cudaFuncAttributeMaxDynamicSharedMemorySize, SMEM_BYTES);
  }
  void *xn, *qkv;
  cudaGetSymbolAddress(&xn, g_xn);
  cudaGetSymbolAddress(&qkv, g_qkv);

  Params p;
  map2(&p.xn, xn, SEQ, DM, 64, 128);
  map2(&p.ckv, ckv, SEQ, DC, 64, 128);
  map3(&p.wq, wq, DM, NQ, 64, 2);
  map3(&p.wk, wk, DC, NQ, 64, 2);
  map3(&p.wv, wv, DC, NQ, 64, 2);
  map3(&p.kv, qkv, 3 * SEQ, NQ, 128, 1);
  map2(&p.ctx_ld, qkv, SEQ, NQ, 64, 128);
  map3(&p.ctx_st, qkv, SEQ, NQ, 64, 1, 32);
  map3(&p.wo, wo, NQ, DM, 64, 1);
  map3(&p.x, x, SEQ, DM, 64, 1);
  map3(&p.wd, wdown, FF, DM, 32, 8);
  map2(&p.out, out, SEQ, DM, 64, 64);
  map2(&p.wg, wgate, DM, FF, 32, 128);
  map2(&p.wu, wup, DM, FF, 32, 128);
  fused_kernel<<<128, 384, SMEM_BYTES, cudaStreamPerThread>>>(x, wq, w_r, out, p);
}
```

```cpp
#include <cuda_runtime.h>
#include <cuda_bf16.h>
#include <cuda.h>
#include <stdint.h>
#include <type_traits>

#pragma nv_diag_suppress 549
namespace {

constexpr int SEQ = 2048, DM = 1024, NH = 32, HD = 128, DC = 512, NQ = NH * HD, FF = 3584;

__device__ __align__(1024) __nv_bfloat16 g_xn[SEQ * DM];
__device__ __align__(1024) __nv_bfloat16 g_qkv[3 * SEQ * NQ];
constexpr int XR_PS = 0;
constexpr int XR_KEY = 128;
constexpr int XR_FLAG = 132;
constexpr int XR_CAND = 136;
constexpr int XR_Y = 648;
constexpr int XR_SIZE = 1104;
__device__ __align__(1024) uint4 g_xr[128 * XR_SIZE];
constexpr int C_LN = 0, C_QKV = 16, C_CTX = 32, C_NUM = 64;
__device__ unsigned g_cnt[C_NUM];

#define TL(k, i, cond) do {} while (0)
#define TL_BYTES 0
#define TL_INIT() do {} while (0)
#define TL_DUMP() do {} while (0)
#define TC(g, i) do {} while (0)
#define TS(i) do {} while (0)
#undef TCLK
#define TCLK 0

__device__ __forceinline__ uint32_t s2u(const void* p) { return (uint32_t)__cvta_generic_to_shared(p); }
__device__ __forceinline__ void mbar_init(uint32_t b, uint32_t c) { asm volatile("mbarrier.init.shared::cta.b64 [%0], %1;" ::"r"(b), "r"(c) : "memory"); }
__device__ __forceinline__ void mbar_expect(uint32_t b, uint32_t bytes) { asm volatile("mbarrier.arrive.expect_tx.shared::cta.b64 _, [%0], %1;" ::"r"(b), "r"(bytes) : "memory"); }
__device__ __forceinline__ void mbar_arrive(uint32_t b) { asm volatile("mbarrier.arrive.shared::cta.b64 _, [%0];" ::"r"(b) : "memory"); }
__device__ __forceinline__ bool mbar_test(uint32_t b, uint32_t ph) {
  uint32_t ok;
  asm volatile("{\n.reg .pred p;\nmbarrier.test_wait.parity.shared::cta.b64 p, [%1], %2;\nselp.u32 %0, 1, 0, p;\n}" : "=r"(ok) : "r"(b), "r"(ph) : "memory");
  return ok;
}
__device__ __forceinline__ void mbar_wait(uint32_t b, uint32_t ph) {
  asm volatile(
      "{\n.reg .pred p;\n.reg .u32 n;\nmov.u32 n, 0;\n"
      "LW:\nmbarrier.try_wait.parity.shared::cta.b64 p, [%0], %1, 20000;\n@p bra LD;\n"
      "add.u32 n, n, 1;\nsetp.lt.u32 p, n, 0x40000;\n@p bra LW;\ntrap;\nLD:\n}" ::"r"(b), "r"(ph) : "memory");
}
__device__ __forceinline__ void mbar_wait_c(uint32_t b, uint32_t ph) {
  asm volatile(
      "{\n.reg .pred p;\n.reg .u32 n;\nmov.u32 n, 0;\n"
      "LW:\nmbarrier.try_wait.parity.shared::cta.b64 p, [%0], %1;\n@p bra LD;\n"
      "add.u32 n, n, 1;\nsetp.lt.u32 p, n, 0x100000;\n@p bra LW;\ntrap;\nLD:\n}" ::"r"(b), "r"(ph) : "memory");
}
__device__ __forceinline__ bool mbar_try(uint32_t b, uint32_t ph) {
  uint32_t ok;
  asm volatile("{\n.reg .pred p;\nmbarrier.try_wait.parity.shared::cta.b64 p, [%1], %2;\nselp.u32 %0, 1, 0, p;\n}" : "=r"(ok) : "r"(b), "r"(ph) : "memory");
  return ok;
}
#define UNLIKELY(c) __builtin_expect(!!(c), 0)
__device__ __forceinline__ uint32_t pinned(uint32_t v) { uint32_t r; asm volatile("mov.b32 %0, %1;" : "=r"(r) : "r"(v)); return r; }
__device__ __forceinline__ bool elect_one() {
  uint32_t p;
  asm volatile("{\n.reg .pred p;\nelect.sync _|p, 0xFFFFFFFF;\nselp.u32 %0, 1, 0, p;\n}" : "=r"(p));
  return p;
}
__device__ __forceinline__ int lane_id() { int r; asm volatile("mov.u32 %0, %%laneid;" : "=r"(r)); return r; }
template <bool SLEEP = false>
__device__ __forceinline__ void spin_until_ge(const unsigned* p, unsigned target) {
  asm volatile(
      "{\n.reg .pred p, q;\n.reg .u32 n, v;\nmov.u32 n, 0;\nsetp.ne.u32 q, %2, 0;\n"
      "LW:\nld.acquire.gpu.global.u32 v, [%0];\nsetp.ge.u32 p, v, %1;\n@p bra LD;\n@q nanosleep.u32 200;\n"
      "add.u32 n, n, 1;\nsetp.lt.u32 p, n, 0x400000;\n@p bra LW;\ntrap;\nLD:\n}" ::"l"(p), "r"(target), "n"((int)SLEEP) : "memory");
}
template <int N>
__device__ __forceinline__ void poll_chunks(uint4 (&v)[N], const uint4* p, int stride) {
  uint32_t m[N];
#pragma unroll
  for (int i = 0; i < N; i++) { m[i] = ~0u; v[i] = make_uint4(0, 0, 0, 0); }
#pragma unroll 1
  for (int n = 0; n < 0x400000; n++) {
    uint32_t a = 0;
#pragma unroll
    for (int i = 0; i < N; i++)
      asm volatile("{\n.reg .pred p;\nsetp.eq.u32 p, %5, 0xFFFFFFFF;\n@p ld.relaxed.gpu.global.v4.u32 {%0,%1,%2,%3}, [%4];\n}"
                   : "+r"(v[i].x), "+r"(v[i].y), "+r"(v[i].z), "+r"(v[i].w) : "l"(p + i * stride), "r"(m[i]) : "memory");
#pragma unroll
    for (int i = 0; i < N; i++) { m[i] = max(max(v[i].x, v[i].y), max(v[i].z, v[i].w)); a = max(a, m[i]); }
    if (__all_sync(~0u, a != 0xFFFFFFFFu)) break;
  }
}
__device__ __forceinline__ void fence_async_all() { asm volatile("fence.proxy.async;" ::: "memory"); }
__device__ __forceinline__ void bar_sync(int id, int n) { asm volatile("bar.sync %0, %1;" ::"r"(id), "r"(n) : "memory"); }
__device__ __forceinline__ void bar_arrive(int id, int n) { asm volatile("bar.arrive %0, %1;" ::"r"(id), "r"(n) : "memory"); }
__device__ __forceinline__ void cluster_arrive() { asm volatile("barrier.cluster.arrive.relaxed.aligned;" ::: "memory"); }
__device__ __forceinline__ void cluster_wait() { asm volatile("barrier.cluster.wait.acquire.aligned;" ::: "memory"); }
__device__ __forceinline__ void fence_gpu() { asm volatile("fence.acq_rel.gpu;" ::: "memory"); }
__device__ __forceinline__ void red_add(unsigned* p, unsigned v) { asm volatile("red.relaxed.gpu.global.add.u32 [%0], %1;" ::"l"(p), "r"(v) : "memory"); }
__device__ __forceinline__ void prefetch_tm(const CUtensorMap* m) { asm volatile("prefetch.tensormap [%0];" ::"l"(m) : "memory"); }

constexpr uint64_t EV_N = 0x1000000000000000ull, EV_F = 0x12F0000000000000ull;
__device__ __forceinline__ void tma_ld2(uint32_t dst, const CUtensorMap* m, uint32_t bar, int c0, int c1, bool ef = false) {
  asm volatile("cp.async.bulk.tensor.2d.shared::cta.global.mbarrier::complete_tx::bytes.L2::cache_hint [%0], [%1, {%3,%4}], [%2], %5;" ::"r"(dst), "l"(m), "r"(bar), "r"(c0), "r"(c1), "l"(ef ? EV_F : EV_N) : "memory");
}
__device__ __forceinline__ void tma_ld3(uint32_t dst, const CUtensorMap* m, uint32_t bar, int c0, int c1, int c2, bool ef = false) {
  asm volatile("cp.async.bulk.tensor.3d.shared::cta.global.mbarrier::complete_tx::bytes.L2::cache_hint [%0], [%1, {%3,%4,%5}], [%2], %6;" ::"r"(dst), "l"(m), "r"(bar), "r"(c0), "r"(c1), "r"(c2), "l"(ef ? EV_F : EV_N) : "memory");
}
__device__ __forceinline__ void tma_ld3_mc(uint32_t dst, const CUtensorMap* m, uint32_t bar, int c0, int c1, int c2, uint16_t mask, bool ef = false) {
  asm volatile("cp.async.bulk.tensor.3d.shared::cluster.global.mbarrier::complete_tx::bytes.multicast::cluster.L2::cache_hint [%0], [%1, {%3,%4,%5}], [%2], %6, %7;" ::"r"(dst), "l"(m), "r"(bar), "r"(c0), "r"(c1), "r"(c2), "h"(mask), "l"(ef ? EV_F : EV_N) : "memory");
}
__device__ __forceinline__ void tma_pf3(const CUtensorMap* m, int c0, int c1, int c2) {
  asm volatile("cp.async.bulk.prefetch.tensor.3d.L2.global [%0, {%1,%2,%3}];" ::"l"(m), "r"(c0), "r"(c1), "r"(c2) : "memory");
}
__device__ __forceinline__ void l2_prefetch(const void* p, uint32_t bytes) { asm volatile("cp.async.bulk.prefetch.L2.global [%0], %1;" ::"l"(p), "r"(bytes) : "memory"); }

__device__ __forceinline__ void wg_fence() { asm volatile("wgmma.fence.sync.aligned;" ::: "memory"); }
__device__ __forceinline__ void wg_commit() { asm volatile("wgmma.commit_group.sync.aligned;" ::: "memory"); }
template <int N> __device__ __forceinline__ void wg_wait() { asm volatile("wgmma.wait_group.sync.aligned %0;" ::"n"(N) : "memory"); }
template <int N> __device__ __forceinline__ void reg_alloc() { asm volatile("setmaxnreg.inc.sync.aligned.u32 %0;" ::"n"(N)); }
template <int N> __device__ __forceinline__ void reg_dealloc() { asm volatile("setmaxnreg.dec.sync.aligned.u32 %0;" ::"n"(N)); }
template <int N> __device__ __forceinline__ void fence_regs(float* d) {
#pragma unroll
  for (int i = 0; i < N; i++) asm volatile("" : "+f"(d[i])::"memory");
}
template <int N> __device__ __forceinline__ void fence_regs(uint32_t* d) {
#pragma unroll
  for (int i = 0; i < N; i++) asm volatile("" : "+r"(d[i])::"memory");
}

__device__ __forceinline__ uint64_t mk_desc(uint32_t addr, uint32_t lbo, uint32_t sbo, uint32_t swz) {
  uint32_t lo = ((addr & 0x3FFFF) >> 4) | ((lbo >> 4) << 16);
  uint32_t hi = (sbo >> 4) | (swz << 30);
  return ((uint64_t)hi << 32) | lo;
}
__device__ __forceinline__ uint64_t desc_add(uint64_t d, uint32_t bytes) {
  uint32_t lo = (uint32_t)d + (bytes >> 4);
  return (d & 0xFFFFFFFF00000000ull) | lo;
}

#define R8(b) "+f"(d[b + 0]), "+f"(d[b + 1]), "+f"(d[b + 2]), "+f"(d[b + 3]), "+f"(d[b + 4]), "+f"(d[b + 5]), "+f"(d[b + 6]), "+f"(d[b + 7])
#define REGS32 "%0,%1,%2,%3,%4,%5,%6,%7,%8,%9,%10,%11,%12,%13,%14,%15,%16,%17,%18,%19,%20,%21,%22,%23,%24,%25,%26,%27,%28,%29,%30,%31"
#define REGS64 REGS32 ",%32,%33,%34,%35,%36,%37,%38,%39,%40,%41,%42,%43,%44,%45,%46,%47,%48,%49,%50,%51,%52,%53,%54,%55,%56,%57,%58,%59,%60,%61,%62,%63"
#define REGS128 REGS64 ",%64,%65,%66,%67,%68,%69,%70,%71,%72,%73,%74,%75,%76,%77,%78,%79,%80,%81,%82,%83,%84,%85,%86,%87,%88,%89,%90,%91,%92,%93,%94,%95," \
               "%96,%97,%98,%99,%100,%101,%102,%103,%104,%105,%106,%107,%108,%109,%110,%111,%112,%113,%114,%115,%116,%117,%118,%119,%120,%121,%122,%123,%124,%125,%126,%127"

template <int TB>
__device__ __forceinline__ void mma_n256_ss(float (&d)[128], uint64_t a, uint64_t b, int acc) {
  asm volatile("{\n.reg .pred p;\nsetp.ne.b32 p, %130, 0;\n"
               "wgmma.mma_async.sync.aligned.m64n256k16.f32.bf16.bf16 {" REGS128 "}, %128, %129, p, 1, 1, 0, %131;\n}\n"
               : R8(0), R8(8), R8(16), R8(24), R8(32), R8(40), R8(48), R8(56), R8(64), R8(72), R8(80), R8(88), R8(96), R8(104), R8(112), R8(120)
               : "l"(a), "l"(b), "r"(acc), "n"(TB));
}
template <int TB>
__device__ __forceinline__ void mma_n128_ss(float* d, uint64_t a, uint64_t b, int acc) {
  asm volatile("{\n.reg .pred p;\nsetp.ne.b32 p, %66, 0;\n"
               "wgmma.mma_async.sync.aligned.m64n128k16.f32.bf16.bf16 {" REGS64 "}, %64, %65, p, 1, 1, 0, %67;\n}\n"
               : R8(0), R8(8), R8(16), R8(24), R8(32), R8(40), R8(48), R8(56)
               : "l"(a), "l"(b), "r"(acc), "n"(TB));
}
template <int TB>
__device__ __forceinline__ void mma_n128_rs(float* d, const uint32_t* a, uint64_t b, int acc) {
  asm volatile("{\n.reg .pred p;\nsetp.ne.b32 p, %69, 0;\n"
               "wgmma.mma_async.sync.aligned.m64n128k16.f32.bf16.bf16 {" REGS64 "}, {%64,%65,%66,%67}, %68, p, 1, 1, %70;\n}\n"
               : R8(0), R8(8), R8(16), R8(24), R8(32), R8(40), R8(48), R8(56)
               : "r"(a[0]), "r"(a[1]), "r"(a[2]), "r"(a[3]), "l"(b), "r"(acc), "n"(TB));
}
__device__ __forceinline__ void mma_n64_rs(float* d, const uint32_t* a, uint64_t b, int acc) {
  asm volatile("{\n.reg .pred p;\nsetp.ne.b32 p, %37, 0;\n"
               "wgmma.mma_async.sync.aligned.m64n64k16.f32.bf16.bf16 {" REGS32 "}, {%32,%33,%34,%35}, %36, p, 1, 1, 0;\n}\n"
               : R8(0), R8(8), R8(16), R8(24)
               : "r"(a[0]), "r"(a[1]), "r"(a[2]), "r"(a[3]), "l"(b), "r"(acc));
}
#define W8(b) "=f"(d[b + 0]), "=f"(d[b + 1]), "=f"(d[b + 2]), "=f"(d[b + 3]), "=f"(d[b + 4]), "=f"(d[b + 5]), "=f"(d[b + 6]), "=f"(d[b + 7])
__device__ __forceinline__ void mma_n128_rs0(float* d, const uint32_t* a, uint64_t b) {
  asm volatile("wgmma.mma_async.sync.aligned.m64n128k16.f32.bf16.bf16 {" REGS64 "}, {%64,%65,%66,%67}, %68, 0, 1, 1, 0;\n"
               : W8(0), W8(8), W8(16), W8(24), W8(32), W8(40), W8(48), W8(56)
               : "r"(a[0]), "r"(a[1]), "r"(a[2]), "r"(a[3]), "l"(b));
}
__device__ __forceinline__ void mma_n64_rs0(float* d, const uint32_t* a, uint64_t b) {
  asm volatile("wgmma.mma_async.sync.aligned.m64n64k16.f32.bf16.bf16 {" REGS32 "}, {%32,%33,%34,%35}, %36, 0, 1, 1, 0;\n"
               : W8(0), W8(8), W8(16), W8(24)
               : "r"(a[0]), "r"(a[1]), "r"(a[2]), "r"(a[3]), "l"(b));
}
__device__ __forceinline__ uint32_t pack_bf16(float lo, float hi) {
  uint32_t r;
  asm("cvt.rn.bf16x2.f32 %0, %1, %2;" : "=r"(r) : "f"(hi), "f"(lo));
  return r;
}
__device__ __forceinline__ float bf_lo(uint32_t v) { return __uint_as_float(v << 16); }
__device__ __forceinline__ float bf_hi(uint32_t v) { return __uint_as_float(v & 0xFFFF0000u); }
__device__ __forceinline__ float bf_round(float v) { return bf_lo(pack_bf16(v, v)); }
__device__ __forceinline__ void stsm4(uint32_t addr, uint32_t r0, uint32_t r1, uint32_t r2, uint32_t r3) {
  asm volatile("stmatrix.sync.aligned.m8n8.x4.shared.b16 [%0], {%1,%2,%3,%4};" ::"r"(addr), "r"(r0), "r"(r1), "r"(r2), "r"(r3) : "memory");
}
__device__ __forceinline__ uint4 lds128(uint32_t addr) {
  uint4 v;
  asm volatile("ld.shared.v4.u32 {%0,%1,%2,%3}, [%4];" : "=r"(v.x), "=r"(v.y), "=r"(v.z), "=r"(v.w) : "r"(addr));
  return v;
}
__device__ __forceinline__ float ex2(float x) {
  float y;
  asm("ex2.approx.ftz.f32 %0, %1;" : "=f"(y) : "f"(x));
  return y;
}
__device__ __forceinline__ void pin_order(float v, uint32_t dummy) {
  asm volatile("{\n.reg .pred p;\nsetp.eq.b32 p, %0, 0xFFFFFFFF;\n@p st.shared.b32 [%1], %0;\n}" ::"r"(__float_as_uint(v)), "r"(dummy) : "memory");
}
__device__ __forceinline__ float sigmoid(float x) {
  float y;
  asm("rcp.approx.ftz.f32 %0, %1;" : "=f"(y) : "f"(1.f + ex2(x * -1.4426950408889634f)));
  return y;
}
__device__ __forceinline__ void sched_fence(uint32_t dummy) {
  asm volatile("{\n.reg .pred p;\n.reg .u32 c;\nsetp.eq.b32 p, %0, 0xFFFFFFFF;\nmov.u32 c, %%clock;\n@p st.shared.b32 [%0], c;\n}" ::"r"(dummy) : "memory");
}
__device__ __forceinline__ void idle(int n) {
  asm volatile("{\n.reg .pred p;\n.reg .u32 a, b;\nmov.u32 a, %%clock;\nLI:\nmov.u32 b, %%clock;\nsub.u32 b, b, a;\nsetp.lt.u32 p, b, %0;\n@p bra LI;\n}" ::"r"(n) : "memory");
}
__device__ __forceinline__ void stage_store_128(uint32_t base, int lane, const uint32_t* pk) {
  const int row = (lane & 7) + ((lane >> 3) & 1) * 8;
  const uint32_t rb = base + row * 128;
  const int hi = lane >> 4;
#pragma unroll
  for (int j = 0; j < 8; j++) {
    const int chunk = 2 * j + hi;
    const uint32_t a = rb + (j >> 2) * 8192 + (((chunk & 7) ^ (lane & 7)) << 4);
    stsm4(a, pk[4 * j + 0], pk[4 * j + 1], pk[4 * j + 2], pk[4 * j + 3]);
  }
}
__device__ __forceinline__ void ln_round(float mean, float var, float& m_bf, float& inv_s) {
  const uint32_t mv = pack_bf16(mean, var);
  m_bf = bf_lo(mv);
  float sq, rc;
  asm("sqrt.approx.ftz.f32 %0, %1;" : "=f"(sq) : "f"(bf_round(bf_hi(mv) + 1e-5f)));
  asm("rcp.approx.ftz.f32 %0, %1;" : "=f"(rc) : "f"(bf_round(sq)));
  inv_s = rc;
}
__device__ __forceinline__ uint32_t hadd2_bf(uint32_t a, uint32_t b) {
  uint32_t r;
  asm("add.rn.bf16x2 %0, %1, %2;" : "=r"(r) : "r"(a), "r"(b));
  return r;
}
__device__ __forceinline__ uint32_t ln_apply(uint32_t h, uint32_t nm2, float inv_s) {
  const uint32_t d = hadd2_bf(h, nm2);
  return pack_bf16(bf_lo(d) * inv_s, bf_hi(d) * inv_s);
}
__device__ __forceinline__ void ldsm4(uint32_t* r, uint32_t addr) {
  asm volatile("ldmatrix.sync.aligned.m8n8.x4.shared.b16 {%0,%1,%2,%3}, [%4];" : "=r"(r[0]), "=r"(r[1]), "=r"(r[2]), "=r"(r[3]) : "r"(addr) : "memory");
}
__device__ __forceinline__ void mma16816(float* d, uint32_t a0, uint32_t a1, uint32_t a2, uint32_t a3, uint32_t b0, uint32_t b1) {
  asm volatile("mma.sync.aligned.m16n8k16.row.col.f32.bf16.bf16.f32 {%0,%1,%2,%3}, {%4,%5,%6,%7}, {%8,%9}, {%0,%1,%2,%3};"
               : "+f"(d[0]), "+f"(d[1]), "+f"(d[2]), "+f"(d[3]) : "r"(a0), "r"(a1), "r"(a2), "r"(a3), "r"(b0), "r"(b1));
}

template <class F>
__device__ __forceinline__ void unroll8(F f) {
  f(std::integral_constant<int, 0>{}); f(std::integral_constant<int, 1>{}); f(std::integral_constant<int, 2>{}); f(std::integral_constant<int, 3>{});
  f(std::integral_constant<int, 4>{}); f(std::integral_constant<int, 5>{}); f(std::integral_constant<int, 6>{}); f(std::integral_constant<int, 7>{});
}

constexpr float AT_C = 0.08838834764831845f * 1.4426950408889634f;
constexpr float AT_LO = 0x1p-40f, AT_HI = 0x1p40f;
constexpr int AT_R1 = 48;
template <int I0, int I1>
__device__ __forceinline__ void at_exp(float* S) {
#pragma unroll
  for (int i = I0; i < I1; i++) asm volatile("ex2.approx.ftz.f32 %0, %0;" : "+f"(S[i]));
}
template <int I0, int I1>
__device__ __forceinline__ void at_fin(const float* S, uint32_t* P) {
#pragma unroll
  for (int i = I0; i < I1; i += 4) {
    P[i / 2] = pack_bf16(S[i], S[i + 1]); P[i / 2 + 1] = pack_bf16(S[i + 2], S[i + 3]);
  }
}
__device__ __forceinline__ void at_sum(const uint32_t* P, bool half, float& l0, float& l1) {
  uint32_t u[4];
#pragma unroll
  for (int r = 0; r < 4; r++) {
    const uint32_t* q = P + (r >> 1) * 16 + (r & 1);
    u[r] = hadd2_bf(hadd2_bf(hadd2_bf(q[0], q[2]), hadd2_bf(q[4], q[6])), hadd2_bf(hadd2_bf(q[8], q[10]), hadd2_bf(q[12], q[14])));
  }
  u[0] = hadd2_bf(u[0], half ? 0u : u[2]);
  u[1] = hadd2_bf(u[1], half ? 0u : u[3]);
  l0 += bf_lo(u[0]) + bf_hi(u[0]);
  l1 += bf_lo(u[1]) + bf_hi(u[1]);
}
template <int j>
__device__ __forceinline__ void at_mask1(float* S, int d) {
  float dummy0 = 0.f, dummy1 = 0.f;
  float& lo0 = j < 7 ? S[4 * (j < 7 ? j + 1 : j) + 2] : dummy0;
  float& lo1 = j < 7 ? S[4 * (j < 7 ? j + 1 : j) + 3] : dummy1;
  asm("{\n.reg .pred p, q;\nsetp.lt.s32 p, %4, %5;\nsetp.le.s32 q, %4, %5;\n"
      "@p add.f32 %0, %0, 0fFF800000;\n@q add.f32 %1, %1, 0fFF800000;\n@p add.f32 %2, %2, 0fFF800000;\n@q add.f32 %3, %3, 0fFF800000;\n}"
      : "+f"(S[4 * j]), "+f"(S[4 * j + 1]), "+f"(lo0), "+f"(lo1) : "r"(d), "r"(8 * j));
}
__device__ __forceinline__ void at_mask(float* S, int r, int lane) {
  unroll8([&](auto jc) { at_mask1<decltype(jc)::value>(S, r + (lane >> 2) - (lane & 3) * 2); });
}
__device__ __forceinline__ uint32_t ldg32(const __nv_bfloat16* p) { return __ldcg(reinterpret_cast<const uint32_t*>(p)); }
__device__ __forceinline__ uint32_t ldg16x2(const __nv_bfloat16* p, int stride) {
  return (uint32_t)__ldcg(reinterpret_cast<const unsigned short*>(p)) | ((uint32_t)__ldcg(reinterpret_cast<const unsigned short*>(p + stride)) << 16);
}
__device__ __forceinline__ void slow_tile(float* O, uint32_t* Q, float& l0, float& l1, const __nv_bfloat16* wq, int row0, int head, int lane, uint32_t dummy) {
  const int r = lane >> 2, q = lane & 3;
#pragma unroll
  for (int i = 0; i < 64; i++) O[i] = 0.f;
  {
    const __nv_bfloat16* xa = g_xn + (size_t)(row0 + r) * DM + 2 * q;
    const __nv_bfloat16* wb = wq + (size_t)(2 * q) * NQ + head * HD + (r >> 1) * 8 + (r & 1);
#pragma unroll 1
    for (int k = 0; k < DM; k += 16) {
      const uint32_t a0 = ldg32(xa + k), a1 = ldg32(xa + k + 8 * DM), a2 = ldg32(xa + k + 8), a3 = ldg32(xa + k + 8 * DM + 8);
#pragma unroll
      for (int j = 0; j < 16; j++) {
        const __nv_bfloat16* wp = wb + (size_t)k * NQ + (j >> 2) * 32 + (j & 3) * 2;
        mma16816(O + 4 * j, a0, a1, a2, a3, ldg16x2(wp, NQ), ldg16x2(wp + 8 * NQ, NQ));
        if (j == 7) sched_fence(dummy);
      }
    }
  }
#pragma unroll
  for (int i = 0; i < 32; i++) Q[i] = pack_bf16(O[2 * i], O[2 * i + 1]);
#pragma unroll
  for (int i = 0; i < 64; i++) O[i] = 0.f;
  float m0 = -INFINITY, m1 = -INFINITY;
  l0 = l1 = 0.f;
#pragma unroll 1
  for (int kv = 0; kv <= row0; kv += 16) {
    float s[8] = {0.f, 0.f, 0.f, 0.f, 0.f, 0.f, 0.f, 0.f};
    const __nv_bfloat16* kp = g_qkv + (size_t)(SEQ + kv + r) * NQ + head * HD + 2 * q;
#pragma unroll
    for (int k = 0; k < 8; k++) {
      mma16816(s, Q[4 * k], Q[4 * k + 1], Q[4 * k + 2], Q[4 * k + 3], ldg32(kp + 16 * k), ldg32(kp + 16 * k + 8));
      mma16816(s + 4, Q[4 * k], Q[4 * k + 1], Q[4 * k + 2], Q[4 * k + 3], ldg32(kp + 8 * NQ + 16 * k), ldg32(kp + 8 * NQ + 16 * k + 8));
    }
#pragma unroll
    for (int i = 0; i < 8; i++)
      if (kv + (i >> 2) * 8 + 2 * q + (i & 1) > row0 + r + (i & 2) * 4) s[i] = -INFINITY;
    float a = fmaxf(fmaxf(fmaxf(s[0], s[1]), fmaxf(s[4], s[5])), m0), b = fmaxf(fmaxf(fmaxf(s[2], s[3]), fmaxf(s[6], s[7])), m1);
    a = fmaxf(a, __shfl_xor_sync(~0u, a, 1)); b = fmaxf(b, __shfl_xor_sync(~0u, b, 1));
    a = fmaxf(a, __shfl_xor_sync(~0u, a, 2)); b = fmaxf(b, __shfl_xor_sync(~0u, b, 2));
    const float c0 = ex2(m0 - a), c1 = ex2(m1 - b);
    m0 = a; m1 = b;
#pragma unroll
    for (int i = 0; i < 8; i++) s[i] = ex2(s[i] - ((i & 2) ? b : a));
    l0 = l0 * c0 + (s[0] + s[1]) + (s[4] + s[5]);
    l1 = l1 * c1 + (s[2] + s[3]) + (s[6] + s[7]);
    sched_fence(dummy);
    const uint32_t p0 = pack_bf16(s[0], s[1]), p1 = pack_bf16(s[2], s[3]), p2 = pack_bf16(s[4], s[5]), p3 = pack_bf16(s[6], s[7]);
    const __nv_bfloat16* vp = g_qkv + (size_t)(2 * SEQ + kv + 2 * q) * NQ + head * HD + r;
#pragma unroll
    for (int j = 0; j < 16; j++) {
      O[4 * j] *= c0; O[4 * j + 1] *= c0; O[4 * j + 2] *= c1; O[4 * j + 3] *= c1;
      mma16816(O + 4 * j, p0, p1, p2, p3, ldg16x2(vp + 8 * j, NQ), ldg16x2(vp + 8 * NQ + 8 * j, NQ));
      if (j == 7) sched_fence(dummy);
    }
  }
}

constexpr int P1_STAGE = 49152;
constexpr int SLOT = 32768;
constexpr int OFF_R3 = 0;
constexpr int OFF_BAR = 229376;
constexpr int OFF_MISC = OFF_BAR + 8 * 58;
constexpr int SMEM_BYTES = OFF_MISC + 2080 + TL_BYTES;
enum : int {
  B_FULL1 = 0, B_KF = 4, B_VF = 6, B_FULL3 = 8, B_XF = 14, B_LN = 15, B_DEP = 16, B_OUT2 = 22, B_FIN = 23, B_SET2 = 25, B_QP = 26, B_WF2 = 29,
  B_WF = 30, B_WR = 31,
  B_XE = 33, B_PUB = 34, B_OUT = 40, B_OUT3 = 41,
  B_EMPTY1 = 42, B_KE = 46, B_VE = 48, B_EMPTY3 = 50, B_WE = 56, B_NUM = 57
};
constexpr int OFF_STG = SLOT, SL_SCR = 2;
constexpr int PRE = 3;
constexpr int LN_PF = 5, LN_PFN = 2, LN_LD = 4;
constexpr int WQ_0 = 18, WQ_D = 2;
constexpr int KV_PF = 10, W_G0 = 23;
constexpr int X_KB = 20, G_KB = 35;
constexpr int SL_NS = 600, SET_NS = 50;
constexpr int OUT_CLK = 500, Y_CLK = 400;
struct Params {
  CUtensorMap xn, ckv, wq, wk, wv, kv, ctx_ld, ctx_st, wo, x, wd, wg, wu, out;
};

__global__ void __cluster_dims__(2, 1, 1) __launch_bounds__(384, 1)
fused_kernel(const __nv_bfloat16* __restrict__ x, const __nv_bfloat16* __restrict__ wq, const __nv_bfloat16* __restrict__ w_r,
             __nv_bfloat16* __restrict__ out, const __grid_constant__ Params p) {
  extern __shared__ __align__(1024) uint8_t sp[];
  const uint32_t sb = s2u(sp);
  const uint32_t bar = sb + OFF_BAR;
  auto B = [&](int i) { return bar + 8 * i; };
  const int tid = threadIdx.x, warp = __shfl_sync(~0u, tid >> 5, 0), wg = warp >> 2, lane = tid & 31;
  const int cta = blockIdx.x, rank = cta & 1, cl = cta >> 1;
  const int mp = cl < 4 ? 1 : (cl < 36 ? (cl & 7) : (0x3207654 >> (4 * ((cl - 36) % 7))) & 7);
  const int gq = cl < 4 ? 4 + cl : (cl < 36 ? (cl - 4) >> 3 : 4 + (cl - 36) / 7);
  const int mt = 2 * mp + rank;
  const int ti = (gq & 3) * 2 + rank, hh = mp * 2 + (gq >> 2);
  const int rid = mt * 8 + gq;
  const int fid = mt * 7 + gq - 1;
  const bool ffn = gq > 0;
  uint4* const xr = g_xr + rid * XR_SIZE;
  TL_INIT();
  TL(0, 0, tid == 128);
  if (warp == 0) {
    if (elect_one()) {
#pragma unroll
      for (int kb = 0; kb < PRE; kb++) mbar_init(B(B_FULL1 + kb), 1);
      asm volatile("fence.mbarrier_init.release.cluster;" ::: "memory");
    }
    __syncwarp();
    cluster_arrive();
    if (elect_one()) {
#pragma unroll
      for (int kb = 0; kb < PRE; kb++) {
        mbar_expect(B(B_FULL1 + kb), P1_STAGE);
        tma_ld2(sb + kb * P1_STAGE, &p.ckv, B(B_FULL1 + kb), kb * 64, mt * 128);
        tma_ld3(sb + kb * P1_STAGE + 16384 + rank * 16384, &p.wk, B(B_FULL1 + kb), 0, kb * 64, (gq + 8) * 4 + rank * 2);
        tma_ld3(sb + kb * P1_STAGE + 32768 - rank * 16384, &p.wk, B(B_FULL1 + kb), 0, kb * 64, (gq + 8) * 4 + 2 - rank * 2);
      }
    }
  } else if (elect_one()) {
#pragma unroll 1
    for (int i = PRE + warp - 1; i < B_NUM; i += 11)
      mbar_init(B(i), i >= B_EMPTY1 ? 16 : (i >= B_XE ? 8 : (i >= B_WF ? 2 : 1)));
    asm volatile("fence.mbarrier_init.release.cluster;" ::: "memory");
  }
  __syncwarp();
  if (warp) cluster_arrive();
  if (wg == 0) {
    reg_dealloc<40>();
    if (warp == 1 && elect_one()) {
      if (mt >= 2 * PRE) tma_pf3(&p.wk, 0, mp * 64, (gq + 8) * 4 + rank * 2);
      if (gq >= PRE) asm volatile("cp.async.bulk.prefetch.tensor.2d.L2.global [%0, {%1,%2}];" ::"l"(&p.ckv), "r"(gq * 64), "r"(mt * 128) : "memory");
    } else if (warp == 2 && elect_one()) {
      prefetch_tm(&p.wv); prefetch_tm(&p.wq); prefetch_tm(&p.xn);
    }
    __syncwarp();
    cluster_wait();
    if (warp == 0) {
      int st = PRE; uint32_t ph = 1;
#pragma unroll 1
      for (int t = 0; t < 6; t++) {
        const CUtensorMap* ma = t >= 4 ? &p.xn : &p.ckv;
        const CUtensorMap* mb = t >= 4 ? &p.wq : ((t & 1) ? &p.wv : &p.wk);
        const int nk = t >= 4 ? 16 : 8;
        const int row = (t < 4 ? mt : (t == 4 ? 15 - ti : ti)) * 128;
        const int col = t < 4 ? (gq + ((t >> 1) ^ 1) * 8) * 4 + rank * 2 : (hh + rank * 16) * 2;
        if (t >= 4) mbar_wait(B(B_DEP + t - 4), 0);
#pragma unroll 1
        for (int kb = t ? 0 : PRE; kb < nk; kb++) {
          const uint32_t d = sb + st * P1_STAGE, fb = B(B_FULL1 + st);
          const int n = t * 8 + kb;
          mbar_wait_c(B(B_EMPTY1 + st), ph);
          if (elect_one()) {
            const bool la = t == 0 || t >= 4 || (kb & 1);
            mbar_expect(fb, la ? P1_STAGE : 32768);
            if (la) tma_ld2(t == 0 && (kb & 5) == 4 ? sb + 6 * SLOT + (kb & 2) * 8192 : d, ma, fb, kb * 64, row);
            tma_ld3_mc(d + 16384 + rank * 16384, mb, fb, 0, kb * 64, col, 3);
          }
          if (t < 5 && elect_one()) {
            if (n >= LN_PF && n < LN_PF + LN_PFN) l2_prefetch(x + (size_t)cta * 16 * DM + (n - LN_PF) * (16 * DM / LN_PFN), 32768 / LN_PFN);
            if (n == LN_LD) mbar_arrive(B(B_LN));
            if (t < 3 && kb == (t ? 0 : 4)) tma_pf3((t & 1) ? &p.wk : &p.wv, 0, mp * 64, (gq + (((t + 1) >> 1) ^ 1) * 8) * 4 + rank * 2);
            if (n >= WQ_0 && n < WQ_0 + 4 * WQ_D && (n - WQ_0) % WQ_D == 0) tma_pf3(&p.wq, 0, ((n - WQ_0) / WQ_D * 4 + (gq & 3)) * 64, (hh + rank * 16) * 2);
          }
          if (++st == 4) { st = 0; ph ^= 1; }
        }
      }
      if (elect_one()) { prefetch_tm(&p.kv); prefetch_tm(&p.ctx_ld); prefetch_tm(&p.wo); prefetch_tm(&p.wg); prefetch_tm(&p.wu); }
      auto load_kv = [&](int g, int isv) {
        const int h2 = g >= 17, sx = g - 17 * h2, n1 = h2 ? ti + 1 : 16 - ti;
        const int row = (1 + isv) * SEQ + (sx < n1 ? sx : 16 - sx) * 128, col = (hh + 16 * h2) * 2;
        const uint32_t d = sb + (isv ? 2 + 2 * (g & 1) : (g & 1)) * SLOT, fb = B(B_KF + 2 * isv + (g & 1));
        const bool ef = sx >= n1 || sx >= 8;
        const bool shared = sx != (h2 ? (ti & 6) + 1 : 15 - (ti & 6));
        const int n3 = g - KV_PF;
        const int pb = ti >= 6 && n3 >= 0 && n3 < 16 ? ((n3 & 1) || !n3 ? (n3 + 1) >> 1 : 16 - (n3 >> 1)) : -1;
        mbar_wait_c(g < 2 ? B(B_EMPTY1 + (isv ? 1 + 2 * g : g)) : B(B_KE + 2 * isv + (g & 1)), g < 2 ? 1 : ((g >> 1) & 1) ^ 1);
        if (elect_one()) {
          mbar_expect(fb, SLOT);
          if (shared) {
            tma_ld3_mc(d + rank * 16384, &p.kv, fb, 0, row, col + rank, 3, ef);
          } else {
            tma_ld3(d, &p.kv, fb, 0, row, col, ef);
            tma_ld3(d + 16384, &p.kv, fb, 0, row, col + 1, ef);
          }
          if (pb >= 0) tma_pf3(&p.kv, 0, (1 + isv) * SEQ + pb * 128, (hh + 16) * 2 + rank);
        }
      };
      int nw = ffn ? 0 : 12;
      auto load_w = [&]() {
        const int c = nw < 8 ? (nw >> 2) + (nw & 2) : nw >> 1;
        if (elect_one()) {
          if (!(nw & 3)) mbar_expect(B(B_WF - (nw >> 3)), 32768);
          tma_ld2(sb + (c < 2 ? 3 : 4) * SLOT + c * 16384 + (nw & 1) * 8192, (nw & 1) ? &p.wg : &p.wu, B(B_WF - (nw >> 3)), fid * 32, c * 128, true);
        }
        nw++;
      };
#pragma unroll 1
      for (int g = 0; g < 34; g++) {
        if (g == 0 || g == KV_PF) mbar_wait(B(B_DEP + 2 + (g > 0)), 0);
        load_kv(g, 0);
        if (g > 0) load_kv(g - 1, 1);
        if (g >= W_G0 && nw < 12 && __all_sync(~0u, mbar_test(B(B_QP + (nw >> 2)), 0))) load_w();
      }
      load_kv(33, 1);
#pragma unroll 1
      while (nw < 12) { mbar_wait(B(B_QP + (nw >> 2)), 0); load_w(); }
      if (elect_one()) { prefetch_tm(&p.wd); prefetch_tm(&p.x); prefetch_tm(&p.out); }
      auto load3 = [&](int kb, int sl) {
        if (elect_one()) {
          mbar_expect(B(B_FULL3 + sl), SLOT);
          tma_ld2(sb + OFF_R3 + sl * SLOT, &p.ctx_ld, B(B_FULL3 + sl), kb * 64, mt * 128, true);
          tma_ld3_mc(sb + OFF_R3 + sl * SLOT + 16384 + rank * 8192, &p.wo, B(B_FULL3 + sl), 0, kb * 64, gq * 2 + rank, 3);
        }
      };
      mbar_wait(B(B_DEP + 4), 0);
#pragma unroll
      for (int kb = 0; kb < 5; kb++) {
        mbar_wait_c(B(kb == 3 ? B_WE : (kb == 4 ? B_VE + 1 : B_KE + kb)), 0);
        load3(kb, kb);
      }
      if (elect_one()) mbar_arrive(B(B_FULL3 + 5));
#pragma unroll 1
      for (int r = 1; r < 11; r++) {
#pragma unroll
        for (int j = 0; j < 6; j++) {
          if (j == 5 && r == 10) break;
          if (j == 3 && r == 5) mbar_wait(B(B_DEP + 5), 0);
          mbar_wait_c(B(B_EMPTY3 + j), ~r & 1);
          load3(r * 6 + j - 1, j);
          if (j == 5 && r == 9 && elect_one()) l2_prefetch(xr, XR_CAND * 16);
        }
      }
      if (ffn) {
#pragma unroll
        for (int j = 1; j >= 0; j--) {
          mbar_wait(B(B_EMPTY3 + 5 * j), j);
          if (elect_one()) {
            mbar_expect(B(B_FULL3 + 5 * j), SLOT);
            tma_ld3(sb + OFF_R3 + 5 * j * SLOT, &p.wd, B(B_FULL3 + 5 * j), 0, fid * 32, 8 * j, true);
          }
        }
      }
    } else {
      if (warp >= 2) {
#pragma unroll 1
        for (int i = tid - 64; i < XR_CAND; i += 64) xr[i] = make_uint4(~0u, ~0u, ~0u, ~0u);
        if (warp == 2) { __syncwarp(); if (lane == 0) mbar_arrive(B(B_WR)); }
      }
      if (warp == 3) {
        float ws = 0.f;
#pragma unroll
        for (int j = 0; j < 4; j++) {
          const uint4 q = __ldg(reinterpret_cast<const uint4*>(w_r) + j * 32 + lane);
          ws += bf_lo(q.x) + bf_hi(q.x) + bf_lo(q.y) + bf_hi(q.y) + bf_lo(q.z) + bf_hi(q.z) + bf_lo(q.w) + bf_hi(q.w);
        }
#pragma unroll
        for (int o = 16; o; o >>= 1) ws += __shfl_xor_sync(~0u, ws, o);
        uint2* tab = reinterpret_cast<uint2*>(sp + OFF_MISC + 512);
        tab[lane] = make_uint2(0x3F803F80u, 0x3F803F80u);
        tab[32 + lane] = __ldg(reinterpret_cast<const uint2*>(w_r + gq * 128) + lane);
        if (lane == 0) *reinterpret_cast<float*>(sp + OFF_MISC + 1024) = ws;
        __syncwarp();
        if (lane == 0) mbar_arrive(B(B_WR));
      }
      if (tid == 32) TS(0);
      mbar_wait(B(B_LN), 0);
      const uint4* src = reinterpret_cast<const uint4*>(x + (size_t)(cta * 16 + warp - 1) * DM) + lane;
      uint4* dst = reinterpret_cast<uint4*>(g_xn + (size_t)(cta * 16 + warp - 1) * DM) + lane;
      uint4 v[4];
#pragma unroll
      for (int j = 0; j < 4; j++) v[j] = __ldcs(src + j * 32);
#pragma unroll 1
      for (int r = warp - 1; r < 16; r += 3) {
        float a0 = 0.f, a1 = 0.f, b0 = 0.f, b1 = 0.f;
#pragma unroll
        for (int j = 0; j < 4; j++) {
          const uint32_t u[4] = {v[j].x, v[j].y, v[j].z, v[j].w};
#pragma unroll
          for (int i = 0; i < 4; i++) { const float a = bf_lo(u[i]), b = bf_hi(u[i]); a0 += a; a1 += b; b0 = fmaf(a, a, b0); b1 = fmaf(b, b, b1); }
        }
        a0 += a1; b0 += b1;
#pragma unroll
        for (int o = 16; o; o >>= 1) { a0 += __shfl_xor_sync(~0u, a0, o); b0 += __shfl_xor_sync(~0u, b0, o); }
        const float mean = a0 * (1.f / DM);
        float mb, inv;
        ln_round(mean, fmaxf(fmaf(b0, 1.f / DM, -mean * mean), 0.f), mb, inv);
        inv *= AT_C;
        const uint32_t nm2 = pack_bf16(-mb, -mb);
        src += 384;
#pragma unroll
        for (int j = 0; j < 4; j++) {
          dst[j * 32] = make_uint4(ln_apply(v[j].x, nm2, inv), ln_apply(v[j].y, nm2, inv), ln_apply(v[j].z, nm2, inv), ln_apply(v[j].w, nm2, inv));
          sched_fence(sb + lane);
          if (r < 13) v[j] = __ldcs(src + j * 32);
        }
        dst += 384;
      }
      __syncwarp();
      if (lane == 0) {
        fence_gpu();
        red_add(&g_cnt[C_LN + (cta >> 3)], 1);
      }
      TL(3, warp, lane == 0);
      __syncwarp();
      cluster_arrive();
      if (warp == 3) {
        if (lane == 0) {
#pragma unroll 1
          for (int i = 0; i < 6; i++) {
            const int c = i < 2 ? C_LN + (i ? ti : 15 - ti) : (i < 4 ? C_QKV + (i - 2) * 8 + mp : C_CTX + (i - 4) * 16 + mt);
            spin_until_ge<true>(&g_cnt[c], i < 2 ? 24 : 16);
            fence_async_all();
            mbar_arrive(B(B_DEP + i));
            TL(3, 4 + i, true);
          }
        }
      } else if (warp == 1 && elect_one()) {
        mbar_wait(B(B_WR), 0);
#pragma unroll 1
        for (int i = 0; i < 6; i++) {
          const int c = i < 2 ? C_QKV + gq + (i ^ 1) * 8 : C_CTX + (i >> 2) * 16 + ((i == 3 || i == 4) ? ti : 15 - ti);
          mbar_wait(B(B_PUB + i), 0);
          if (i >= 2 && i < 5) {
            asm volatile("fence.proxy.async.shared::cta;" ::: "memory");
#pragma unroll 1
            for (int n = 0; n < 8; n++) {
              const int h = n >> 2, a = n & 3;
              asm volatile("cp.async.bulk.tensor.3d.global.shared::cta.bulk_group [%0, {%2,%3,%4}], [%1];" ::"l"(&p.ctx_st),
                           "r"(sb + (i == 4 ? 6 * SLOT + h * 16384 : (3 + 2 * h) * SLOT + (i - 2) * 16384) + a * 4096),
                           "r"(0), "r"((i == 2 ? 15 - ti : ti) * 128 + h * 64), "r"((hh + (i >> 2) * 16) * 4 + a) : "memory");
              asm volatile("cp.async.bulk.commit_group;\ncp.async.bulk.wait_group.read 0;" ::: "memory");
            }
            mbar_arrive(B(B_QP + i - 2));
            asm volatile("cp.async.bulk.wait_group 0;" ::: "memory");
          }
          fence_gpu();
          red_add(&g_cnt[c], 1);
          TS(1 + i);
        }
      }
      if (warp == 2) {
#pragma unroll 1
        for (int n = 0; n < 8; n++) {
          if (!(n & 3)) mbar_wait(B(B_XE), n >> 2);
          if ((n < 4 || ffn) && elect_one()) {
            const uint32_t fb = B(n < 4 ? B_XF : B_WF2), d = sb + 6 * SLOT + (n & 3) * 8192;
            if (!(n & 3)) mbar_expect(fb, 32768);
            if (n < 4) tma_ld3(d, &p.x, fb, 0, mt * 128 + (n >> 1) * 64, gq * 2 + (n & 1), true);
            else tma_ld2(d, (n & 1) ? &p.wg : &p.wu, fb, fid * 32, (4 + (n >> 1)) * 128, true);
          }
          __nanosleep(SL_NS);
        }
#pragma unroll 1
        for (int i = XR_CAND + lane; i < XR_SIZE; i += 32) { xr[i] = make_uint4(~0u, ~0u, ~0u, ~0u); __nanosleep(SET_NS); }
        __syncwarp();
        if (lane == 0) { fence_gpu(); mbar_arrive(B(B_SET2)); }
        TL(2, 26, lane == 0);
        __syncwarp();
      }
      __syncwarp();
      if (warp == 3) {
        mbar_wait(B(B_OUT), 0);
        uint4 kv[2];
        poll_chunks(kv, g_xr + ((lane >> 1) * 8 + gq) * XR_SIZE + XR_KEY + (lane & 1) * 2, 1);
        const uint32_t a1 = max(kv[0].x, kv[0].z), a2 = max(min(kv[0].x, kv[0].z), max(kv[0].y, kv[0].w));
        const uint32_t b1 = max(kv[1].x, kv[1].z), b2 = max(min(kv[1].x, kv[1].z), max(kv[1].y, kv[1].w));
        const uint32_t k1 = max(a1, b1), k2 = max(min(a1, b1), max(a2, b2));
        const uint32_t m1 = __reduce_max_sync(~0u, k1);
        const uint32_t m2 = __reduce_max_sync(~0u, k1 == m1 ? k2 : k1);
        auto cand = [&](uint32_t k) { return (((~k >> 7) & 15) * (8 * XR_SIZE) + ((~k >> 4) & 7) * 64) * 16; };
        const uint32_t o1 = cand(m1), o2 = cand(m2) + (((m1 ^ m2) & 0x7FF0) ? 0 : 256);
        if (lane == 0) {
          *reinterpret_cast<uint4*>(sp + OFF_MISC) = make_uint4(m1, m2, o1, o2);
          mbar_arrive(B(B_OUT2));
        }
        const uint32_t key = (lane & 4) ? m2 : m1;
        const uint4* src = g_xr + (((~key >> 7) & 15) * 8 + (rid >> 4)) * XR_SIZE;
        poll_chunks(kv, g_xr + (((lane & 4) ? o2 : o1) >> 4) + (rid >> 4) * XR_SIZE + XR_CAND + (rid & 12) + (lane & 3), 32);
        uint32_t u = key >> 16;
        u = (u & 0x8000u) ? (u & 0x7FFFu) : (~u & 0xFFFFu);
        const float rs = bf_round(sigmoid(__uint_as_float(u << 16)));
        if (lane < 8)
          *reinterpret_cast<uint4*>(sp + OFF_MISC + 128 + lane * 16) = make_uint4((rid & 2) ? ((rid & 1) ? kv[0].w : kv[0].z) : ((rid & 1) ? kv[0].y : kv[0].x),
              (rid & 2) ? ((rid & 1) ? kv[1].w : kv[1].z) : ((rid & 1) ? kv[1].y : kv[1].x), __float_as_uint(rs), 0);
#pragma unroll 1
        for (int n = 0; n < 0x400000; n++) {
          uint32_t v;
          asm volatile("ld.acquire.gpu.global.u32 %0, [%1];" : "=r"(v) : "l"(src + XR_FLAG) : "memory");
          if (__all_sync(~0u, v == 0)) break;
        }
        __syncwarp();
        if (lane == 0) mbar_arrive(B(B_FIN));
      }
      if (warp == 1 && elect_one()) {
        mbar_wait(B(B_OUT3), 0);
        auto owner = [&]() {
          uint2 top;
          asm volatile("ld.shared.v2.u32 {%0,%1}, [%2];" : "=r"(top.x), "=r"(top.y) : "r"(sb + OFF_MISC) : "memory");
          return (0x7FFF - (top.x & 0x7FFF)) >> 7 == mt || (0x7FFF - (top.y & 0x7FFF)) >> 7 == mt;
        };
#pragma unroll 1
        for (int n = 0; n < 4; n++) {
          if (n && !(mbar_test(B(B_OUT2), 0) && owner())) idle(OUT_CLK);
          asm volatile("cp.async.bulk.tensor.2d.global.shared::cta.bulk_group [%0, {%2,%3}], [%1];" ::"l"(&p.out), "r"(sb + OFF_STG + n * 8192),
                       "r"(gq * 128 + (n & 1) * 64), "r"(mt * 128 + (n >> 1) * 64) : "memory");
        }
        asm volatile("cp.async.bulk.commit_group;" ::: "memory");
        mbar_wait(B(B_OUT2), 0);
        if (owner()) {
          asm volatile("cp.async.bulk.wait_group 0;" ::: "memory");
          asm volatile("st.release.gpu.global.u32 [%0], 0;" ::"l"(xr + XR_FLAG) : "memory");
        } else {
          asm volatile("cp.async.bulk.wait_group.read 0;" ::: "memory");
        }
        TL(2, 25, true);
      }
    }
    __syncwarp();
    if (warp == 0) cluster_arrive();
    cluster_wait();
    TL_DUMP();
    if (tid == 32) TS(8);
  } else {
    reg_alloc<232>();
    cluster_wait();
    const int w = wg - 1, cw = warp - 4;
    int lane = lane_id();
    const uint32_t stg = sb + OFF_STG + w * 16384 + (cw & 3) * 2048;
    auto publish = [&](int i) { __syncwarp(); if (lane == 0) mbar_arrive(B(B_PUB + i)); };
    uint32_t rbar;
    asm("mapa.shared::cluster.u32 %0, %1, %2;" : "=r"(rbar) : "r"(bar), "r"(lane & 1));
    auto release2 = [&](int i) { if (lane < 2) asm volatile("mbarrier.arrive.shared::cluster.b64 _, [%0];" ::"r"(rbar + 8 * i) : "memory"); };
    float R[128];
    float O[64], acc[64];
    uint32_t pk[64];
    uint32_t* const Q = pk;
    uint32_t P[32];
    auto packed = [&](int i) {
      const float* v = R + 16 * (i >> 1) + 2 * (i & 1);
      return make_uint4(pack_bf16(v[0], v[1]), pack_bf16(v[4], v[5]), pack_bf16(v[8], v[9]), pack_bf16(v[12], v[13]));
    };
    const uint32_t q_st = sb + (cw & 3) * 1024 + (lane >> 2) * 64 + (((lane & 3) ^ (lane >> 3)) << 4);
    const uint32_t q_ld = sb + (cw & 3) * 1024 + (lane & 15) * 64 + (((lane >> 4) ^ ((lane >> 1) & 3)) << 4);
    auto park = [&](uint32_t off, int i, uint4 v) {
      asm volatile("st.shared.v4.u32 [%0], {%1,%2,%3,%4};" ::"r"(q_st + off + (i >> 1) * 4096 + (i & 1) * 512), "r"(v.x), "r"(v.y), "r"(v.z), "r"(v.w) : "memory");
    };
    auto load_q = [&](uint32_t off, int k) { ldsm4(Q + 4 * k, ((q_ld + off) ^ ((k & 1) << 5)) + (k >> 1) * 4096); };
    {
      TL(0, 1, tid == 128);
      __nv_bfloat16* pdst = g_qkv;
      auto put2 = [&](int j) {
#pragma unroll
        for (int i = (j >> 1) * 4 + (j & 1); i < (j >> 1) * 4 + 4; i += 2)
          __stcs(reinterpret_cast<uint4*>(pdst + (i & 1) * 8 * NQ + (i >> 1) * 32), make_uint4(pk[4 * i], pk[4 * i + 1], pk[4 * i + 2], pk[4 * i + 3]));
      };
      const uint64_t da0 = mk_desc(sb + w * 8192, 16, 1024, 1);
      const uint64_t db0 = mk_desc(sb + 16384, 8192, 1024, 1);
      int st = 0; uint32_t ph = 0;
      auto issue = [&](int accum, auto between, bool res = false) {
        mbar_wait_c(B(B_FULL1 + st), ph);
        const uint64_t da = desc_add(da0, res ? 6 * SLOT + st * 8192 : st * P1_STAGE), db = desc_add(db0, st * P1_STAGE);
        between();
        wg_fence();
#pragma unroll
        for (int k = 0; k < 4; k++) mma_n256_ss<1>(R, desc_add(da, k * 32), desc_add(db, k * 2048), k == 0 ? accum : 1);
        wg_commit();
      };
      issue(0, []() {});
#pragma unroll 1
      for (int t = 0;; t++) {
        const int nk = t >= 4 ? 16 : 8;
        const bool tr = t > 0 && t < 5;
        TL(0, 2 + 2 * t + 16 * w, (tid & 127) == 0);
        int prev = st;
        if (++st == 4) { st = 0; ph ^= 1; }
#pragma unroll 1
        for (int kb = 1; kb < nk; kb++) {
          if (kb == nk - 1 && w == 1) bar_sync(5, 256);
          issue(1, []() {}, t < 4 && (kb & 5) == 4);
          if (kb == nk - 1 && w == 0) bar_arrive(5, 256);
          if (tr) {
#pragma unroll
            for (int i = 1; i < 8; i++) if (kb == i) put2(i);
            if (kb == 7 && !(t & 1)) publish((t >> 1) - 1);
          } else if (t == 5) {
            if (kb == 2) {
#pragma unroll
              for (int i = 0; i < 8; i++) park(6 * SLOT + w * 16384, i, make_uint4(pk[4 * i], pk[4 * i + 1], pk[4 * i + 2], pk[4 * i + 3]));
              __syncwarp();
            }
            if (kb == 4) {
#pragma unroll
              for (int k = 0; k < 8; k++) load_q(6 * SLOT + w * 16384, k);
              __syncwarp();
            }
            if (kb == 6) {
#pragma unroll
              for (int i = 0; i < 8; i++) park(6 * SLOT + w * 16384, i, make_uint4(pk[32 + 4 * i], pk[33 + 4 * i], pk[34 + 4 * i], pk[35 + 4 * i]));
            }
          }
          wg_wait<1>();
          release2(B_EMPTY1 + prev);
          prev = st;
          if (++st == 4) { st = 0; ph ^= 1; }
        }
        if (t == 5) break;
        issue(0, [&]() {
          sched_fence(q_st);
          wg_wait<0>();
          fence_regs<128>(R);
          TL(0, 3 + 2 * t + 16 * w, (tid & 127) == 0);
#pragma unroll
          for (int i = 0; i < 16; i++) { const uint4 v = packed(i); pk[4 * i] = v.x; pk[4 * i + 1] = v.y; pk[4 * i + 2] = v.z; pk[4 * i + 3] = v.w; }
          release2(B_EMPTY1 + prev);
          fence_regs<128>(R);
        });
        if (w == 1) bar_arrive(4, 256);
        sched_fence(q_st);
        pdst = g_qkv + (size_t)(((t & 1) + 1) * SEQ + mt * 128 + cw * 16 + (lane >> 2)) * NQ + (gq + ((t >> 1) ^ 1) * 8) * 256 + (lane & 3) * 8;
        if (t < 4) put2(0);
        if (w == 0) bar_sync(4, 256);
      }
      if (w == 1) bar_arrive(6, 256);
      mbar_wait_c(B(B_KF), 0);
      sched_fence(q_st);
      wg_wait<0>();
      fence_regs<128>(R);
      release2(B_EMPTY1 + 3);
      TL(0, 13 + 16 * w, (tid & 127) == 0);
    }
    auto issue3 = [&](int st, uint32_t ph, int accum) {
      mbar_wait_c(B(B_FULL3 + st), ph);
      const uint64_t da = mk_desc(sb + OFF_R3 + w * 8192 + st * SLOT, 16, 1024, 1), db = mk_desc(sb + OFF_R3 + 16384 + st * SLOT, 8192, 1024, 1);
      wg_fence();
#pragma unroll
      for (int k = 0; k < 4; k++) mma_n128_ss<1>(acc, desc_add(da, k * 32), desc_add(db, k * 2048), k == 0 ? accum : 1);
      wg_commit();
    };
    uint32_t wf[128];
    auto w_addr = [&](uint32_t off, int m) {
      const uint32_t w_ld = sb + ((lane >> 3) & 1) * 8192 + ((cw >> 1) * 32 + (lane & 7) + (lane >> 4) * 8) * 64 + ((((cw & 1) * 2) ^ ((lane >> 1) & 3)) << 4);
      return ((w_ld + off) ^ ((m & 1) << 4)) + (m >> 2) * 16384 + ((m >> 1) & 1) * 1024;
    };
    auto grab = [&](uint32_t* d, uint32_t off, int m0, int m1) {
#pragma unroll
      for (int m = m0; m < m1; m++)
        asm volatile("ldmatrix.sync.aligned.m8n8.x4.trans.shared.b16 {%0,%1,%2,%3}, [%4];"
                     : "=r"(d[4 * m]), "=r"(d[4 * m + 1]), "=r"(d[4 * m + 2]), "=r"(d[4 * m + 3]) : "r"(w_addr(off, m)) : "memory");
    };
    float inv[2] = {0.f, 0.f};
    auto scaled = [&](int i) {
      const float* o = O + 16 * (i >> 1) + 2 * (i & 1);
      const float c = inv[i & 1];
      return make_uint4(pack_bf16(o[0] * c, o[1] * c), pack_bf16(o[4] * c, o[5] * c), pack_bf16(o[8] * c, o[9] * c), pack_bf16(o[12] * c, o[13] * c));
    };
    {
      const int wrow = cw * 16;
      const uint64_t dk0 = mk_desc(sb, 16, 1024, 1);
      const uint64_t dv0 = mk_desc(sb + 2 * SLOT, 16384, 1024, 1);
      const uint32_t pin = sb + OFF_MISC + 1028;
      float l0 = 0.f, l1 = 0.f;
      int g = 0, t = 0;
      uint32_t fail = 0;
      auto piece = [&](int tt) { return (uint32_t)(tt == 3 ? 6 * SLOT + w * 16384 : (3 + 2 * w) * SLOT + (tt - 1) * 16384); };
      uint32_t par = 0;
      auto issue_s = [&](float* S) {
        const uint64_t dk = desc_add(dk0, par * 16);
        mma_n128_rs0(S, Q, dk);
#pragma unroll
        for (int k = 1; k < 8; k++) mma_n128_rs<0>(S, Q + 4 * k, desc_add(dk, (k >> 2) * 16384 + (k & 3) * 32), 1);
        wg_commit();
      };
      auto issue_pv = [&](bool half, int accum) {
        const uint64_t dv = desc_add(dv0, ((g - 1) & 1) * 2 * SLOT);
        wg_fence();
#pragma unroll
        for (int k = 0; k < 4; k++) mma_n128_rs<1>(O, P + 4 * k, desc_add(dv, k * 2048), k == 0 ? accum : 1);
        wg_commit();
        if (UNLIKELY(half)) {
          wg_fence();
          wg_commit();
        } else {
          wg_fence();
#pragma unroll
          for (int k = 4; k < 8; k++) mma_n128_rs<1>(O, P + 4 * k, desc_add(dv, k * 2048), 1);
          wg_commit();
        }
        bar_arrive(2 - w, 256);
        wg_wait<2>();
        fence_regs<32>(Q);
      };
      auto release_k = [&]() { release2(B_KE); rbar ^= 8; };
      auto pv_done = [&]() {
        TC(g, 3);
        sched_fence(q_st);
        wg_wait<0>();
        fence_regs<64>(O); fence_regs<32>(P);
        TC(g, 4);
        release2(B_VE);
      };
      auto row_inv = [&](bool go) {
        float a = l0 + __shfl_xor_sync(~0u, l0, 1), b = l1 + __shfl_xor_sync(~0u, l1, 1);
        a += __shfl_xor_sync(~0u, a, 2); b += __shfl_xor_sync(~0u, b, 2);
        const bool ok = __all_sync(~0u, a >= AT_LO && a <= AT_HI && b >= AT_LO && b <= AT_HI) != 0;
        asm("rcp.approx.ftz.f32 %0, %1;" : "=f"(inv[0]) : "f"(a));
        asm("rcp.approx.ftz.f32 %0, %1;" : "=f"(inv[1]) : "f"(b));
        fail |= (uint32_t)(go && !ok) << t;
        l0 = go ? 0.f : l0; l1 = go ? 0.f : l1;
        t += go;
      };
      const uint64_t m_first = 1ull | (1ull << (16 - ti)) | (1ull << 17) | (1ull << (18 + ti));
      const uint64_t m_diag = (3ull << (15 - ti)) | (3ull << (17 + ti));
      enum { F_FIRST = 1, F_DIAG = 2, F_LAST = 4, F_PFIRST = 8, F_PHALF = 16, F_STOP = 32 };
      auto kind = [&](int gn) {
        const uint32_t a = (uint32_t)((m_first << 1) >> gn), d = (uint32_t)((m_diag << 1) >> gn);
        return ((a >> 1) & 1) * F_FIRST | ((d >> 1) & 1) * F_DIAG | ((a >> 2) & 1) * F_LAST | (a & 1) * F_PFIRST |
               (w == 0 ? (d & 1) * F_PHALF | ((d >> 1) & 1) * F_STOP : 0) | (gn == 34 ? F_STOP : 0);
      };
      uint32_t kinds;
      {
        uint32_t qt[64];
#pragma unroll
        for (int i = 0; i < 16; i++) { const uint4 v = packed(i); qt[4 * i] = v.x; qt[4 * i + 1] = v.y; qt[4 * i + 2] = v.z; qt[4 * i + 3] = v.w; }
        fence_regs<64>(qt);
        sched_fence(q_st);
        float S[64];
        wg_fence();
        issue_s(S);
        bar_arrive(w ? 1 : 7, 256);
        bar_sync(6 + w, 256);
        sched_fence(q_st);
        TL(1, 0, tid == 128);
#pragma unroll
        for (int i = 0; i < 16; i++) park(piece(1), i, make_uint4(qt[4 * i], qt[4 * i + 1], qt[4 * i + 2], qt[4 * i + 3]));
        kinds = pinned(kind(lane + 3));
        sched_fence(q_st);
        wg_wait<0>();
        fence_regs<64>(S);
        release_k();
        TL(1, 1, tid == 128);
        const bool kok = mbar_try(B(B_KF + 1), 0);
        at_exp<0, 32>(S);
        sched_fence(q_st);
        at_exp<32, 64>(S); at_fin<0, 64>(S, P);
        if (UNLIKELY(!kok)) mbar_wait_c(B(B_KF + 1), 0);
        TL(1, 2, tid == 128);
      }
      uint32_t f = F_PFIRST, fn;
      auto shadow = [&]() {
        const bool vok = mbar_try(B(B_VF + ((g - 1) & 1)), ((g - 1) >> 1) & 1);
        at_sum(P, f & F_PHALF, l0, l1);
        fn = __shfl_sync(~0u, kinds, max(g - 2, 0));
        if (UNLIKELY(!vok)) mbar_wait_c(B(B_VF + ((g - 1) & 1)), ((g - 1) >> 1) & 1);
      };
      auto hand_over = [&]() { __syncwarp(); if (lane == 0 && !((fail >> (t - 1)) & 1)) mbar_arrive(B(B_PUB + 1 + t)); };
      auto exp_q = [&](float* S, auto kc, auto nc) {
        constexpr int k = decltype(kc)::value, n = decltype(nc)::value;
        asm volatile("{\n.reg .pred p;\nsetp.ne.b32 p, %5, 0;\n@p ldmatrix.sync.aligned.m8n8.x4.shared.b16 {%0,%1,%2,%3}, [%4];\n}"
                     : "+r"(Q[4 * k]), "+r"(Q[4 * k + 1]), "+r"(Q[4 * k + 2]), "+r"(Q[4 * k + 3])
                     : "r"(((q_ld + piece(t + 1)) ^ ((k & 1) << 5)) + (k >> 1) * 4096), "r"(f & F_LAST) : "memory");
        at_exp<n * k, n * k + n>(S);
      };
      g = 1; par = SLOT / 16;
#pragma unroll 1
      for (;;) {
        {
          TC(g, 0);
          bar_sync(1 + w, 256);
          fence_regs<32>(Q);
          float S[64];
          wg_fence();
          issue_s(S);
          sched_fence(q_st);
          TC(g, 1);
          shadow();
          fence_regs<64>(O); fence_regs<32>(P);
          issue_pv(f & F_PHALF, ~f & F_PFIRST);
          fence_regs<64>(S);
          TC(g, 2);
          release_k();
          at_exp<0, 8>(S);
          const bool first = f & F_FIRST;
          if (UNLIKELY(f & (F_FIRST | F_LAST))) {
            row_inv(first);
            at_mask(S + 32, (f & F_DIAG) ? wrow - 64 : 64, lane);
            unroll8([&](auto kc) { exp_q(S + 8, kc, std::integral_constant<int, AT_R1 / 8 - 1>{}); });
          } else {
            at_exp<8, AT_R1>(S);
          }
          pv_done();
          g = pinned(g + 1); par = pinned(par ^ (SLOT / 16)); f = fn;
          const bool kok = mbar_try(B(B_KF + (g & 1)), g < 34 ? (g >> 1) & 1 : 0);
          if (UNLIKELY(first)) {
            unroll8([&](auto ic) {
              constexpr int i = decltype(ic)::value, n = (64 - AT_R1) / 8;
              at_exp<AT_R1 + n * i, AT_R1 + n * i + n>(S);
              park(piece(t), i, scaled(i));
            });
            at_fin<0, 64>(S, P);
            hand_over();
          } else {
            at_exp<AT_R1, 64>(S); at_fin<0, 64>(S, P);
          }
          TC(g - 1, 5);
          if (!TCLK) TL(1, 1 + g, tid == 128);
          if (kok && !(f & F_STOP)) continue;
          if (UNLIKELY(!kok)) mbar_wait_c(B(B_KF + (g & 1)), (g >> 1) & 1);
          if (g == 34) break;
        }
#pragma unroll 1
        while (f & F_STOP) {
          TC(g, 0);
          bar_sync(1, 256);
          fence_regs<64>(O); fence_regs<32>(Q); fence_regs<32>(P);
          float S[32];
          const uint64_t dk = desc_add(dk0, par * 16);
          wg_fence();
          mma_n64_rs0(S, Q, dk);
#pragma unroll
          for (int k = 1; k < 8; k++) mma_n64_rs(S, Q + 4 * k, desc_add(dk, (k >> 2) * 16384 + (k & 3) * 32), 1);
          wg_commit();
          TC(g, 1);
          mbar_wait_c(B(B_VF + ((g - 1) & 1)), ((g - 1) >> 1) & 1);
          issue_pv(f & F_PHALF, ~f & F_PFIRST);
          fence_regs<32>(S);
          TC(g, 2);
          release_k();
          const bool first = f & F_FIRST;
          at_sum(P, f & F_PHALF, l0, l1);
          fn = __shfl_sync(~0u, kinds, g - 2);
          row_inv(first);
          pv_done();
          sched_fence(q_st);
          at_mask(S, wrow, lane);
          unroll8([&](auto kc) { exp_q(S, kc, std::integral_constant<int, 4>{}); });
          g++; par ^= SLOT / 16; f = fn;
          at_fin<0, 32>(S, P);
          if (first) {
#pragma unroll
            for (int i = 0; i < 8; i++) park(piece(t), i, scaled(i));
            hand_over();
          }
          TC(g - 1, 5);
          if (!TCLK) TL(1, 1 + g, tid == 128);
          mbar_wait_c(B(B_KF + (g & 1)), (g >> 1) & 1);
        }
      }
      const bool wok = mbar_test(B(ffn ? B_WF : B_QP + 1), 0);
      grab(wf, 3 * SLOT, 0, 8);
      mbar_wait_c(B(B_VF + 1), 0);
      bar_sync(1 + w, 256);
      fence_regs<64>(O); fence_regs<32>(P);
      wg_fence();
#pragma unroll
      for (int k = 0; k < 8; k++) mma_n128_rs<1>(O, P + 4 * k, desc_add(dv0, 2 * SLOT + k * 2048), 1);
      wg_commit();
      if (w == 0) bar_arrive(2, 256);
      pin_order(__uint_as_float(wf[28] & wf[24]), pin);
      __syncwarp();
      if (wok) release2(B_WE);
      TL(3, 12 + 16 * w, (tid & 127) == 0);
      sched_fence(q_st);
      at_sum(P, false, l0, l1);
      row_inv(true);
      sched_fence(q_st);
      wg_wait<0>();
      fence_regs<64>(O); fence_regs<32>(P);
      release2(B_VE + 1);
      if (UNLIKELY(!wok || fail != 0)) {
#pragma unroll 1
        for (int tt = 0; tt < 4; tt++) {
          if (!((tt < 3 ? fail >> tt : fail != 0) & 1)) continue;
          slow_tile(O, P, l0, l1, wq, (((tt + 1) & 2) ? ti : 15 - ti) * 128 + wrow, hh + (tt & 2) * 8, lane, q_st);
          row_inv(false);
          if (tt < 3) {
#pragma unroll
            for (int i = 0; i < 8; i++) park(piece(tt + 1), i, scaled(i));
            publish(2 + tt);
          }
        }
        if (!wok) {
          mbar_wait_c(B(ffn ? B_WF : B_QP + 1), 0);
          grab(wf, 3 * SLOT, 0, 8);
          pin_order(__uint_as_float(wf[28] & wf[24]), pin);
          __syncwarp();
          release2(B_WE);
        }
      }
      TL(3, 13 + 16 * w, (tid & 127) == 0);
      issue3(0, 0, 0);
      TL(3, 14 + 16 * w, (tid & 127) == 0);
      TL(1, 36, tid == 128);
    }
    uint32_t hp[32];
    lane = lane_id();
    {
      int st = 1, prev = 0; uint32_t ph = 0;
      __nv_bfloat16* dst = g_qkv + (size_t)((15 - ti) * 128 + cw * 16 + (lane >> 2)) * NQ + (hh + 16) * 128 + (lane & 3) * 8;
      auto kblock = [&](auto between, int lim = 6) {
        issue3(st, ph, 1);
        between();
        wg_wait<1>();
        release2(B_EMPTY3 + prev);
        prev = st;
        if (++st == lim) { st = 0; ph ^= 1; }
      };
      uint4 ob[8];
      kblock([&]() { sched_fence(rbar); ob[0] = scaled(0); ob[1] = scaled(2); ob[2] = scaled(1); ob[3] = scaled(3); sched_fence(rbar); });
      kblock([&]() { sched_fence(rbar); ob[4] = scaled(4); ob[5] = scaled(6); ob[6] = scaled(5); ob[7] = scaled(7); sched_fence(rbar); grab(wf + 32, 5 * SLOT, 0, 8); });
#pragma unroll 1
      for (int kb = 3; kb < 11; kb++) {
        kblock([&]() {
          sched_fence(rbar);
#pragma unroll
          for (int i = 0; i < 8; i++)
            if (kb == 3 + i) *reinterpret_cast<uint4*>(dst + (i & 2) * 4 * NQ + (i & 1) * 32 + (i & 4) * 16) = ob[i];
          TL(3, 14 + kb + 16 * w, (tid & 127) == 0);
          if (kb == 8) TL(2, 2, tid == 128);
        }, kb == 4 ? 5 : 6);
        if (kb == 4) release2(B_EMPTY3 + 5);
      }
      publish(5);
      kblock([&]() { mbar_wait_c(B(ffn ? B_WF2 : B_QP + 2), 0); grab(wf + 32, 5 * SLOT, 8, 16); });
#pragma unroll 1
      for (int kb = 12; kb < G_KB; kb++) {
        kblock([&]() { if ((kb & 7) == 0) TL(2, 1 + (kb >> 3), tid == 128); });
        if (kb == X_KB && lane == 0) mbar_arrive(B(B_XE));
      }
      kblock([&]() {
        mbar_wait_c(B(B_XF), 0);
#pragma unroll
        for (int i = 0; i < 8; i++)
          ldsm4(hp + 4 * i, sb + 6 * SLOT + w * 16384 + ((cw & 3) * 16 + (lane & 15)) * 128 + (i >> 2) * 8192 + ((((i & 3) * 2 + (lane >> 4)) ^ (lane & 7)) << 4));
      });
#pragma unroll 1
      for (int kb = G_KB + 1; kb < 64; kb++) {
        kblock([&]() { if ((kb & 7) == 0) TL(2, 1 + (kb >> 3), tid == 128); });
        if (kb == G_KB + 2 && lane == 0) mbar_arrive(B(B_XE));
      }
    }
    lane = lane_id();
    const int r0 = lane >> 2, q4 = lane & 3, ct = cw * 32 + lane;
    uint32_t tb[16];
    mbar_wait_c(B(B_WR), 0);
#pragma unroll
    for (int i = 0; i < 4; i++) ldsm4(tb + 4 * i, sb + OFF_MISC + 512 + (lane & 1) * 256 + (lane >> 3) * 16 + i * 64);
    mbar_wait_c(B(B_SET2), 0);
    float4* const psd = reinterpret_cast<float4*>(xr + XR_PS + cw * 16 + r0);
    const uint4* const pss = g_xr + (mt * 8 + (ct & 1) * 4) * XR_SIZE + XR_PS + (ct >> 1);
    sched_fence(stg);
    wg_wait<0>();
    fence_regs<64>(acc);
    TL(2, 10, tid == 128);
    {
      float d[2][4] = {}, qa[2][4] = {}, qb[2][4] = {};
#pragma unroll
      for (int j = 0; j < 16; j++) {
        hp[2 * j] = hadd2_bf(hp[2 * j], pack_bf16(acc[4 * j], acc[4 * j + 1]));
        hp[2 * j + 1] = hadd2_bf(hp[2 * j + 1], pack_bf16(acc[4 * j + 2], acc[4 * j + 3]));
        if (j & 1) {
          mma16816(d[(j >> 1) & 1], hp[2 * j - 2], hp[2 * j - 1], hp[2 * j], hp[2 * j + 1], tb[j - 1], tb[j]);
          mma16816(qa[(j >> 1) & 1], hp[2 * j - 2], hp[2 * j - 1], hp[2 * j], hp[2 * j + 1], hp[2 * j - 2], hp[2 * j]);
          mma16816(qb[(j >> 1) & 1], hp[2 * j - 2], hp[2 * j - 1], hp[2 * j], hp[2 * j + 1], hp[2 * j - 1], hp[2 * j + 1]);
        }
      }
      if (q4 == (r0 >> 1)) {
        __stcg(psd, make_float4(d[0][0] + d[1][0], (r0 & 1) ? qa[0][1] + qa[1][1] : qa[0][0] + qa[1][0], d[0][1] + d[1][1], 0.f));
        __stcg(psd + 8, make_float4(d[0][2] + d[1][2], (r0 & 1) ? qb[0][3] + qb[1][3] : qb[0][2] + qb[1][2], d[0][3] + d[1][3], 0.f));
      }
    }
    TL(2, 11, tid == 128);
    mbar_wait_c(B(B_EMPTY3 + 1), 0);
    stage_store_128(stg, lane, hp);
    if (ffn) mbar_wait_c(B(B_WF2), 1);
    grab(wf + 96, 6 * SLOT, 0, 8);
    const float wsum = *reinterpret_cast<const float*>(sp + OFF_MISC + 1024);
    __syncwarp();
    {
      uint4 ps[4];
      poll_chunks(ps, pss, XR_SIZE);
      TL(2, 12, tid == 128);
      auto F = [](uint32_t u) { return __uint_as_float(u); };
      float s1 = (F(ps[0].x) + F(ps[1].x)) + (F(ps[2].x) + F(ps[3].x)), s2 = (F(ps[0].y) + F(ps[1].y)) + (F(ps[2].y) + F(ps[3].y));
      float s3 = (F(ps[0].z) + F(ps[1].z)) + (F(ps[2].z) + F(ps[3].z));
      __syncwarp();
      s1 += __shfl_xor_sync(~0u, s1, 1); s2 += __shfl_xor_sync(~0u, s2, 1); s3 += __shfl_xor_sync(~0u, s3, 1);
      const float mean = s1 * (1.f / DM);
      float mb, inv;
      ln_round(mean, fmaxf(fmaf(s2, 1.f / DM, -mean * mean), 0.f), mb, inv);
      const uint32_t u = pack_bf16(0.f, fmaf(s3 - mb * wsum, inv, 0.f));
      const uint32_t key = (u ^ ((((int)u >> 31) & 0x7FFF0000u) | 0x80000000u)) | (0x7FFFu - (mt * 128 + (ct >> 1)));
      const uint32_t nm2 = pack_bf16(-mb, -mb);
      const uint32_t c1 = __reduce_max_sync(~0u, key);
      const uint32_t c2 = __reduce_max_sync(~0u, key == c1 ? 0u : key);
      if (lane == 0) {
        __stcg(reinterpret_cast<uint2*>(psd) + (XR_KEY - XR_PS) * 2 - cw * 31, make_uint2(c1, c2));
        mbar_arrive(B(B_OUT));
      }
      TL(2, 13, tid == 128);
      const int row = (0x7FFF - (((lane >> 4) ? c2 : c1) & 0x7FFF)) & 15;
      const uint32_t rn = __shfl_sync(~0u, nm2, row * 2);
      const float ri = __shfl_sync(~0u, inv, row * 2);
      uint32_t v[4];
#pragma unroll
      for (int i = 0; i < 4; i++)
        asm volatile("ld.shared.u32 %0, [%1];" : "=r"(v[i]) : "r"(stg + ((lane >> 3) & 1) * 8192 + row * 128 + ((((lane & 4) + i) ^ (row & 7)) << 4) + q4 * 4) : "memory");
      __stcg(xr + XR_CAND + cw * 64 + 32 + lane, make_uint4(ln_apply(v[0], rn, ri), ln_apply(v[1], rn, ri), ln_apply(v[2], rn, ri), ln_apply(v[3], rn, ri)));
      __stcg(xr + XR_CAND + cw * 64 + lane, make_uint4(v[0], v[1], v[2], v[3]));
      sched_fence(stg);
      const uint32_t na = __shfl_sync(~0u, nm2, r0 * 2), nb = __shfl_sync(~0u, nm2, r0 * 2 + 16);
      const float ia = __shfl_sync(~0u, inv, r0 * 2), ib = __shfl_sync(~0u, inv, r0 * 2 + 16);
#pragma unroll
      for (int i = 0; i < 32; i++) hp[i] = hadd2_bf(hp[i], ln_apply(hp[i], (i & 1) ? nb : na, (i & 1) ? ib : ia));
      __syncwarp();
      stage_store_128(stg, lane, hp);
      asm volatile("fence.proxy.async.shared::cta;" ::: "memory");
      publish(B_OUT3 - B_PUB);
    }
    uint32_t wd[16][4];
    sched_fence(stg);
    if (ffn) mbar_wait_c(B(B_FULL3 + 5 * w), 1 - w);
    auto load_wd = [&](int h) {
#pragma unroll
      for (int i = h; i < 16; i += 2)
        asm volatile("ldmatrix.sync.aligned.m8n8.x4.trans.shared.b16 {%0,%1,%2,%3}, [%4];"
                     : "=r"(wd[i][0]), "=r"(wd[i][1]), "=r"(wd[i][2]), "=r"(wd[i][3])
                     : "r"(sb + OFF_R3 + 5 * w * SLOT + (2 * (cw & 3) + (i >> 3)) * 4096 + (h * 16 + (lane & 7) + (lane >> 4) * 8) * 128 +
                           (((2 * ((i >> 1) & 3) + ((lane >> 3) & 1)) ^ (lane & 7)) << 4)) : "memory");
    };
    load_wd(0);
    __syncwarp();
    cluster_arrive();
    const char* xsrc = reinterpret_cast<const char*>(g_xr + (r0 >> 1) * XR_SIZE + XR_CAND + 32 + (cw >> 1) * 4 + q4);
    asm volatile("" : "+l"(xsrc));
    sched_fence(stg);
    TL(2, 22, tid == 128);
    mbar_wait_c(B(B_OUT2), 0);
    TL(2, 14, tid == 128);
    if (ffn) {
      uint4 xb[2];
      poll_chunks(xb, reinterpret_cast<const uint4*>(xsrc + *reinterpret_cast<const uint32_t*>(sp + OFF_MISC + 8 + (r0 & 1) * 4)), 4 * XR_SIZE);
      __syncwarp();
      TL(2, 15, tid == 128);
      float d[8][4] = {};
#pragma unroll
      for (int n = 0; n < 32; n++) {
        if (n == 8) { sched_fence(stg); load_wd(1); }
        const int s = (n >> 4) * 4 + ((n >> 1) & 3), m = ((n >> 3) & 1) * 2 + (n & 1);
        const uint32_t* a = wf + 16 * s + 4 * m;
        mma16816(d[n & 7], a[0], a[1], a[2], a[3], (m & 2) ? xb[s >> 2].z : xb[s >> 2].x, (m & 2) ? xb[s >> 2].w : xb[s >> 2].y);
      }
      float v[8];
#pragma unroll
      for (int i = 0; i < 8; i++) {
        const float lo = (q4 & 1) ? d[2 + (i >> 2)][i & 3] : d[i >> 2][i & 3], hi = (q4 & 1) ? d[6 + (i >> 2)][i & 3] : d[4 + (i >> 2)][i & 3];
        v[i] = (q4 & 2) ? hi : lo;
      }
#pragma unroll
      for (int i = 0; i < 4; i++) v[i] = ((q4 & 2) ? v[i + 4] : v[i]) + __shfl_xor_sync(~0u, (q4 & 2) ? v[i] : v[i + 4], 2);
#pragma unroll
      for (int i = 0; i < 2; i++) v[i] = ((q4 & 1) ? v[i + 2] : v[i]) + __shfl_xor_sync(~0u, (q4 & 1) ? v[i] : v[i + 2], 1);
      float4* red = reinterpret_cast<float4*>(sp + SL_SCR * SLOT);
      reinterpret_cast<float2*>(red + cw * 16 + (q4 >> 1) * 8 + r0)[q4 & 1] = make_float2(v[0], v[1]);
      bar_sync(3, 256);
      TL(2, 16, tid == 128);
      const float4 z0 = red[lane], z1 = red[32 + lane], z2 = red[64 + lane], z3 = red[96 + lane];
      const uint32_t ub = pack_bf16((z0.x + z1.x) + (z2.x + z3.x), (z0.y + z1.y) + (z2.y + z3.y));
      const uint32_t gb = pack_bf16((z0.z + z1.z) + (z2.z + z3.z), (z0.w + z1.w) + (z2.w + z3.w));
      const float g0 = bf_lo(gb), g1 = bf_hi(gb);
      const uint32_t sg = pack_bf16(g0 * sigmoid(g0), g1 * sigmoid(g1));
      const uint32_t act = pack_bf16(bf_lo(sg) * bf_lo(ub), bf_hi(sg) * bf_hi(ub));
      const uint32_t pr = __byte_perm(act, __shfl_xor_sync(~0u, act, 1), (lane & 1) ? 0x3276 : 0x5410);
      const int src = q4 * 2 + (r0 & 1);
      const uint32_t a0 = __shfl_sync(~0u, pr, src), a1 = __shfl_sync(~0u, pr, src + 8), a2 = __shfl_sync(~0u, pr, src + 16), a3 = __shfl_sync(~0u, pr, src + 24);
      TL(2, 17, tid == 128);
      float y[8][4] = {};
#pragma unroll
      for (int i = 0; i < 8; i++) mma16816(y[i], wd[2 * i][0], wd[2 * i][1], wd[2 * i][2], wd[2 * i][3], a0, a1);
#pragma unroll
      for (int i = 0; i < 8; i++) mma16816(y[i], wd[2 * i + 1][0], wd[2 * i + 1][1], wd[2 * i + 1][2], wd[2 * i + 1][3], a2, a3);
      float2* yd = reinterpret_cast<float2*>(g_xr + (cw * 16 + 2 * q4) * XR_SIZE + XR_Y + fid * 4) + r0;
#pragma unroll
      for (int j = 0; j < 2; j++) {
        float v[4];
#pragma unroll
        for (int e = 0; e < 4; e++) {
          const float lo = (q4 & 1) ? y[4 * j + 1][e] : y[4 * j][e], hi = (q4 & 1) ? y[4 * j + 3][e] : y[4 * j + 2][e];
          v[e] = (q4 & 2) ? hi : lo;
        }
        __stcg(yd + j * 16 * XR_SIZE, make_float2(v[0], v[1]));
        __stcg(yd + j * 16 * XR_SIZE + 2 * XR_SIZE, make_float2(v[2], v[3]));
      }
    }
    TL(2, 18, tid == 128);
    cluster_wait();
    if (rid == 127 && ct < C_NUM) g_cnt[ct] = 0;
    if (cw < 2) {
      const int tok = (lane >> 1) & 1, pair = cw * 2 + (lane & 1);
      uint32_t* const dst = reinterpret_cast<uint32_t*>(out + (size_t)(~*reinterpret_cast<const uint32_t*>(sp + OFF_MISC + tok * 4) & 0x7FF) * DM) + rid * 4 + pair;
      idle(ffn ? Y_CLK : Y_CLK + 2000);
      const bool fin = mbar_test(B(B_FIN), 0);
      uint4 op = lds128(sb + OFF_MISC + 128 + (tok * 4 + pair) * 16);
      uint4 z[7];
      poll_chunks(z, xr + XR_Y + (lane >> 1) * 4 + pair, 64);
      __syncwarp();
      TL(2, 19, tid == 128);
      if (!fin) { mbar_wait_c(B(B_FIN), 0); op = lds128(sb + OFF_MISC + 128 + (tok * 4 + pair) * 16); }
      auto F = [](uint32_t u) { return __uint_as_float(u); };
      const float v0 = ((F(z[0].x) + F(z[1].x)) + (F(z[2].x) + F(z[3].x))) + ((F(z[4].x) + F(z[5].x)) + F(z[6].x));
      const float v1 = ((F(z[0].y) + F(z[1].y)) + (F(z[2].y) + F(z[3].y))) + ((F(z[4].y) + F(z[5].y)) + F(z[6].y));
      const float v2 = ((F(z[0].z) + F(z[1].z)) + (F(z[2].z) + F(z[3].z))) + ((F(z[4].z) + F(z[5].z)) + F(z[6].z));
      const float v3 = ((F(z[0].w) + F(z[1].w)) + (F(z[2].w) + F(z[3].w))) + ((F(z[4].w) + F(z[5].w)) + F(z[6].w));
      float ya = (tok ? v1 : v0) + __shfl_xor_sync(~0u, tok ? v0 : v1, 2), yb = (tok ? v3 : v2) + __shfl_xor_sync(~0u, tok ? v2 : v3, 2);
#pragma unroll
      for (int o = 4; o < 32; o <<= 1) { ya += __shfl_xor_sync(~0u, ya, o); yb += __shfl_xor_sync(~0u, yb, o); }
      const uint32_t yp = pack_bf16(ya, yb);
      if (lane < 4) *dst = hadd2_bf(op.x, hadd2_bf(op.y, pack_bf16(bf_lo(yp) * F(op.z), bf_hi(yp) * F(op.z))));
      TL(2, 21, tid == 128);
    }
    TL(2, 20, tid == 128);
    TL_DUMP();
  }
}

typedef CUresult (*EncodeFn)(CUtensorMap*, CUtensorMapDataType, cuuint32_t, void*, const cuuint64_t*, const cuuint64_t*, const cuuint32_t*,
                             const cuuint32_t*, CUtensorMapInterleave, CUtensorMapSwizzle, CUtensorMapL2promotion, CUtensorMapFloatOOBfill);
EncodeFn g_enc = nullptr;

void map2(CUtensorMap* m, const void* ptr, uint64_t rows, uint64_t cols, uint32_t bc, uint32_t br) {
  const CUtensorMapSwizzle sw = bc == 64 ? CU_TENSOR_MAP_SWIZZLE_128B : CU_TENSOR_MAP_SWIZZLE_64B;
  cuuint64_t gd[2] = {cols, rows}, gs[1] = {cols * 2};
  cuuint32_t bd[2] = {bc, br}, es[2] = {1, 1};
  g_enc(m, CU_TENSOR_MAP_DATA_TYPE_BFLOAT16, 2, (void*)ptr, gd, gs, bd, es, CU_TENSOR_MAP_INTERLEAVE_NONE, sw,
        CU_TENSOR_MAP_L2_PROMOTION_L2_128B, CU_TENSOR_MAP_FLOAT_OOB_FILL_NONE);
}
void map3(CUtensorMap* m, const void* ptr, uint64_t rows, uint64_t cols, uint32_t br, uint32_t bch, uint32_t bc = 64) {
  cuuint64_t gd[3] = {bc, rows, cols / bc}, gs[2] = {cols * 2, bc * 2};
  cuuint32_t bd[3] = {bc, br, bch}, es[3] = {1, 1, 1};
  g_enc(m, CU_TENSOR_MAP_DATA_TYPE_BFLOAT16, 3, (void*)ptr, gd, gs, bd, es, CU_TENSOR_MAP_INTERLEAVE_NONE, bc == 64 ? CU_TENSOR_MAP_SWIZZLE_128B : CU_TENSOR_MAP_SWIZZLE_64B,
        CU_TENSOR_MAP_L2_PROMOTION_L2_128B, CU_TENSOR_MAP_FLOAT_OOB_FILL_NONE);
}

}

extern "C" void kernel_launch(void* const* d_in, const int* in_sizes, int n_in, void* d_out, int out_size) {
  const __nv_bfloat16* x = (const __nv_bfloat16*)d_in[0];
  const __nv_bfloat16* ckv = (const __nv_bfloat16*)d_in[1];
  const __nv_bfloat16* wq = (const __nv_bfloat16*)d_in[2];
  const __nv_bfloat16* wk = (const __nv_bfloat16*)d_in[3];
  const __nv_bfloat16* wv = (const __nv_bfloat16*)d_in[4];
  const __nv_bfloat16* wo = (const __nv_bfloat16*)d_in[5];
  const __nv_bfloat16* w_r = (const __nv_bfloat16*)d_in[7];
  const __nv_bfloat16* wgate = (const __nv_bfloat16*)d_in[8];
  const __nv_bfloat16* wup = (const __nv_bfloat16*)d_in[9];
  const __nv_bfloat16* wdown = (const __nv_bfloat16*)d_in[10];
  __nv_bfloat16* out = (__nv_bfloat16*)d_out;

  if (!g_enc) {
    void* fn = nullptr;
    cudaDriverEntryPointQueryResult qr;
    cudaGetDriverEntryPoint("cuTensorMapEncodeTiled", &fn, cudaEnableDefault, &qr);
    g_enc = (EncodeFn)fn;
    cudaFuncSetAttribute(fused_kernel, cudaFuncAttributeMaxDynamicSharedMemorySize, SMEM_BYTES);
  }
  void *xn, *qkv;
  cudaGetSymbolAddress(&xn, g_xn);
  cudaGetSymbolAddress(&qkv, g_qkv);

  Params p;
  map2(&p.xn, xn, SEQ, DM, 64, 128);
  map2(&p.ckv, ckv, SEQ, DC, 64, 128);
  map3(&p.wq, wq, DM, NQ, 64, 2);
  map3(&p.wk, wk, DC, NQ, 64, 2);
  map3(&p.wv, wv, DC, NQ, 64, 2);
  map3(&p.kv, qkv, 3 * SEQ, NQ, 128, 1);
  map2(&p.ctx_ld, qkv, SEQ, NQ, 64, 128);
  map3(&p.ctx_st, qkv, SEQ, NQ, 64, 1, 32);
  map3(&p.wo, wo, NQ, DM, 64, 1);
  map3(&p.x, x, SEQ, DM, 64, 1);
  map3(&p.wd, wdown, FF, DM, 32, 8);
  map2(&p.out, out, SEQ, DM, 64, 64);
  map2(&p.wg, wgate, DM, FF, 32, 128);
  map2(&p.wu, wup, DM, FF, 32, 128);
  fused_kernel<<<128, 384, SMEM_BYTES, cudaStreamPerThread>>>(x, wq, w_r, out, p);
}
```

```cpp
#include <cuda_runtime.h>
#include <cuda_bf16.h>
#include <cuda.h>
#include <stdint.h>
#include <type_traits>

#pragma nv_diag_suppress 549
namespace {

constexpr int SEQ = 2048, DM = 1024, NH = 32, HD = 128, DC = 512, NQ = NH * HD, FF = 3584;

__device__ __align__(1024) __nv_bfloat16 g_xn[SEQ * DM];
__device__ __align__(1024) __nv_bfloat16 g_qkv[3 * SEQ * NQ];
constexpr int XR_PS = 0;
constexpr int XR_KEY = 128;
constexpr int XR_FLAG = 132;
constexpr int XR_CAND = 136;
constexpr int XR_Y = 648;
constexpr int XR_SIZE = 1104;
__device__ __align__(1024) uint4 g_xr[128 * XR_SIZE];
constexpr int C_LN = 0, C_QKV = 16, C_CTX = 32, C_NUM = 64;
__device__ unsigned g_cnt[C_NUM];

#define TL(k, i, cond) do {} while (0)
#define TL_BYTES 0
#define TL_INIT() do {} while (0)
#define TL_DUMP() do {} while (0)
#define TC(g, i) do {} while (0)
#define TS(i) do {} while (0)
#undef TCLK
#define TCLK 0

__device__ __forceinline__ uint32_t s2u(const void* p) { return (uint32_t)__cvta_generic_to_shared(p); }
__device__ __forceinline__ void mbar_init(uint32_t b, uint32_t c) { asm volatile("mbarrier.init.shared::cta.b64 [%0], %1;" ::"r"(b), "r"(c) : "memory"); }
__device__ __forceinline__ void mbar_expect(uint32_t b, uint32_t bytes) { asm volatile("mbarrier.arrive.expect_tx.shared::cta.b64 _, [%0], %1;" ::"r"(b), "r"(bytes) : "memory"); }
__device__ __forceinline__ void mbar_arrive(uint32_t b) { asm volatile("mbarrier.arrive.shared::cta.b64 _, [%0];" ::"r"(b) : "memory"); }
__device__ __forceinline__ bool mbar_test(uint32_t b, uint32_t ph) {
  uint32_t ok;
  asm volatile("{\n.reg .pred p;\nmbarrier.test_wait.parity.shared::cta.b64 p, [%1], %2;\nselp.u32 %0, 1, 0, p;\n}" : "=r"(ok) : "r"(b), "r"(ph) : "memory");
  return ok;
}
__device__ __forceinline__ void mbar_wait(uint32_t b, uint32_t ph) {
  asm volatile(
      "{\n.reg .pred p;\n.reg .u32 n;\nmov.u32 n, 0;\n"
      "LW:\nmbarrier.try_wait.parity.shared::cta.b64 p, [%0], %1, 20000;\n@p bra LD;\n"
      "add.u32 n, n, 1;\nsetp.lt.u32 p, n, 0x40000;\n@p bra LW;\ntrap;\nLD:\n}" ::"r"(b), "r"(ph) : "memory");
}
__device__ __forceinline__ void mbar_wait_c(uint32_t b, uint32_t ph) {
  asm volatile(
      "{\n.reg .pred p;\n.reg .u32 n;\nmov.u32 n, 0;\n"
      "LW:\nmbarrier.try_wait.parity.shared::cta.b64 p, [%0], %1;\n@p bra LD;\n"
      "add.u32 n, n, 1;\nsetp.lt.u32 p, n, 0x100000;\n@p bra LW;\ntrap;\nLD:\n}" ::"r"(b), "r"(ph) : "memory");
}
__device__ __forceinline__ bool mbar_try(uint32_t b, uint32_t ph) {
  uint32_t ok;
  asm volatile("{\n.reg .pred p;\nmbarrier.try_wait.parity.shared::cta.b64 p, [%1], %2;\nselp.u32 %0, 1, 0, p;\n}" : "=r"(ok) : "r"(b), "r"(ph) : "memory");
  return ok;
}
#define UNLIKELY(c) __builtin_expect(!!(c), 0)
__device__ __forceinline__ uint32_t pinned(uint32_t v) { uint32_t r; asm volatile("mov.b32 %0, %1;" : "=r"(r) : "r"(v)); return r; }
__device__ __forceinline__ bool elect_one() {
  uint32_t p;
  asm volatile("{\n.reg .pred p;\nelect.sync _|p, 0xFFFFFFFF;\nselp.u32 %0, 1, 0, p;\n}" : "=r"(p));
  return p;
}
__device__ __forceinline__ int lane_id() { int r; asm volatile("mov.u32 %0, %%laneid;" : "=r"(r)); return r; }
template <bool SLEEP = false>
__device__ __forceinline__ void spin_until_ge(const unsigned* p, unsigned target) {
  asm volatile(
      "{\n.reg .pred p, q;\n.reg .u32 n, v;\nmov.u32 n, 0;\nsetp.ne.u32 q, %2, 0;\n"
      "LW:\nld.acquire.gpu.global.u32 v, [%0];\nsetp.ge.u32 p, v, %1;\n@p bra LD;\n@q nanosleep.u32 200;\n"
      "add.u32 n, n, 1;\nsetp.lt.u32 p, n, 0x400000;\n@p bra LW;\ntrap;\nLD:\n}" ::"l"(p), "r"(target), "n"((int)SLEEP) : "memory");
}
template <int N>
__device__ __forceinline__ void poll_chunks(uint4 (&v)[N], const uint4* p, int stride) {
  uint32_t m[N];
#pragma unroll
  for (int i = 0; i < N; i++) { m[i] = ~0u; v[i] = make_uint4(0, 0, 0, 0); }
#pragma unroll 1
  for (int n = 0; n < 0x400000; n++) {
    uint32_t a = 0;
#pragma unroll
    for (int i = 0; i < N; i++)
      asm volatile("{\n.reg .pred p;\nsetp.eq.u32 p, %5, 0xFFFFFFFF;\n@p ld.relaxed.gpu.global.v4.u32 {%0,%1,%2,%3}, [%4];\n}"
                   : "+r"(v[i].x), "+r"(v[i].y), "+r"(v[i].z), "+r"(v[i].w) : "l"(p + i * stride), "r"(m[i]) : "memory");
#pragma unroll
    for (int i = 0; i < N; i++) { m[i] = max(max(v[i].x, v[i].y), max(v[i].z, v[i].w)); a = max(a, m[i]); }
    if (__all_sync(~0u, a != 0xFFFFFFFFu)) break;
  }
}
__device__ __forceinline__ void fence_async_all() { asm volatile("fence.proxy.async;" ::: "memory"); }
__device__ __forceinline__ void bar_sync(int id, int n) { asm volatile("bar.sync %0, %1;" ::"r"(id), "r"(n) : "memory"); }
__device__ __forceinline__ void bar_arrive(int id, int n) { asm volatile("bar.arrive %0, %1;" ::"r"(id), "r"(n) : "memory"); }
__device__ __forceinline__ void cluster_arrive() { asm volatile("barrier.cluster.arrive.relaxed.aligned;" ::: "memory"); }
__device__ __forceinline__ void cluster_wait() { asm volatile("barrier.cluster.wait.acquire.aligned;" ::: "memory"); }
__device__ __forceinline__ void fence_gpu() { asm volatile("fence.acq_rel.gpu;" ::: "memory"); }
__device__ __forceinline__ void red_add(unsigned* p, unsigned v) { asm volatile("red.relaxed.gpu.global.add.u32 [%0], %1;" ::"l"(p), "r"(v) : "memory"); }
__device__ __forceinline__ void prefetch_tm(const CUtensorMap* m) { asm volatile("prefetch.tensormap [%0];" ::"l"(m) : "memory"); }

constexpr uint64_t EV_N = 0x1000000000000000ull, EV_F = 0x12F0000000000000ull;
__device__ __forceinline__ void tma_ld2(uint32_t dst, const CUtensorMap* m, uint32_t bar, int c0, int c1, bool ef = false) {
  asm volatile("cp.async.bulk.tensor.2d.shared::cta.global.mbarrier::complete_tx::bytes.L2::cache_hint [%0], [%1, {%3,%4}], [%2], %5;" ::"r"(dst), "l"(m), "r"(bar), "r"(c0), "r"(c1), "l"(ef ? EV_F : EV_N) : "memory");
}
__device__ __forceinline__ void tma_ld3(uint32_t dst, const CUtensorMap* m, uint32_t bar, int c0, int c1, int c2, bool ef = false) {
  asm volatile("cp.async.bulk.tensor.3d.shared::cta.global.mbarrier::complete_tx::bytes.L2::cache_hint [%0], [%1, {%3,%4,%5}], [%2], %6;" ::"r"(dst), "l"(m), "r"(bar), "r"(c0), "r"(c1), "r"(c2), "l"(ef ? EV_F : EV_N) : "memory");
}
__device__ __forceinline__ void tma_ld3_mc(uint32_t dst, const CUtensorMap* m, uint32_t bar, int c0, int c1, int c2, uint16_t mask, bool ef = false) {
  asm volatile("cp.async.bulk.tensor.3d.shared::cluster.global.mbarrier::complete_tx::bytes.multicast::cluster.L2::cache_hint [%0], [%1, {%3,%4,%5}], [%2], %6, %7;" ::"r"(dst), "l"(m), "r"(bar), "r"(c0), "r"(c1), "r"(c2), "h"(mask), "l"(ef ? EV_F : EV_N) : "memory");
}
__device__ __forceinline__ void tma_pf3(const CUtensorMap* m, int c0, int c1, int c2) {
  asm volatile("cp.async.bulk.prefetch.tensor.3d.L2.global [%0, {%1,%2,%3}];" ::"l"(m), "r"(c0), "r"(c1), "r"(c2) : "memory");
}
__device__ __forceinline__ void l2_prefetch(const void* p, uint32_t bytes) { asm volatile("cp.async.bulk.prefetch.L2.global [%0], %1;" ::"l"(p), "r"(bytes) : "memory"); }

__device__ __forceinline__ void wg_fence() { asm volatile("wgmma.fence.sync.aligned;" ::: "memory"); }
__device__ __forceinline__ void wg_commit() { asm volatile("wgmma.commit_group.sync.aligned;" ::: "memory"); }
template <int N> __device__ __forceinline__ void wg_wait() { asm volatile("wgmma.wait_group.sync.aligned %0;" ::"n"(N) : "memory"); }
template <int N> __device__ __forceinline__ void reg_alloc() { asm volatile("setmaxnreg.inc.sync.aligned.u32 %0;" ::"n"(N)); }
template <int N> __device__ __forceinline__ void reg_dealloc() { asm volatile("setmaxnreg.dec.sync.aligned.u32 %0;" ::"n"(N)); }
template <int N> __device__ __forceinline__ void fence_regs(float* d) {
#pragma unroll
  for (int i = 0; i < N; i++) asm volatile("" : "+f"(d[i])::"memory");
}
template <int N> __device__ __forceinline__ void fence_regs(uint32_t* d) {
#pragma unroll
  for (int i = 0; i < N; i++) asm volatile("" : "+r"(d[i])::"memory");
}

__device__ __forceinline__ uint64_t mk_desc(uint32_t addr, uint32_t lbo, uint32_t sbo, uint32_t swz) {
  uint32_t lo = ((addr & 0x3FFFF) >> 4) | ((lbo >> 4) << 16);
  uint32_t hi = (sbo >> 4) | (swz << 30);
  return ((uint64_t)hi << 32) | lo;
}
__device__ __forceinline__ uint64_t desc_add(uint64_t d, uint32_t bytes) {
  uint32_t lo = (uint32_t)d + (bytes >> 4);
  return (d & 0xFFFFFFFF00000000ull) | lo;
}

#define R8(b) "+f"(d[b + 0]), "+f"(d[b + 1]), "+f"(d[b + 2]), "+f"(d[b + 3]), "+f"(d[b + 4]), "+f"(d[b + 5]), "+f"(d[b + 6]), "+f"(d[b + 7])
#define REGS32 "%0,%1,%2,%3,%4,%5,%6,%7,%8,%9,%10,%11,%12,%13,%14,%15,%16,%17,%18,%19,%20,%21,%22,%23,%24,%25,%26,%27,%28,%29,%30,%31"
#define REGS64 REGS32 ",%32,%33,%34,%35,%36,%37,%38,%39,%40,%41,%42,%43,%44,%45,%46,%47,%48,%49,%50,%51,%52,%53,%54,%55,%56,%57,%58,%59,%60,%61,%62,%63"
#define REGS128 REGS64 ",%64,%65,%66,%67,%68,%69,%70,%71,%72,%73,%74,%75,%76,%77,%78,%79,%80,%81,%82,%83,%84,%85,%86,%87,%88,%89,%90,%91,%92,%93,%94,%95," \
               "%96,%97,%98,%99,%100,%101,%102,%103,%104,%105,%106,%107,%108,%109,%110,%111,%112,%113,%114,%115,%116,%117,%118,%119,%120,%121,%122,%123,%124,%125,%126,%127"

template <int TB>
__device__ __forceinline__ void mma_n256_ss(float (&d)[128], uint64_t a, uint64_t b, int acc) {
  asm volatile("{\n.reg .pred p;\nsetp.ne.b32 p, %130, 0;\n"
               "wgmma.mma_async.sync.aligned.m64n256k16.f32.bf16.bf16 {" REGS128 "}, %128, %129, p, 1, 1, 0, %131;\n}\n"
               : R8(0), R8(8), R8(16), R8(24), R8(32), R8(40), R8(48), R8(56), R8(64), R8(72), R8(80), R8(88), R8(96), R8(104), R8(112), R8(120)
               : "l"(a), "l"(b), "r"(acc), "n"(TB));
}
template <int TB>
__device__ __forceinline__ void mma_n128_ss(float* d, uint64_t a, uint64_t b, int acc) {
  asm volatile("{\n.reg .pred p;\nsetp.ne.b32 p, %66, 0;\n"
               "wgmma.mma_async.sync.aligned.m64n128k16.f32.bf16.bf16 {" REGS64 "}, %64, %65, p, 1, 1, 0, %67;\n}\n"
               : R8(0), R8(8), R8(16), R8(24), R8(32), R8(40), R8(48), R8(56)
               : "l"(a), "l"(b), "r"(acc), "n"(TB));
}
template <int TB>
__device__ __forceinline__ void mma_n128_rs(float* d, const uint32_t* a, uint64_t b, int acc) {
  asm volatile("{\n.reg .pred p;\nsetp.ne.b32 p, %69, 0;\n"
               "wgmma.mma_async.sync.aligned.m64n128k16.f32.bf16.bf16 {" REGS64 "}, {%64,%65,%66,%67}, %68, p, 1, 1, %70;\n}\n"
               : R8(0), R8(8), R8(16), R8(24), R8(32), R8(40), R8(48), R8(56)
               : "r"(a[0]), "r"(a[1]), "r"(a[2]), "r"(a[3]), "l"(b), "r"(acc), "n"(TB));
}
__device__ __forceinline__ void mma_n64_rs(float* d, const uint32_t* a, uint64_t b, int acc) {
  asm volatile("{\n.reg .pred p;\nsetp.ne.b32 p, %37, 0;\n"
               "wgmma.mma_async.sync.aligned.m64n64k16.f32.bf16.bf16 {" REGS32 "}, {%32,%33,%34,%35}, %36, p, 1, 1, 0;\n}\n"
               : R8(0), R8(8), R8(16), R8(24)
               : "r"(a[0]), "r"(a[1]), "r"(a[2]), "r"(a[3]), "l"(b), "r"(acc));
}
#define W8(b) "=f"(d[b + 0]), "=f"(d[b + 1]), "=f"(d[b + 2]), "=f"(d[b + 3]), "=f"(d[b + 4]), "=f"(d[b + 5]), "=f"(d[b + 6]), "=f"(d[b + 7])
__device__ __forceinline__ void mma_n128_rs0(float* d, const uint32_t* a, uint64_t b) {
  asm volatile("wgmma.mma_async.sync.aligned.m64n128k16.f32.bf16.bf16 {" REGS64 "}, {%64,%65,%66,%67}, %68, 0, 1, 1, 0;\n"
               : W8(0), W8(8), W8(16), W8(24), W8(32), W8(40), W8(48), W8(56)
               : "r"(a[0]), "r"(a[1]), "r"(a[2]), "r"(a[3]), "l"(b));
}
__device__ __forceinline__ void mma_n64_rs0(float* d, const uint32_t* a, uint64_t b) {
  asm volatile("wgmma.mma_async.sync.aligned.m64n64k16.f32.bf16.bf16 {" REGS32 "}, {%32,%33,%34,%35}, %36, 0, 1, 1, 0;\n"
               : W8(0), W8(8), W8(16), W8(24)
               : "r"(a[0]), "r"(a[1]), "r"(a[2]), "r"(a[3]), "l"(b));
}
__device__ __forceinline__ uint32_t pack_bf16(float lo, float hi) {
  uint32_t r;
  asm("cvt.rn.bf16x2.f32 %0, %1, %2;" : "=r"(r) : "f"(hi), "f"(lo));
  return r;
}
__device__ __forceinline__ float bf_lo(uint32_t v) { return __uint_as_float(v << 16); }
__device__ __forceinline__ float bf_hi(uint32_t v) { return __uint_as_float(v & 0xFFFF0000u); }
__device__ __forceinline__ float bf_round(float v) { return bf_lo(pack_bf16(v, v)); }
__device__ __forceinline__ void stsm4(uint32_t addr, uint32_t r0, uint32_t r1, uint32_t r2, uint32_t r3) {
  asm volatile("stmatrix.sync.aligned.m8n8.x4.shared.b16 [%0], {%1,%2,%3,%4};" ::"r"(addr), "r"(r0), "r"(r1), "r"(r2), "r"(r3) : "memory");
}
__device__ __forceinline__ uint4 lds128(uint32_t addr) {
  uint4 v;
  asm volatile("ld.shared.v4.u32 {%0,%1,%2,%3}, [%4];" : "=r"(v.x), "=r"(v.y), "=r"(v.z), "=r"(v.w) : "r"(addr));
  return v;
}
__device__ __forceinline__ float ex2(float x) {
  float y;
  asm("ex2.approx.ftz.f32 %0, %1;" : "=f"(y) : "f"(x));
  return y;
}
__device__ __forceinline__ void pin_order(float v, uint32_t dummy) {
  asm volatile("{\n.reg .pred p;\nsetp.eq.b32 p, %0, 0xFFFFFFFF;\n@p st.shared.b32 [%1], %0;\n}" ::"r"(__float_as_uint(v)), "r"(dummy) : "memory");
}
__device__ __forceinline__ float sigmoid(float x) {
  float y;
  asm("rcp.approx.ftz.f32 %0, %1;" : "=f"(y) : "f"(1.f + ex2(x * -1.4426950408889634f)));
  return y;
}
__device__ __forceinline__ void sched_fence(uint32_t dummy) {
  asm volatile("{\n.reg .pred p;\n.reg .u32 c;\nsetp.eq.b32 p, %0, 0xFFFFFFFF;\nmov.u32 c, %%clock;\n@p st.shared.b32 [%0], c;\n}" ::"r"(dummy) : "memory");
}
__device__ __forceinline__ void idle(int n) {
  asm volatile("{\n.reg .pred p;\n.reg .u32 a, b;\nmov.u32 a, %%clock;\nLI:\nmov.u32 b, %%clock;\nsub.u32 b, b, a;\nsetp.lt.u32 p, b, %0;\n@p bra LI;\n}" ::"r"(n) : "memory");
}
__device__ __forceinline__ void stage_store_128(uint32_t base, int lane, const uint32_t* pk) {
  const int row = (lane & 7) + ((lane >> 3) & 1) * 8;
  const uint32_t rb = base + row * 128;
  const int hi = lane >> 4;
#pragma unroll
  for (int j = 0; j < 8; j++) {
    const int chunk = 2 * j + hi;
    const uint32_t a = rb + (j >> 2) * 8192 + (((chunk & 7) ^ (lane & 7)) << 4);
    stsm4(a, pk[4 * j + 0], pk[4 * j + 1], pk[4 * j + 2], pk[4 * j + 3]);
  }
}
__device__ __forceinline__ void ln_round(float mean, float var, float& m_bf, float& inv_s) {
  const uint32_t mv = pack_bf16(mean, var);
  m_bf = bf_lo(mv);
  float sq, rc;
  asm("sqrt.approx.ftz.f32 %0, %1;" : "=f"(sq) : "f"(bf_round(bf_hi(mv) + 1e-5f)));
  asm("rcp.approx.ftz.f32 %0, %1;" : "=f"(rc) : "f"(bf_round(sq)));
  inv_s = rc;
}
__device__ __forceinline__ uint32_t hadd2_bf(uint32_t a, uint32_t b) {
  uint32_t r;
  asm("add.rn.bf16x2 %0, %1, %2;" : "=r"(r) : "r"(a), "r"(b));
  return r;
}
__device__ __forceinline__ uint32_t ln_apply(uint32_t h, uint32_t nm2, float inv_s) {
  const uint32_t d = hadd2_bf(h, nm2);
  return pack_bf16(bf_lo(d) * inv_s, bf_hi(d) * inv_s);
}
__device__ __forceinline__ void ldsm4(uint32_t* r, uint32_t addr) {
  asm volatile("ldmatrix.sync.aligned.m8n8.x4.shared.b16 {%0,%1,%2,%3}, [%4];" : "=r"(r[0]), "=r"(r[1]), "=r"(r[2]), "=r"(r[3]) : "r"(addr) : "memory");
}
__device__ __forceinline__ void mma16816(float* d, uint32_t a0, uint32_t a1, uint32_t a2, uint32_t a3, uint32_t b0, uint32_t b1) {
  asm volatile("mma.sync.aligned.m16n8k16.row.col.f32.bf16.bf16.f32 {%0,%1,%2,%3}, {%4,%5,%6,%7}, {%8,%9}, {%0,%1,%2,%3};"
               : "+f"(d[0]), "+f"(d[1]), "+f"(d[2]), "+f"(d[3]) : "r"(a0), "r"(a1), "r"(a2), "r"(a3), "r"(b0), "r"(b1));
}

template <class F>
__device__ __forceinline__ void unroll8(F f) {
  f(std::integral_constant<int, 0>{}); f(std::integral_constant<int, 1>{}); f(std::integral_constant<int, 2>{}); f(std::integral_constant<int, 3>{});
  f(std::integral_constant<int, 4>{}); f(std::integral_constant<int, 5>{}); f(std::integral_constant<int, 6>{}); f(std::integral_constant<int, 7>{});
}

constexpr float AT_C = 0.08838834764831845f * 1.4426950408889634f;
constexpr float AT_LO = 0x1p-40f, AT_HI = 0x1p40f;
constexpr int AT_R1 = 48;
template <int I0, int I1>
__device__ __forceinline__ void at_exp(float* S) {
#pragma unroll
  for (int i = I0; i < I1; i++) asm volatile("ex2.approx.ftz.f32 %0, %0;" : "+f"(S[i]));
}
template <int I0, int I1>
__device__ __forceinline__ void at_fin(const float* S, uint32_t* P) {
#pragma unroll
  for (int i = I0; i < I1; i += 4) {
    P[i / 2] = pack_bf16(S[i], S[i + 1]); P[i / 2 + 1] = pack_bf16(S[i + 2], S[i + 3]);
  }
}
__device__ __forceinline__ void at_sum(const uint32_t* P, bool half, float& l0, float& l1) {
  uint32_t u[4];
#pragma unroll
  for (int r = 0; r < 4; r++) {
    const uint32_t* q = P + (r >> 1) * 16 + (r & 1);
    u[r] = hadd2_bf(hadd2_bf(hadd2_bf(q[0], q[2]), hadd2_bf(q[4], q[6])), hadd2_bf(hadd2_bf(q[8], q[10]), hadd2_bf(q[12], q[14])));
  }
  u[0] = hadd2_bf(u[0], half ? 0u : u[2]);
  u[1] = hadd2_bf(u[1], half ? 0u : u[3]);
  l0 += bf_lo(u[0]) + bf_hi(u[0]);
  l1 += bf_lo(u[1]) + bf_hi(u[1]);
}
template <int j>
__device__ __forceinline__ void at_mask1(float* S, int d) {
  float dummy0 = 0.f, dummy1 = 0.f;
  float& lo0 = j < 7 ? S[4 * (j < 7 ? j + 1 : j) + 2] : dummy0;
  float& lo1 = j < 7 ? S[4 * (j < 7 ? j + 1 : j) + 3] : dummy1;
  asm("{\n.reg .pred p, q;\nsetp.lt.s32 p, %4, %5;\nsetp.le.s32 q, %4, %5;\n"
      "@p add.f32 %0, %0, 0fFF800000;\n@q add.f32 %1, %1, 0fFF800000;\n@p add.f32 %2, %2, 0fFF800000;\n@q add.f32 %3, %3, 0fFF800000;\n}"
      : "+f"(S[4 * j]), "+f"(S[4 * j + 1]), "+f"(lo0), "+f"(lo1) : "r"(d), "r"(8 * j));
}
__device__ __forceinline__ void at_mask(float* S, int r, int lane) {
  unroll8([&](auto jc) { at_mask1<decltype(jc)::value>(S, r + (lane >> 2) - (lane & 3) * 2); });
}
__device__ __forceinline__ uint32_t ldg32(const __nv_bfloat16* p) { return __ldcg(reinterpret_cast<const uint32_t*>(p)); }
__device__ __forceinline__ uint32_t ldg16x2(const __nv_bfloat16* p, int stride) {
  return (uint32_t)__ldcg(reinterpret_cast<const unsigned short*>(p)) | ((uint32_t)__ldcg(reinterpret_cast<const unsigned short*>(p + stride)) << 16);
}
__device__ __forceinline__ void slow_tile(float* O, uint32_t* Q, float& l0, float& l1, const __nv_bfloat16* wq, int row0, int head, int lane, uint32_t dummy) {
  const int r = lane >> 2, q = lane & 3;
#pragma unroll
  for (int i = 0; i < 64; i++) O[i] = 0.f;
  {
    const __nv_bfloat16* xa = g_xn + (size_t)(row0 + r) * DM + 2 * q;
    const __nv_bfloat16* wb = wq + (size_t)(2 * q) * NQ + head * HD + (r >> 1) * 8 + (r & 1);
#pragma unroll 1
    for (int k = 0; k < DM; k += 16) {
      const uint32_t a0 = ldg32(xa + k), a1 = ldg32(xa + k + 8 * DM), a2 = ldg32(xa + k + 8), a3 = ldg32(xa + k + 8 * DM + 8);
#pragma unroll
      for (int j = 0; j < 16; j++) {
        const __nv_bfloat16* wp = wb + (size_t)k * NQ + (j >> 2) * 32 + (j & 3) * 2;
        mma16816(O + 4 * j, a0, a1, a2, a3, ldg16x2(wp, NQ), ldg16x2(wp + 8 * NQ, NQ));
        if (j == 7) sched_fence(dummy);
      }
    }
  }
#pragma unroll
  for (int i = 0; i < 32; i++) Q[i] = pack_bf16(O[2 * i], O[2 * i + 1]);
#pragma unroll
  for (int i = 0; i < 64; i++) O[i] = 0.f;
  float m0 = -INFINITY, m1 = -INFINITY;
  l0 = l1 = 0.f;
#pragma unroll 1
  for (int kv = 0; kv <= row0; kv += 16) {
    float s[8] = {0.f, 0.f, 0.f, 0.f, 0.f, 0.f, 0.f, 0.f};
    const __nv_bfloat16* kp = g_qkv + (size_t)(SEQ + kv + r) * NQ + head * HD + 2 * q;
#pragma unroll
    for (int k = 0; k < 8; k++) {
      mma16816(s, Q[4 * k], Q[4 * k + 1], Q[4 * k + 2], Q[4 * k + 3], ldg32(kp + 16 * k), ldg32(kp + 16 * k + 8));
      mma16816(s + 4, Q[4 * k], Q[4 * k + 1], Q[4 * k + 2], Q[4 * k + 3], ldg32(kp + 8 * NQ + 16 * k), ldg32(kp + 8 * NQ + 16 * k + 8));
    }
#pragma unroll
    for (int i = 0; i < 8; i++)
      if (kv + (i >> 2) * 8 + 2 * q + (i & 1) > row0 + r + (i & 2) * 4) s[i] = -INFINITY;
    float a = fmaxf(fmaxf(fmaxf(s[0], s[1]), fmaxf(s[4], s[5])), m0), b = fmaxf(fmaxf(fmaxf(s[2], s[3]), fmaxf(s[6], s[7])), m1);
    a = fmaxf(a, __shfl_xor_sync(~0u, a, 1)); b = fmaxf(b, __shfl_xor_sync(~0u, b, 1));
    a = fmaxf(a, __shfl_xor_sync(~0u, a, 2)); b = fmaxf(b, __shfl_xor_sync(~0u, b, 2));
    const float c0 = ex2(m0 - a), c1 = ex2(m1 - b);
    m0 = a; m1 = b;
#pragma unroll
    for (int i = 0; i < 8; i++) s[i] = ex2(s[i] - ((i & 2) ? b : a));
    l0 = l0 * c0 + (s[0] + s[1]) + (s[4] + s[5]);
    l1 = l1 * c1 + (s[2] + s[3]) + (s[6] + s[7]);
    sched_fence(dummy);
    const uint32_t p0 = pack_bf16(s[0], s[1]), p1 = pack_bf16(s[2], s[3]), p2 = pack_bf16(s[4], s[5]), p3 = pack_bf16(s[6], s[7]);
    const __nv_bfloat16* vp = g_qkv + (size_t)(2 * SEQ + kv + 2 * q) * NQ + head * HD + r;
#pragma unroll
    for (int j = 0; j < 16; j++) {
      O[4 * j] *= c0; O[4 * j + 1] *= c0; O[4 * j + 2] *= c1; O[4 * j + 3] *= c1;
      mma16816(O + 4 * j, p0, p1, p2, p3, ldg16x2(vp + 8 * j, NQ), ldg16x2(vp + 8 * NQ + 8 * j, NQ));
      if (j == 7) sched_fence(dummy);
    }
  }
}

constexpr int P1_STAGE = 49152;
constexpr int SLOT = 32768;
constexpr int OFF_R3 = 0;
constexpr int OFF_BAR = 229376;
constexpr int OFF_MISC = OFF_BAR + 8 * 58;
constexpr int SMEM_BYTES = OFF_MISC + 2080 + TL_BYTES;
enum : int {
  B_FULL1 = 0, B_KF = 4, B_VF = 6, B_FULL3 = 8, B_XF = 14, B_LN = 15, B_DEP = 16, B_OUT2 = 22, B_FIN = 23, B_SET2 = 25, B_QP = 26, B_WF2 = 29,
  B_WF = 30, B_WR = 31,
  B_XE = 33, B_PUB = 34, B_OUT = 40, B_OUT3 = 41,
  B_EMPTY1 = 42, B_KE = 46, B_VE = 48, B_EMPTY3 = 50, B_WE = 56, B_NUM = 57
};
constexpr int OFF_STG = SLOT, SL_SCR = 2;
constexpr int PRE = 3;
constexpr int LN_PF = 5, LN_PFN = 2, LN_LD = 4;
constexpr int WQ_0 = 18, WQ_D = 2;
constexpr int KV_PF = 10, W_G0 = 23;
constexpr int X_KB = 20, G_KB = 35;
constexpr int SL_NS = 600, SET_NS = 50;
constexpr int OUT_CLK = 500, Y_CLK = 400;
struct Params {
  CUtensorMap xn, ckv, wq, wk, wv, kv, ctx_ld, ctx_st, wo, x, wd, wg, wu, out;
};

__global__ void __cluster_dims__(2, 1, 1) __launch_bounds__(384, 1)
fused_kernel(const __nv_bfloat16* __restrict__ x, const __nv_bfloat16* __restrict__ wq, const __nv_bfloat16* __restrict__ w_r,
             __nv_bfloat16* __restrict__ out, const __grid_constant__ Params p) {
  extern __shared__ __align__(1024) uint8_t sp[];
  const uint32_t sb = s2u(sp);
  const uint32_t bar = sb + OFF_BAR;
  auto B = [&](int i) { return bar + 8 * i; };
  const int tid = threadIdx.x, warp = __shfl_sync(~0u, tid >> 5, 0), wg = warp >> 2, lane = tid & 31;
  const int cta = blockIdx.x, rank = cta & 1, cl = cta >> 1;
  const int mp = cl < 4 ? 1 : (cl < 36 ? (cl & 7) : (0x3207654 >> (4 * ((cl - 36) % 7))) & 7);
  const int gq = cl < 4 ? 4 + cl : (cl < 36 ? (cl - 4) >> 3 : 4 + (cl - 36) / 7);
  const int mt = 2 * mp + rank;
  const int ti = (gq & 3) * 2 + rank, hh = mp * 2 + (gq >> 2);
  const int rid = mt * 8 + gq;
  const int fid = mt * 7 + gq - 1;
  const bool ffn = gq > 0;
  uint4* const xr = g_xr + rid * XR_SIZE;
  TL_INIT();
  TL(0, 0, tid == 128);
  if (warp == 0) {
    if (elect_one()) {
#pragma unroll
      for (int kb = 0; kb < PRE; kb++) mbar_init(B(B_FULL1 + kb), 1);
      asm volatile("fence.mbarrier_init.release.cluster;" ::: "memory");
    }
    __syncwarp();
    cluster_arrive();
    if (elect_one()) {
#pragma unroll
      for (int kb = 0; kb < PRE; kb++) {
        mbar_expect(B(B_FULL1 + kb), P1_STAGE);
        tma_ld2(sb + kb * P1_STAGE, &p.ckv, B(B_FULL1 + kb), kb * 64, mt * 128);
        tma_ld3(sb + kb * P1_STAGE + 16384 + rank * 16384, &p.wk, B(B_FULL1 + kb), 0, kb * 64, (gq + 8) * 4 + rank * 2);
        tma_ld3(sb + kb * P1_STAGE + 32768 - rank * 16384, &p.wk, B(B_FULL1 + kb), 0, kb * 64, (gq + 8) * 4 + 2 - rank * 2);
      }
    }
  } else if (elect_one()) {
#pragma unroll 1
    for (int i = PRE + warp - 1; i < B_NUM; i += 11)
      mbar_init(B(i), i >= B_EMPTY1 ? 16 : (i >= B_XE ? 8 : (i >= B_WF ? 2 : 1)));
    asm volatile("fence.mbarrier_init.release.cluster;" ::: "memory");
  }
  __syncwarp();
  if (warp) cluster_arrive();
  if (wg == 0) {
    reg_dealloc<40>();
    if (warp == 1 && elect_one()) {
      if (mt >= 2 * PRE) tma_pf3(&p.wk, 0, mp * 64, (gq + 8) * 4 + rank * 2);
      if (gq >= PRE) asm volatile("cp.async.bulk.prefetch.tensor.2d.L2.global [%0, {%1,%2}];" ::"l"(&p.ckv), "r"(gq * 64), "r"(mt * 128) : "memory");
    } else if (warp == 2 && elect_one()) {
      prefetch_tm(&p.wv); prefetch_tm(&p.wq); prefetch_tm(&p.xn);
    }
    __syncwarp();
    cluster_wait();
    if (warp == 0) {
      int st = PRE; uint32_t ph = 1;
#pragma unroll 1
      for (int t = 0; t < 6; t++) {
        const CUtensorMap* ma = t >= 4 ? &p.xn : &p.ckv;
        const CUtensorMap* mb = t >= 4 ? &p.wq : ((t & 1) ? &p.wv : &p.wk);
        const int nk = t >= 4 ? 16 : 8;
        const int row = (t < 4 ? mt : (t == 4 ? 15 - ti : ti)) * 128;
        const int col = t < 4 ? (gq + ((t >> 1) ^ 1) * 8) * 4 + rank * 2 : (hh + rank * 16) * 2;
        if (t >= 4) mbar_wait(B(B_DEP + t - 4), 0);
#pragma unroll 1
        for (int kb = t ? 0 : PRE; kb < nk; kb++) {
          const uint32_t d = sb + st * P1_STAGE, fb = B(B_FULL1 + st);
          const int n = t * 8 + kb;
          const bool la = t == 0 || t >= 4 || (kb & 5) == 5, lb = t < 5 || kb >= 4;
          const int k0 = (t == 5 ? (kb + 12) & 15 : kb ^ ((t & kb & 1) * 4)) * 64;
          mbar_wait_c(B(B_EMPTY1 + st), ph);
          if (elect_one()) {
            mbar_expect(fb, la * 16384 + lb * 32768);
            if (la) tma_ld2(t == 0 && (kb & 5) == 4 ? sb + 6 * SLOT + (kb & 2) * 8192 : d, ma, fb, k0, row);
            if (lb) tma_ld3_mc(d + 16384 + rank * 16384, mb, fb, 0, k0, col, 3);
          }
          if (t < 5 && elect_one()) {
            if (n >= LN_PF && n < LN_PF + LN_PFN) l2_prefetch(x + (size_t)cta * 16 * DM + (n - LN_PF) * (16 * DM / LN_PFN), 32768 / LN_PFN);
            if (n == LN_LD) mbar_arrive(B(B_LN));
            if (t < 3 && kb == (t ? 0 : 4)) tma_pf3((t & 1) ? &p.wk : &p.wv, 0, mp * 64, (gq + (((t + 1) >> 1) ^ 1) * 8) * 4 + rank * 2);
            if (n >= WQ_0 && n < WQ_0 + 4 * WQ_D && (n - WQ_0) % WQ_D == 0) tma_pf3(&p.wq, 0, ((n - WQ_0) / WQ_D * 4 + (gq & 3)) * 64, (hh + rank * 16) * 2);
          }
          if (++st == 4) { st = 0; ph ^= 1; }
        }
      }
      if (elect_one()) { prefetch_tm(&p.kv); prefetch_tm(&p.ctx_ld); prefetch_tm(&p.wo); prefetch_tm(&p.wg); prefetch_tm(&p.wu); }
      auto load_kv = [&](int g, int isv) {
        const int h2 = g >= 17, sx = g - 17 * h2, n1 = h2 ? ti + 1 : 16 - ti;
        const int row = (1 + isv) * SEQ + (sx < n1 ? sx : 16 - sx) * 128, col = (hh + 16 * h2) * 2;
        const uint32_t d = sb + (isv ? 2 + 2 * (g & 1) : (g & 1)) * SLOT, fb = B(B_KF + 2 * isv + (g & 1));
        const bool ef = sx >= n1 || sx >= 8;
        const bool shared = sx != (h2 ? (ti & 6) + 1 : 15 - (ti & 6));
        const int n3 = g - KV_PF;
        const int pb = ti >= 6 && n3 >= 0 && n3 < 16 ? ((n3 & 1) || !n3 ? (n3 + 1) >> 1 : 16 - (n3 >> 1)) : -1;
        mbar_wait_c(g < 2 ? B(B_EMPTY1 + (isv ? 1 + 2 * g : g)) : B(B_KE + 2 * isv + (g & 1)), g < 2 ? 1 : ((g >> 1) & 1) ^ 1);
        if (elect_one()) {
          mbar_expect(fb, SLOT);
          if (shared) {
            tma_ld3_mc(d + rank * 16384, &p.kv, fb, 0, row, col + rank, 3, ef);
          } else {
            tma_ld3(d, &p.kv, fb, 0, row, col, ef);
            tma_ld3(d + 16384, &p.kv, fb, 0, row, col + 1, ef);
          }
          if (pb >= 0) tma_pf3(&p.kv, 0, (1 + isv) * SEQ + pb * 128, (hh + 16) * 2 + rank);
        }
      };
      int nw = ffn ? 0 : 12;
      auto load_w = [&]() {
        const int c = nw < 8 ? (nw >> 2) + (nw & 2) : nw >> 1;
        if (elect_one()) {
          if (!(nw & 3)) mbar_expect(B(B_WF - (nw >> 3)), 32768);
          tma_ld2(sb + (c < 2 ? 3 : 4) * SLOT + c * 16384 + (nw & 1) * 8192, (nw & 1) ? &p.wg : &p.wu, B(B_WF - (nw >> 3)), fid * 32, c * 128, true);
        }
        nw++;
      };
#pragma unroll 1
      for (int g = 0; g < 34; g++) {
        if (g == 0 || g == KV_PF) mbar_wait(B(B_DEP + 2 + (g > 0)), 0);
        load_kv(g, 0);
        if (g > 0) load_kv(g - 1, 1);
        if (g >= W_G0 && nw < 12 && __all_sync(~0u, mbar_test(B(B_QP + (nw >> 2)), 0))) load_w();
      }
      load_kv(33, 1);
#pragma unroll 1
      while (nw < 12) { mbar_wait(B(B_QP + (nw >> 2)), 0); load_w(); }
      if (elect_one()) { prefetch_tm(&p.wd); prefetch_tm(&p.x); prefetch_tm(&p.out); }
      auto load3 = [&](int kb, int sl) {
        if (elect_one()) {
          mbar_expect(B(B_FULL3 + sl), SLOT);
          tma_ld2(sb + OFF_R3 + sl * SLOT, &p.ctx_ld, B(B_FULL3 + sl), kb * 64, mt * 128, true);
          tma_ld3_mc(sb + OFF_R3 + sl * SLOT + 16384 + rank * 8192, &p.wo, B(B_FULL3 + sl), 0, kb * 64, gq * 2 + rank, 3);
        }
      };
      mbar_wait(B(B_DEP + 4), 0);
#pragma unroll
      for (int kb = 0; kb < 5; kb++) {
        mbar_wait_c(B(kb == 3 ? B_WE : (kb == 4 ? B_VE + 1 : B_KE + kb)), 0);
        load3(kb, kb);
      }
      if (elect_one()) mbar_arrive(B(B_FULL3 + 5));
#pragma unroll 1
      for (int r = 1; r < 11; r++) {
#pragma unroll
        for (int j = 0; j < 6; j++) {
          if (j == 5 && r == 10) break;
          if (j == 3 && r == 5) mbar_wait(B(B_DEP + 5), 0);
          mbar_wait_c(B(B_EMPTY3 + j), ~r & 1);
          load3(r * 6 + j - 1, j);
          if (j == 5 && r == 9 && elect_one()) l2_prefetch(xr, XR_CAND * 16);
        }
      }
      if (ffn) {
#pragma unroll
        for (int j = 1; j >= 0; j--) {
          mbar_wait(B(B_EMPTY3 + 5 * j), j);
          if (elect_one()) {
            mbar_expect(B(B_FULL3 + 5 * j), SLOT);
            tma_ld3(sb + OFF_R3 + 5 * j * SLOT, &p.wd, B(B_FULL3 + 5 * j), 0, fid * 32, 8 * j, true);
          }
        }
      }
    } else {
      if (warp >= 2) {
#pragma unroll 1
        for (int i = tid - 64; i < XR_CAND; i += 64) xr[i] = make_uint4(~0u, ~0u, ~0u, ~0u);
        if (warp == 2) { __syncwarp(); if (lane == 0) mbar_arrive(B(B_WR)); }
      }
      if (warp == 3) {
        float ws = 0.f;
#pragma unroll
        for (int j = 0; j < 4; j++) {
          const uint4 q = __ldg(reinterpret_cast<const uint4*>(w_r) + j * 32 + lane);
          ws += bf_lo(q.x) + bf_hi(q.x) + bf_lo(q.y) + bf_hi(q.y) + bf_lo(q.z) + bf_hi(q.z) + bf_lo(q.w) + bf_hi(q.w);
        }
#pragma unroll
        for (int o = 16; o; o >>= 1) ws += __shfl_xor_sync(~0u, ws, o);
        uint2* tab = reinterpret_cast<uint2*>(sp + OFF_MISC + 512);
        tab[lane] = make_uint2(0x3F803F80u, 0x3F803F80u);
        tab[32 + lane] = __ldg(reinterpret_cast<const uint2*>(w_r + gq * 128) + lane);
        if (lane == 0) *reinterpret_cast<float*>(sp + OFF_MISC + 1024) = ws;
        __syncwarp();
        if (lane == 0) mbar_arrive(B(B_WR));
      }
      if (tid == 32) TS(0);
      mbar_wait(B(B_LN), 0);
      const uint4* src = reinterpret_cast<const uint4*>(x + (size_t)(cta * 16 + warp - 1) * DM) + lane;
      uint4* dst = reinterpret_cast<uint4*>(g_xn + (size_t)(cta * 16 + warp - 1) * DM) + lane;
      uint4 v[4];
#pragma unroll
      for (int j = 0; j < 4; j++) v[j] = __ldcs(src + j * 32);
#pragma unroll 1
      for (int r = warp - 1; r < 16; r += 3) {
        float a0 = 0.f, a1 = 0.f, b0 = 0.f, b1 = 0.f;
#pragma unroll
        for (int j = 0; j < 4; j++) {
          const uint32_t u[4] = {v[j].x, v[j].y, v[j].z, v[j].w};
#pragma unroll
          for (int i = 0; i < 4; i++) { const float a = bf_lo(u[i]), b = bf_hi(u[i]); a0 += a; a1 += b; b0 = fmaf(a, a, b0); b1 = fmaf(b, b, b1); }
        }
        a0 += a1; b0 += b1;
#pragma unroll
        for (int o = 16; o; o >>= 1) { a0 += __shfl_xor_sync(~0u, a0, o); b0 += __shfl_xor_sync(~0u, b0, o); }
        const float mean = a0 * (1.f / DM);
        float mb, inv;
        ln_round(mean, fmaxf(fmaf(b0, 1.f / DM, -mean * mean), 0.f), mb, inv);
        inv *= AT_C;
        const uint32_t nm2 = pack_bf16(-mb, -mb);
        src += 384;
#pragma unroll
        for (int j = 0; j < 4; j++) {
          dst[j * 32] = make_uint4(ln_apply(v[j].x, nm2, inv), ln_apply(v[j].y, nm2, inv), ln_apply(v[j].z, nm2, inv), ln_apply(v[j].w, nm2, inv));
          sched_fence(sb + lane);
          if (r < 13) v[j] = __ldcs(src + j * 32);
        }
        dst += 384;
      }
      __syncwarp();
      if (lane == 0) {
        fence_gpu();
        red_add(&g_cnt[C_LN + (cta >> 3)], 1);
      }
      TL(3, warp, lane == 0);
      __syncwarp();
      cluster_arrive();
      if (warp == 3) {
        if (lane == 0) {
#pragma unroll 1
          for (int i = 0; i < 6; i++) {
            const int c = i < 2 ? C_LN + (i ? ti : 15 - ti) : (i < 4 ? C_QKV + (i - 2) * 8 + mp : C_CTX + (i - 4) * 16 + mt);
            spin_until_ge<true>(&g_cnt[c], i < 2 ? 24 : 16);
            fence_async_all();
            mbar_arrive(B(B_DEP + i));
            TL(3, 4 + i, true);
          }
        }
      } else if (warp == 1 && elect_one()) {
        mbar_wait(B(B_WR), 0);
#pragma unroll 1
        for (int i = 0; i < 6; i++) {
          const int c = i < 2 ? C_QKV + gq + (i ^ 1) * 8 : C_CTX + (i >> 2) * 16 + ((i == 3 || i == 4) ? ti : 15 - ti);
          mbar_wait(B(B_PUB + i), 0);
          if (i >= 2 && i < 5) {
            asm volatile("fence.proxy.async.shared::cta;" ::: "memory");
#pragma unroll 1
            for (int n = 0; n < 8; n++) {
              const int h = n >> 2, a = n & 3;
              asm volatile("cp.async.bulk.tensor.3d.global.shared::cta.bulk_group [%0, {%2,%3,%4}], [%1];" ::"l"(&p.ctx_st),
                           "r"(sb + (i == 4 ? 6 * SLOT + h * 16384 : (3 + 2 * h) * SLOT + (i - 2) * 16384) + a * 4096),
                           "r"(0), "r"((i == 2 ? 15 - ti : ti) * 128 + h * 64), "r"((hh + (i >> 2) * 16) * 4 + a) : "memory");
              asm volatile("cp.async.bulk.commit_group;\ncp.async.bulk.wait_group.read 0;" ::: "memory");
            }
            mbar_arrive(B(B_QP + i - 2));
            asm volatile("cp.async.bulk.wait_group 0;" ::: "memory");
          }
          fence_gpu();
          red_add(&g_cnt[c], 1);
          TS(1 + i);
        }
      }
      if (warp == 2) {
#pragma unroll 1
        for (int n = 0; n < 8; n++) {
          if (!(n & 3)) mbar_wait(B(B_XE), n >> 2);
          if ((n < 4 || ffn) && elect_one()) {
            const uint32_t fb = B(n < 4 ? B_XF : B_WF2), d = sb + 6 * SLOT + (n & 3) * 8192;
            if (!(n & 3)) mbar_expect(fb, 32768);
            if (n < 4) tma_ld3(d, &p.x, fb, 0, mt * 128 + (n >> 1) * 64, gq * 2 + (n & 1), true);
            else tma_ld2(d, (n & 1) ? &p.wg : &p.wu, fb, fid * 32, (4 + (n >> 1)) * 128, true);
          }
          __nanosleep(SL_NS);
        }
#pragma unroll 1
        for (int i = XR_CAND + lane; i < XR_SIZE; i += 32) { xr[i] = make_uint4(~0u, ~0u, ~0u, ~0u); __nanosleep(SET_NS); }
        __syncwarp();
        if (lane == 0) { fence_gpu(); mbar_arrive(B(B_SET2)); }
        TL(2, 26, lane == 0);
        __syncwarp();
      }
      __syncwarp();
      if (warp == 3) {
        mbar_wait(B(B_OUT), 0);
        uint4 kv[2];
        poll_chunks(kv, g_xr + ((lane >> 1) * 8 + gq) * XR_SIZE + XR_KEY + (lane & 1) * 2, 1);
        const uint32_t a1 = max(kv[0].x, kv[0].z), a2 = max(min(kv[0].x, kv[0].z), max(kv[0].y, kv[0].w));
        const uint32_t b1 = max(kv[1].x, kv[1].z), b2 = max(min(kv[1].x, kv[1].z), max(kv[1].y, kv[1].w));
        const uint32_t k1 = max(a1, b1), k2 = max(min(a1, b1), max(a2, b2));
        const uint32_t m1 = __reduce_max_sync(~0u, k1);
        const uint32_t m2 = __reduce_max_sync(~0u, k1 == m1 ? k2 : k1);
        auto cand = [&](uint32_t k) { return (((~k >> 7) & 15) * (8 * XR_SIZE) + ((~k >> 4) & 7) * 64) * 16; };
        const uint32_t o1 = cand(m1), o2 = cand(m2) + (((m1 ^ m2) & 0x7FF0) ? 0 : 256);
        if (lane == 0) {
          *reinterpret_cast<uint4*>(sp + OFF_MISC) = make_uint4(m1, m2, o1, o2);
          mbar_arrive(B(B_OUT2));
        }
        const uint32_t key = (lane & 4) ? m2 : m1;
        const uint4* src = g_xr + (((~key >> 7) & 15) * 8 + (rid >> 4)) * XR_SIZE;
        poll_chunks(kv, g_xr + (((lane & 4) ? o2 : o1) >> 4) + (rid >> 4) * XR_SIZE + XR_CAND + (rid & 12) + (lane & 3), 32);
        uint32_t u = key >> 16;
        u = (u & 0x8000u) ? (u & 0x7FFFu) : (~u & 0xFFFFu);
        const float rs = bf_round(sigmoid(__uint_as_float(u << 16)));
        if (lane < 8)
          *reinterpret_cast<uint4*>(sp + OFF_MISC + 128 + lane * 16) = make_uint4((rid & 2) ? ((rid & 1) ? kv[0].w : kv[0].z) : ((rid & 1) ? kv[0].y : kv[0].x),
              (rid & 2) ? ((rid & 1) ? kv[1].w : kv[1].z) : ((rid & 1) ? kv[1].y : kv[1].x), __float_as_uint(rs), 0);
#pragma unroll 1
        for (int n = 0; n < 0x400000; n++) {
          uint32_t v;
          asm volatile("ld.acquire.gpu.global.u32 %0, [%1];" : "=r"(v) : "l"(src + XR_FLAG) : "memory");
          if (__all_sync(~0u, v == 0)) break;
        }
        __syncwarp();
        if (lane == 0) mbar_arrive(B(B_FIN));
      }
      if (warp == 1 && elect_one()) {
        mbar_wait(B(B_OUT3), 0);
        auto owner = [&]() {
          uint2 top;
          asm volatile("ld.shared.v2.u32 {%0,%1}, [%2];" : "=r"(top.x), "=r"(top.y) : "r"(sb + OFF_MISC) : "memory");
          return (0x7FFF - (top.x & 0x7FFF)) >> 7 == mt || (0x7FFF - (top.y & 0x7FFF)) >> 7 == mt;
        };
#pragma unroll 1
        for (int n = 0; n < 4; n++) {
          if (n && !(mbar_test(B(B_OUT2), 0) && owner())) idle(OUT_CLK);
          asm volatile("cp.async.bulk.tensor.2d.global.shared::cta.bulk_group [%0, {%2,%3}], [%1];" ::"l"(&p.out), "r"(sb + OFF_STG + n * 8192),
                       "r"(gq * 128 + (n & 1) * 64), "r"(mt * 128 + (n >> 1) * 64) : "memory");
        }
        asm volatile("cp.async.bulk.commit_group;" ::: "memory");
        mbar_wait(B(B_OUT2), 0);
        if (owner()) {
          asm volatile("cp.async.bulk.wait_group 0;" ::: "memory");
          asm volatile("st.release.gpu.global.u32 [%0], 0;" ::"l"(xr + XR_FLAG) : "memory");
        } else {
          asm volatile("cp.async.bulk.wait_group.read 0;" ::: "memory");
        }
        TL(2, 25, true);
      }
    }
    __syncwarp();
    if (warp == 0) cluster_arrive();
    cluster_wait();
    TL_DUMP();
    if (tid == 32) TS(8);
  } else {
    reg_alloc<232>();
    cluster_wait();
    const int w = wg - 1, cw = warp - 4;
    int lane = lane_id();
    const uint32_t stg = sb + OFF_STG + w * 16384 + (cw & 3) * 2048;
    auto publish = [&](int i) { __syncwarp(); if (lane == 0) mbar_arrive(B(B_PUB + i)); };
    uint32_t rbar;
    asm("mapa.shared::cluster.u32 %0, %1, %2;" : "=r"(rbar) : "r"(bar), "r"(lane & 1));
    auto release2 = [&](int i) { if (lane < 2) asm volatile("mbarrier.arrive.shared::cluster.b64 _, [%0];" ::"r"(rbar + 8 * i) : "memory"); };
    float R[128];
    float O[64], acc[64];
    uint32_t pk[64];
    uint32_t* const Q = pk;
    uint32_t P[32];
    auto packed = [&](int i) {
      const float* v = R + 16 * (i >> 1) + 2 * (i & 1);
      return make_uint4(pack_bf16(v[0], v[1]), pack_bf16(v[4], v[5]), pack_bf16(v[8], v[9]), pack_bf16(v[12], v[13]));
    };
    const uint32_t q_st = sb + (cw & 3) * 1024 + (lane >> 2) * 64 + (((lane & 3) ^ (lane >> 3)) << 4);
    const uint32_t q_ld = sb + (cw & 3) * 1024 + (lane & 15) * 64 + (((lane >> 4) ^ ((lane >> 1) & 3)) << 4);
    auto park = [&](uint32_t off, int i, uint4 v) {
      asm volatile("st.shared.v4.u32 [%0], {%1,%2,%3,%4};" ::"r"(q_st + off + (i >> 1) * 4096 + (i & 1) * 512), "r"(v.x), "r"(v.y), "r"(v.z), "r"(v.w) : "memory");
    };
    auto load_q = [&](uint32_t off, int k) { ldsm4(Q + 4 * k, ((q_ld + off) ^ ((k & 1) << 5)) + (k >> 1) * 4096); };
    {
      TL(0, 1, tid == 128);
      __nv_bfloat16* pdst = g_qkv;
      auto put2 = [&](int j) {
#pragma unroll
        for (int i = (j >> 1) * 4 + (j & 1); i < (j >> 1) * 4 + 4; i += 2)
          __stcs(reinterpret_cast<uint4*>(pdst + (i & 1) * 8 * NQ + (i >> 1) * 32), make_uint4(pk[4 * i], pk[4 * i + 1], pk[4 * i + 2], pk[4 * i + 3]));
      };
      const uint64_t da0 = mk_desc(sb + w * 8192, 16, 1024, 1);
      const uint64_t db0 = mk_desc(sb + 16384, 8192, 1024, 1);
      int st = 0; uint32_t ph = 0;
      auto issue = [&](int accum, auto between, bool res = false) {
        mbar_wait_c(B(B_FULL1 + st), ph);
        const uint64_t da = desc_add(da0, res ? 6 * SLOT + st * 8192 : st * P1_STAGE), db = desc_add(db0, st * P1_STAGE);
        between();
        wg_fence();
#pragma unroll
        for (int k = 0; k < 4; k++) mma_n256_ss<1>(R, desc_add(da, k * 32), desc_add(db, k * 2048), k == 0 ? accum : 1);
        wg_commit();
      };
      issue(0, []() {});
#pragma unroll 1
      for (int t = 0;; t++) {
        const int nk = t >= 4 ? 16 : 8;
        const bool tr = t > 0 && t < 5;
        TL(0, 2 + 2 * t + 16 * w, (tid & 127) == 0);
        int prev = st;
        if (++st == 4) { st = 0; ph ^= 1; }
#pragma unroll 1
        for (int kb = 1; kb < nk; kb++) {
          if (kb == nk - 1 && w == 1) bar_sync(5, 256);
          issue(1, []() {}, t < 4 && (kb & 5) == 4);
          if (kb == nk - 1 && w == 0) bar_arrive(5, 256);
          if (tr) {
#pragma unroll
            for (int i = 1; i < 8; i++) if (kb == i) put2(i);
            if (kb == 7 && !(t & 1)) publish((t >> 1) - 1);
          } else if (t == 5) {
            if (kb == 2) {
#pragma unroll
              for (int i = 0; i < 8; i++) park(6 * SLOT + w * 16384, i, make_uint4(pk[4 * i], pk[4 * i + 1], pk[4 * i + 2], pk[4 * i + 3]));
              __syncwarp();
            }
            if (kb == 4) {
#pragma unroll
              for (int k = 0; k < 8; k++) load_q(6 * SLOT + w * 16384, k);
              __syncwarp();
            }
            if (kb == 6) {
#pragma unroll
              for (int i = 0; i < 8; i++) park(6 * SLOT + w * 16384, i, make_uint4(pk[32 + 4 * i], pk[33 + 4 * i], pk[34 + 4 * i], pk[35 + 4 * i]));
            }
          }
          wg_wait<1>();
          release2(B_EMPTY1 + prev);
          prev = st;
          if (++st == 4) { st = 0; ph ^= 1; }
        }
        if (t == 5) break;
        issue(0, [&]() {
          sched_fence(q_st);
          wg_wait<0>();
          fence_regs<128>(R);
          TL(0, 3 + 2 * t + 16 * w, (tid & 127) == 0);
#pragma unroll
          for (int i = 0; i < 16; i++) { const uint4 v = packed(i); pk[4 * i] = v.x; pk[4 * i + 1] = v.y; pk[4 * i + 2] = v.z; pk[4 * i + 3] = v.w; }
          release2(B_EMPTY1 + prev);
          fence_regs<128>(R);
        });
        if (w == 1) bar_arrive(4, 256);
        sched_fence(q_st);
        pdst = g_qkv + (size_t)(((t & 1) + 1) * SEQ + mt * 128 + cw * 16 + (lane >> 2)) * NQ + (gq + ((t >> 1) ^ 1) * 8) * 256 + (lane & 3) * 8;
        if (t < 4) put2(0);
        if (w == 0) bar_sync(4, 256);
      }
      if (w == 1) bar_arrive(6, 256);
      mbar_wait_c(B(B_KF), 0);
      sched_fence(q_st);
      wg_wait<0>();
      fence_regs<128>(R);
      release2(B_EMPTY1 + 3);
      TL(0, 13 + 16 * w, (tid & 127) == 0);
    }
    auto issue3 = [&](int st, uint32_t ph, int accum) {
      mbar_wait_c(B(B_FULL3 + st), ph);
      const uint64_t da = mk_desc(sb + OFF_R3 + w * 8192 + st * SLOT, 16, 1024, 1), db = mk_desc(sb + OFF_R3 + 16384 + st * SLOT, 8192, 1024, 1);
      wg_fence();
#pragma unroll
      for (int k = 0; k < 4; k++) mma_n128_ss<1>(acc, desc_add(da, k * 32), desc_add(db, k * 2048), k == 0 ? accum : 1);
      wg_commit();
    };
    uint32_t wf[128];
    auto w_addr = [&](uint32_t off, int m) {
      const uint32_t w_ld = sb + ((lane >> 3) & 1) * 8192 + ((cw >> 1) * 32 + (lane & 7) + (lane >> 4) * 8) * 64 + ((((cw & 1) * 2) ^ ((lane >> 1) & 3)) << 4);
      return ((w_ld + off) ^ ((m & 1) << 4)) + (m >> 2) * 16384 + ((m >> 1) & 1) * 1024;
    };
    auto grab = [&](uint32_t* d, uint32_t off, int m0, int m1) {
#pragma unroll
      for (int m = m0; m < m1; m++)
        asm volatile("ldmatrix.sync.aligned.m8n8.x4.trans.shared.b16 {%0,%1,%2,%3}, [%4];"
                     : "=r"(d[4 * m]), "=r"(d[4 * m + 1]), "=r"(d[4 * m + 2]), "=r"(d[4 * m + 3]) : "r"(w_addr(off, m)) : "memory");
    };
    float inv[2] = {0.f, 0.f};
    auto scaled = [&](int i) {
      const float* o = O + 16 * (i >> 1) + 2 * (i & 1);
      const float c = inv[i & 1];
      return make_uint4(pack_bf16(o[0] * c, o[1] * c), pack_bf16(o[4] * c, o[5] * c), pack_bf16(o[8] * c, o[9] * c), pack_bf16(o[12] * c, o[13] * c));
    };
    {
      const int wrow = cw * 16;
      const uint64_t dk0 = mk_desc(sb, 16, 1024, 1);
      const uint64_t dv0 = mk_desc(sb + 2 * SLOT, 16384, 1024, 1);
      const uint32_t pin = sb + OFF_MISC + 1028;
      float l0 = 0.f, l1 = 0.f;
      int g = 0, t = 0;
      uint32_t fail = 0;
      auto piece = [&](int tt) { return (uint32_t)(tt == 3 ? 6 * SLOT + w * 16384 : (3 + 2 * w) * SLOT + (tt - 1) * 16384); };
      uint32_t par = 0;
      auto issue_s = [&](float* S) {
        const uint64_t dk = desc_add(dk0, par * 16);
        mma_n128_rs0(S, Q, dk);
#pragma unroll
        for (int k = 1; k < 8; k++) mma_n128_rs<0>(S, Q + 4 * k, desc_add(dk, (k >> 2) * 16384 + (k & 3) * 32), 1);
        wg_commit();
      };
      auto issue_pv = [&](bool half, int accum) {
        const uint64_t dv = desc_add(dv0, ((g - 1) & 1) * 2 * SLOT);
        wg_fence();
#pragma unroll
        for (int k = 0; k < 4; k++) mma_n128_rs<1>(O, P + 4 * k, desc_add(dv, k * 2048), k == 0 ? accum : 1);
        wg_commit();
        if (UNLIKELY(half)) {
          wg_fence();
          wg_commit();
        } else {
          wg_fence();
#pragma unroll
          for (int k = 4; k < 8; k++) mma_n128_rs<1>(O, P + 4 * k, desc_add(dv, k * 2048), 1);
          wg_commit();
        }
        bar_arrive(2 - w, 256);
        wg_wait<2>();
        fence_regs<32>(Q);
      };
      auto release_k = [&]() { release2(B_KE); rbar ^= 8; };
      auto pv_done = [&]() {
        TC(g, 3);
        sched_fence(q_st);
        wg_wait<0>();
        fence_regs<64>(O); fence_regs<32>(P);
        TC(g, 4);
        release2(B_VE);
      };
      auto row_inv = [&](bool go) {
        float a = l0 + __shfl_xor_sync(~0u, l0, 1), b = l1 + __shfl_xor_sync(~0u, l1, 1);
        a += __shfl_xor_sync(~0u, a, 2); b += __shfl_xor_sync(~0u, b, 2);
        const bool ok = __all_sync(~0u, a >= AT_LO && a <= AT_HI && b >= AT_LO && b <= AT_HI) != 0;
        asm("rcp.approx.ftz.f32 %0, %1;" : "=f"(inv[0]) : "f"(a));
        asm("rcp.approx.ftz.f32 %0, %1;" : "=f"(inv[1]) : "f"(b));
        fail |= (uint32_t)(go && !ok) << t;
        l0 = go ? 0.f : l0; l1 = go ? 0.f : l1;
        t += go;
      };
      const uint64_t m_first = 1ull | (1ull << (16 - ti)) | (1ull << 17) | (1ull << (18 + ti));
      const uint64_t m_diag = (3ull << (15 - ti)) | (3ull << (17 + ti));
      enum { F_FIRST = 1, F_DIAG = 2, F_LAST = 4, F_PFIRST = 8, F_PHALF = 16, F_STOP = 32 };
      auto kind = [&](int gn) {
        const uint32_t a = (uint32_t)((m_first << 1) >> gn), d = (uint32_t)((m_diag << 1) >> gn);
        return ((a >> 1) & 1) * F_FIRST | ((d >> 1) & 1) * F_DIAG | ((a >> 2) & 1) * F_LAST | (a & 1) * F_PFIRST |
               (w == 0 ? (d & 1) * F_PHALF | ((d >> 1) & 1) * F_STOP : 0) | (gn == 34 ? F_STOP : 0);
      };
      uint32_t kinds;
      {
        uint32_t qt[64];
#pragma unroll
        for (int i = 0; i < 16; i++) { const uint4 v = packed(i); qt[4 * i] = v.x; qt[4 * i + 1] = v.y; qt[4 * i + 2] = v.z; qt[4 * i + 3] = v.w; }
        fence_regs<64>(qt);
        sched_fence(q_st);
        float S[64];
        wg_fence();
        issue_s(S);
        bar_arrive(w ? 1 : 7, 256);
        bar_sync(6 + w, 256);
        sched_fence(q_st);
        TL(1, 0, tid == 128);
#pragma unroll
        for (int i = 0; i < 16; i++) park(piece(1), i, make_uint4(qt[4 * i], qt[4 * i + 1], qt[4 * i + 2], qt[4 * i + 3]));
        kinds = pinned(kind(lane + 3));
        sched_fence(q_st);
        wg_wait<0>();
        fence_regs<64>(S);
        release_k();
        TL(1, 1, tid == 128);
        const bool kok = mbar_try(B(B_KF + 1), 0);
        at_exp<0, 32>(S);
        sched_fence(q_st);
        at_exp<32, 64>(S); at_fin<0, 64>(S, P);
        if (UNLIKELY(!kok)) mbar_wait_c(B(B_KF + 1), 0);
        TL(1, 2, tid == 128);
      }
      uint32_t f = F_PFIRST, fn;
      auto shadow = [&]() {
        const bool vok = mbar_try(B(B_VF + ((g - 1) & 1)), ((g - 1) >> 1) & 1);
        at_sum(P, f & F_PHALF, l0, l1);
        fn = __shfl_sync(~0u, kinds, max(g - 2, 0));
        if (UNLIKELY(!vok)) mbar_wait_c(B(B_VF + ((g - 1) & 1)), ((g - 1) >> 1) & 1);
      };
      auto hand_over = [&]() { __syncwarp(); if (lane == 0 && !((fail >> (t - 1)) & 1)) mbar_arrive(B(B_PUB + 1 + t)); };
      auto exp_q = [&](float* S, auto kc, auto nc) {
        constexpr int k = decltype(kc)::value, n = decltype(nc)::value;
        asm volatile("{\n.reg .pred p;\nsetp.ne.b32 p, %5, 0;\n@p ldmatrix.sync.aligned.m8n8.x4.shared.b16 {%0,%1,%2,%3}, [%4];\n}"
                     : "+r"(Q[4 * k]), "+r"(Q[4 * k + 1]), "+r"(Q[4 * k + 2]), "+r"(Q[4 * k + 3])
                     : "r"(((q_ld + piece(t + 1)) ^ ((k & 1) << 5)) + (k >> 1) * 4096), "r"(f & F_LAST) : "memory");
        at_exp<n * k, n * k + n>(S);
      };
      g = 1; par = SLOT / 16;
#pragma unroll 1
      for (;;) {
        {
          TC(g, 0);
          bar_sync(1 + w, 256);
          fence_regs<32>(Q);
          float S[64];
          wg_fence();
          issue_s(S);
          sched_fence(q_st);
          TC(g, 1);
          shadow();
          fence_regs<64>(O); fence_regs<32>(P);
          issue_pv(f & F_PHALF, ~f & F_PFIRST);
          fence_regs<64>(S);
          TC(g, 2);
          release_k();
          at_exp<0, 8>(S);
          const bool first = f & F_FIRST;
          if (UNLIKELY(f & (F_FIRST | F_LAST))) {
            row_inv(first);
            at_mask(S + 32, (f & F_DIAG) ? wrow - 64 : 64, lane);
            unroll8([&](auto kc) { exp_q(S + 8, kc, std::integral_constant<int, AT_R1 / 8 - 1>{}); });
          } else {
            at_exp<8, AT_R1>(S);
          }
          pv_done();
          g = pinned(g + 1); par = pinned(par ^ (SLOT / 16)); f = fn;
          const bool kok = mbar_try(B(B_KF + (g & 1)), g < 34 ? (g >> 1) & 1 : 0);
          if (UNLIKELY(first)) {
            unroll8([&](auto ic) {
              constexpr int i = decltype(ic)::value, n = (64 - AT_R1) / 8;
              at_exp<AT_R1 + n * i, AT_R1 + n * i + n>(S);
              park(piece(t), i, scaled(i));
            });
            at_fin<0, 64>(S, P);
            hand_over();
          } else {
            at_exp<AT_R1, 64>(S); at_fin<0, 64>(S, P);
          }
          TC(g - 1, 5);
          if (!TCLK) TL(1, 1 + g, tid == 128);
          if (kok && !(f & F_STOP)) continue;
          if (UNLIKELY(!kok)) mbar_wait_c(B(B_KF + (g & 1)), (g >> 1) & 1);
          if (g == 34) break;
        }
#pragma unroll 1
        while (f & F_STOP) {
          TC(g, 0);
          bar_sync(1, 256);
          fence_regs<64>(O); fence_regs<32>(Q); fence_regs<32>(P);
          float S[32];
          const uint64_t dk = desc_add(dk0, par * 16);
          wg_fence();
          mma_n64_rs0(S, Q, dk);
#pragma unroll
          for (int k = 1; k < 8; k++) mma_n64_rs(S, Q + 4 * k, desc_add(dk, (k >> 2) * 16384 + (k & 3) * 32), 1);
          wg_commit();
          TC(g, 1);
          mbar_wait_c(B(B_VF + ((g - 1) & 1)), ((g - 1) >> 1) & 1);
          issue_pv(f & F_PHALF, ~f & F_PFIRST);
          fence_regs<32>(S);
          TC(g, 2);
          release_k();
          const bool first = f & F_FIRST;
          at_sum(P, f & F_PHALF, l0, l1);
          fn = __shfl_sync(~0u, kinds, g - 2);
          row_inv(first);
          pv_done();
          sched_fence(q_st);
          at_mask(S, wrow, lane);
          unroll8([&](auto kc) { exp_q(S, kc, std::integral_constant<int, 4>{}); });
          g++; par ^= SLOT / 16; f = fn;
          at_fin<0, 32>(S, P);
          if (first) {
#pragma unroll
            for (int i = 0; i < 8; i++) park(piece(t), i, scaled(i));
            hand_over();
          }
          TC(g - 1, 5);
          if (!TCLK) TL(1, 1 + g, tid == 128);
          mbar_wait_c(B(B_KF + (g & 1)), (g >> 1) & 1);
        }
      }
      const bool wok = mbar_test(B(ffn ? B_WF : B_QP + 1), 0);
      grab(wf, 3 * SLOT, 0, 8);
      mbar_wait_c(B(B_VF + 1), 0);
      bar_sync(1 + w, 256);
      fence_regs<64>(O); fence_regs<32>(P);
      wg_fence();
#pragma unroll
      for (int k = 0; k < 8; k++) mma_n128_rs<1>(O, P + 4 * k, desc_add(dv0, 2 * SLOT + k * 2048), 1);
      wg_commit();
      if (w == 0) bar_arrive(2, 256);
      pin_order(__uint_as_float(wf[28] & wf[24]), pin);
      __syncwarp();
      if (wok) release2(B_WE);
      TL(3, 12 + 16 * w, (tid & 127) == 0);
      sched_fence(q_st);
      at_sum(P, false, l0, l1);
      row_inv(true);
      sched_fence(q_st);
      wg_wait<0>();
      fence_regs<64>(O); fence_regs<32>(P);
      release2(B_VE + 1);
      if (UNLIKELY(!wok || fail != 0)) {
#pragma unroll 1
        for (int tt = 0; tt < 4; tt++) {
          if (!((tt < 3 ? fail >> tt : fail != 0) & 1)) continue;
          slow_tile(O, P, l0, l1, wq, (((tt + 1) & 2) ? ti : 15 - ti) * 128 + wrow, hh + (tt & 2) * 8, lane, q_st);
          row_inv(false);
          if (tt < 3) {
#pragma unroll
            for (int i = 0; i < 8; i++) park(piece(tt + 1), i, scaled(i));
            publish(2 + tt);
          }
        }
        if (!wok) {
          mbar_wait_c(B(ffn ? B_WF : B_QP + 1), 0);
          grab(wf, 3 * SLOT, 0, 8);
          pin_order(__uint_as_float(wf[28] & wf[24]), pin);
          __syncwarp();
          release2(B_WE);
        }
      }
      TL(3, 13 + 16 * w, (tid & 127) == 0);
      issue3(0, 0, 0);
      TL(3, 14 + 16 * w, (tid & 127) == 0);
      TL(1, 36, tid == 128);
    }
    uint32_t hp[32];
    lane = lane_id();
    {
      int st = 1, prev = 0; uint32_t ph = 0;
      __nv_bfloat16* dst = g_qkv + (size_t)((15 - ti) * 128 + cw * 16 + (lane >> 2)) * NQ + (hh + 16) * 128 + (lane & 3) * 8;
      auto kblock = [&](auto between, int lim = 6) {
        issue3(st, ph, 1);
        between();
        wg_wait<1>();
        release2(B_EMPTY3 + prev);
        prev = st;
        if (++st == lim) { st = 0; ph ^= 1; }
      };
      uint4 ob[8];
      kblock([&]() { sched_fence(rbar); ob[0] = scaled(0); ob[1] = scaled(2); ob[2] = scaled(1); ob[3] = scaled(3); sched_fence(rbar); });
      kblock([&]() { sched_fence(rbar); ob[4] = scaled(4); ob[5] = scaled(6); ob[6] = scaled(5); ob[7] = scaled(7); sched_fence(rbar); grab(wf + 32, 5 * SLOT, 0, 8); });
#pragma unroll 1
      for (int kb = 3; kb < 11; kb++) {
        kblock([&]() {
          sched_fence(rbar);
#pragma unroll
          for (int i = 0; i < 8; i++)
            if (kb == 3 + i) *reinterpret_cast<uint4*>(dst + (i & 2) * 4 * NQ + (i & 1) * 32 + (i & 4) * 16) = ob[i];
          TL(3, 14 + kb + 16 * w, (tid & 127) == 0);
          if (kb == 8) TL(2, 2, tid == 128);
        }, kb == 4 ? 5 : 6);
        if (kb == 4) release2(B_EMPTY3 + 5);
      }
      publish(5);
      kblock([&]() { mbar_wait_c(B(ffn ? B_WF2 : B_QP + 2), 0); grab(wf + 32, 5 * SLOT, 8, 16); });
#pragma unroll 1
      for (int kb = 12; kb < G_KB; kb++) {
        kblock([&]() { if ((kb & 7) == 0) TL(2, 1 + (kb >> 3), tid == 128); });
        if (kb == X_KB && lane == 0) mbar_arrive(B(B_XE));
      }
      kblock([&]() {
        mbar_wait_c(B(B_XF), 0);
#pragma unroll
        for (int i = 0; i < 8; i++)
          ldsm4(hp + 4 * i, sb + 6 * SLOT + w * 16384 + ((cw & 3) * 16 + (lane & 15)) * 128 + (i >> 2) * 8192 + ((((i & 3) * 2 + (lane >> 4)) ^ (lane & 7)) << 4));
      });
#pragma unroll 1
      for (int kb = G_KB + 1; kb < 64; kb++) {
        kblock([&]() { if ((kb & 7) == 0) TL(2, 1 + (kb >> 3), tid == 128); });
        if (kb == G_KB + 2 && lane == 0) mbar_arrive(B(B_XE));
      }
    }
    lane = lane_id();
    const int r0 = lane >> 2, q4 = lane & 3, ct = cw * 32 + lane;
    uint32_t tb[16];
    mbar_wait_c(B(B_WR), 0);
#pragma unroll
    for (int i = 0; i < 4; i++) ldsm4(tb + 4 * i, sb + OFF_MISC + 512 + (lane & 1) * 256 + (lane >> 3) * 16 + i * 64);
    mbar_wait_c(B(B_SET2), 0);
    float4* const psd = reinterpret_cast<float4*>(xr + XR_PS + cw * 16 + r0);
    const uint4* const pss = g_xr + (mt * 8 + (ct & 1) * 4) * XR_SIZE + XR_PS + (ct >> 1);
    sched_fence(stg);
    wg_wait<0>();
    fence_regs<64>(acc);
    TL(2, 10, tid == 128);
    {
      float d[2][4] = {}, qa[2][4] = {}, qb[2][4] = {};
#pragma unroll
      for (int j = 0; j < 16; j++) {
        hp[2 * j] = hadd2_bf(hp[2 * j], pack_bf16(acc[4 * j], acc[4 * j + 1]));
        hp[2 * j + 1] = hadd2_bf(hp[2 * j + 1], pack_bf16(acc[4 * j + 2], acc[4 * j + 3]));
        if (j & 1) {
          mma16816(d[(j >> 1) & 1], hp[2 * j - 2], hp[2 * j - 1], hp[2 * j], hp[2 * j + 1], tb[j - 1], tb[j]);
          mma16816(qa[(j >> 1) & 1], hp[2 * j - 2], hp[2 * j - 1], hp[2 * j], hp[2 * j + 1], hp[2 * j - 2], hp[2 * j]);
          mma16816(qb[(j >> 1) & 1], hp[2 * j - 2], hp[2 * j - 1], hp[2 * j], hp[2 * j + 1], hp[2 * j - 1], hp[2 * j + 1]);
        }
      }
      if (q4 == (r0 >> 1)) {
        __stcg(psd, make_float4(d[0][0] + d[1][0], (r0 & 1) ? qa[0][1] + qa[1][1] : qa[0][0] + qa[1][0], d[0][1] + d[1][1], 0.f));
        __stcg(psd + 8, make_float4(d[0][2] + d[1][2], (r0 & 1) ? qb[0][3] + qb[1][3] : qb[0][2] + qb[1][2], d[0][3] + d[1][3], 0.f));
      }
    }
    TL(2, 11, tid == 128);
    mbar_wait_c(B(B_EMPTY3 + 1), 0);
    stage_store_128(stg, lane, hp);
    if (ffn) mbar_wait_c(B(B_WF2), 1);
    grab(wf + 96, 6 * SLOT, 0, 8);
    const float wsum = *reinterpret_cast<const float*>(sp + OFF_MISC + 1024);
    __syncwarp();
    {
      uint4 ps[4];
      poll_chunks(ps, pss, XR_SIZE);
      TL(2, 12, tid == 128);
      auto F = [](uint32_t u) { return __uint_as_float(u); };
      float s1 = (F(ps[0].x) + F(ps[1].x)) + (F(ps[2].x) + F(ps[3].x)), s2 = (F(ps[0].y) + F(ps[1].y)) + (F(ps[2].y) + F(ps[3].y));
      float s3 = (F(ps[0].z) + F(ps[1].z)) + (F(ps[2].z) + F(ps[3].z));
      __syncwarp();
      s1 += __shfl_xor_sync(~0u, s1, 1); s2 += __shfl_xor_sync(~0u, s2, 1); s3 += __shfl_xor_sync(~0u, s3, 1);
      const float mean = s1 * (1.f / DM);
      float mb, inv;
      ln_round(mean, fmaxf(fmaf(s2, 1.f / DM, -mean * mean), 0.f), mb, inv);
      const uint32_t u = pack_bf16(0.f, fmaf(s3 - mb * wsum, inv, 0.f));
      const uint32_t key = (u ^ ((((int)u >> 31) & 0x7FFF0000u) | 0x80000000u)) | (0x7FFFu - (mt * 128 + (ct >> 1)));
      const uint32_t nm2 = pack_bf16(-mb, -mb);
      const uint32_t c1 = __reduce_max_sync(~0u, key);
      const uint32_t c2 = __reduce_max_sync(~0u, key == c1 ? 0u : key);
      if (lane == 0) {
        __stcg(reinterpret_cast<uint2*>(psd) + (XR_KEY - XR_PS) * 2 - cw * 31, make_uint2(c1, c2));
        mbar_arrive(B(B_OUT));
      }
      TL(2, 13, tid == 128);
      const int row = (0x7FFF - (((lane >> 4) ? c2 : c1) & 0x7FFF)) & 15;
      const uint32_t rn = __shfl_sync(~0u, nm2, row * 2);
      const float ri = __shfl_sync(~0u, inv, row * 2);
      uint32_t v[4];
#pragma unroll
      for (int i = 0; i < 4; i++)
        asm volatile("ld.shared.u32 %0, [%1];" : "=r"(v[i]) : "r"(stg + ((lane >> 3) & 1) * 8192 + row * 128 + ((((lane & 4) + i) ^ (row & 7)) << 4) + q4 * 4) : "memory");
      __stcg(xr + XR_CAND + cw * 64 + 32 + lane, make_uint4(ln_apply(v[0], rn, ri), ln_apply(v[1], rn, ri), ln_apply(v[2], rn, ri), ln_apply(v[3], rn, ri)));
      __stcg(xr + XR_CAND + cw * 64 + lane, make_uint4(v[0], v[1], v[2], v[3]));
      sched_fence(stg);
      const uint32_t na = __shfl_sync(~0u, nm2, r0 * 2), nb = __shfl_sync(~0u, nm2, r0 * 2 + 16);
      const float ia = __shfl_sync(~0u, inv, r0 * 2), ib = __shfl_sync(~0u, inv, r0 * 2 + 16);
#pragma unroll
      for (int i = 0; i < 32; i++) hp[i] = hadd2_bf(hp[i], ln_apply(hp[i], (i & 1) ? nb : na, (i & 1) ? ib : ia));
      __syncwarp();
      stage_store_128(stg, lane, hp);
      asm volatile("fence.proxy.async.shared::cta;" ::: "memory");
      publish(B_OUT3 - B_PUB);
    }
    uint32_t wd[16][4];
    sched_fence(stg);
    if (ffn) mbar_wait_c(B(B_FULL3 + 5 * w), 1 - w);
    auto load_wd = [&](int h) {
#pragma unroll
      for (int i = h; i < 16; i += 2)
        asm volatile("ldmatrix.sync.aligned.m8n8.x4.trans.shared.b16 {%0,%1,%2,%3}, [%4];"
                     : "=r"(wd[i][0]), "=r"(wd[i][1]), "=r"(wd[i][2]), "=r"(wd[i][3])
                     : "r"(sb + OFF_R3 + 5 * w * SLOT + (2 * (cw & 3) + (i >> 3)) * 4096 + (h * 16 + (lane & 7) + (lane >> 4) * 8) * 128 +
                           (((2 * ((i >> 1) & 3) + ((lane >> 3) & 1)) ^ (lane & 7)) << 4)) : "memory");
    };
    load_wd(0);
    __syncwarp();
    cluster_arrive();
    const char* xsrc = reinterpret_cast<const char*>(g_xr + (r0 >> 1) * XR_SIZE + XR_CAND + 32 + (cw >> 1) * 4 + q4);
    asm volatile("" : "+l"(xsrc));
    sched_fence(stg);
    TL(2, 22, tid == 128);
    mbar_wait_c(B(B_OUT2), 0);
    TL(2, 14, tid == 128);
    if (ffn) {
      uint4 xb[2];
      poll_chunks(xb, reinterpret_cast<const uint4*>(xsrc + *reinterpret_cast<const uint32_t*>(sp + OFF_MISC + 8 + (r0 & 1) * 4)), 4 * XR_SIZE);
      __syncwarp();
      TL(2, 15, tid == 128);
      float d[8][4] = {};
#pragma unroll
      for (int n = 0; n < 32; n++) {
        if (n == 8) { sched_fence(stg); load_wd(1); }
        const int s = (n >> 4) * 4 + ((n >> 1) & 3), m = ((n >> 3) & 1) * 2 + (n & 1);
        const uint32_t* a = wf + 16 * s + 4 * m;
        mma16816(d[n & 7], a[0], a[1], a[2], a[3], (m & 2) ? xb[s >> 2].z : xb[s >> 2].x, (m & 2) ? xb[s >> 2].w : xb[s >> 2].y);
      }
      float v[8];
#pragma unroll
      for (int i = 0; i < 8; i++) {
        const float lo = (q4 & 1) ? d[2 + (i >> 2)][i & 3] : d[i >> 2][i & 3], hi = (q4 & 1) ? d[6 + (i >> 2)][i & 3] : d[4 + (i >> 2)][i & 3];
        v[i] = (q4 & 2) ? hi : lo;
      }
#pragma unroll
      for (int i = 0; i < 4; i++) v[i] = ((q4 & 2) ? v[i + 4] : v[i]) + __shfl_xor_sync(~0u, (q4 & 2) ? v[i] : v[i + 4], 2);
#pragma unroll
      for (int i = 0; i < 2; i++) v[i] = ((q4 & 1) ? v[i + 2] : v[i]) + __shfl_xor_sync(~0u, (q4 & 1) ? v[i] : v[i + 2], 1);
      float4* red = reinterpret_cast<float4*>(sp + SL_SCR * SLOT);
      reinterpret_cast<float2*>(red + cw * 16 + (q4 >> 1) * 8 + r0)[q4 & 1] = make_float2(v[0], v[1]);
      bar_sync(3, 256);
      TL(2, 16, tid == 128);
      const float4 z0 = red[lane], z1 = red[32 + lane], z2 = red[64 + lane], z3 = red[96 + lane];
      const uint32_t ub = pack_bf16((z0.x + z1.x) + (z2.x + z3.x), (z0.y + z1.y) + (z2.y + z3.y));
      const uint32_t gb = pack_bf16((z0.z + z1.z) + (z2.z + z3.z), (z0.w + z1.w) + (z2.w + z3.w));
      const float g0 = bf_lo(gb), g1 = bf_hi(gb);
      const uint32_t sg = pack_bf16(g0 * sigmoid(g0), g1 * sigmoid(g1));
      const uint32_t act = pack_bf16(bf_lo(sg) * bf_lo(ub), bf_hi(sg) * bf_hi(ub));
      const uint32_t pr = __byte_perm(act, __shfl_xor_sync(~0u, act, 1), (lane & 1) ? 0x3276 : 0x5410);
      const int src = q4 * 2 + (r0 & 1);
      const uint32_t a0 = __shfl_sync(~0u, pr, src), a1 = __shfl_sync(~0u, pr, src + 8), a2 = __shfl_sync(~0u, pr, src + 16), a3 = __shfl_sync(~0u, pr, src + 24);
      TL(2, 17, tid == 128);
      float y[8][4] = {};
#pragma unroll
      for (int i = 0; i < 8; i++) mma16816(y[i], wd[2 * i][0], wd[2 * i][1], wd[2 * i][2], wd[2 * i][3], a0, a1);
#pragma unroll
      for (int i = 0; i < 8; i++) mma16816(y[i], wd[2 * i + 1][0], wd[2 * i + 1][1], wd[2 * i + 1][2], wd[2 * i + 1][3], a2, a3);
      float2* yd = reinterpret_cast<float2*>(g_xr + (cw * 16 + 2 * q4) * XR_SIZE + XR_Y + fid * 4) + r0;
#pragma unroll
      for (int j = 0; j < 2; j++) {
        float v[4];
#pragma unroll
        for (int e = 0; e < 4; e++) {
          const float lo = (q4 & 1) ? y[4 * j + 1][e] : y[4 * j][e], hi = (q4 & 1) ? y[4 * j + 3][e] : y[4 * j + 2][e];
          v[e] = (q4 & 2) ? hi : lo;
        }
        __stcg(yd + j * 16 * XR_SIZE, make_float2(v[0], v[1]));
        __stcg(yd + j * 16 * XR_SIZE + 2 * XR_SIZE, make_float2(v[2], v[3]));
      }
    }
    TL(2, 18, tid == 128);
    cluster_wait();
    if (rid == 127 && ct < C_NUM) g_cnt[ct] = 0;
    if (cw < 2) {
      const int tok = (lane >> 1) & 1, pair = cw * 2 + (lane & 1);
      uint32_t* const dst = reinterpret_cast<uint32_t*>(out + (size_t)(~*reinterpret_cast<const uint32_t*>(sp + OFF_MISC + tok * 4) & 0x7FF) * DM) + rid * 4 + pair;
      idle(ffn ? Y_CLK : Y_CLK + 2000);
      const bool fin = mbar_test(B(B_FIN), 0);
      uint4 op = lds128(sb + OFF_MISC + 128 + (tok * 4 + pair) * 16);
      uint4 z[7];
      poll_chunks(z, xr + XR_Y + (lane >> 1) * 4 + pair, 64);
      __syncwarp();
      TL(2, 19, tid == 128);
      if (!fin) { mbar_wait_c(B(B_FIN), 0); op = lds128(sb + OFF_MISC + 128 + (tok * 4 + pair) * 16); }
      auto F = [](uint32_t u) { return __uint_as_float(u); };
      const float v0 = ((F(z[0].x) + F(z[1].x)) + (F(z[2].x) + F(z[3].x))) + ((F(z[4].x) + F(z[5].x)) + F(z[6].x));
      const float v1 = ((F(z[0].y) + F(z[1].y)) + (F(z[2].y) + F(z[3].y))) + ((F(z[4].y) + F(z[5].y)) + F(z[6].y));
      const float v2 = ((F(z[0].z) + F(z[1].z)) + (F(z[2].z) + F(z[3].z))) + ((F(z[4].z) + F(z[5].z)) + F(z[6].z));
      const float v3 = ((F(z[0].w) + F(z[1].w)) + (F(z[2].w) + F(z[3].w))) + ((F(z[4].w) + F(z[5].w)) + F(z[6].w));
      float ya = (tok ? v1 : v0) + __shfl_xor_sync(~0u, tok ? v0 : v1, 2), yb = (tok ? v3 : v2) + __shfl_xor_sync(~0u, tok ? v2 : v3, 2);
#pragma unroll
      for (int o = 4; o < 32; o <<= 1) { ya += __shfl_xor_sync(~0u, ya, o); yb += __shfl_xor_sync(~0u, yb, o); }
      const uint32_t yp = pack_bf16(ya, yb);
      if (lane < 4) *dst = hadd2_bf(op.x, hadd2_bf(op.y, pack_bf16(bf_lo(yp) * F(op.z), bf_hi(yp) * F(op.z))));
      TL(2, 21, tid == 128);
    }
    TL(2, 20, tid == 128);
    TL_DUMP();
  }
}

typedef CUresult (*EncodeFn)(CUtensorMap*, CUtensorMapDataType, cuuint32_t, void*, const cuuint64_t*, const cuuint64_t*, const cuuint32_t*,
                             const cuuint32_t*, CUtensorMapInterleave, CUtensorMapSwizzle, CUtensorMapL2promotion, CUtensorMapFloatOOBfill);
EncodeFn g_enc = nullptr;

void map2(CUtensorMap* m, const void* ptr, uint64_t rows, uint64_t cols, uint32_t bc, uint32_t br) {
  const CUtensorMapSwizzle sw = bc == 64 ? CU_TENSOR_MAP_SWIZZLE_128B : CU_TENSOR_MAP_SWIZZLE_64B;
  cuuint64_t gd[2] = {cols, rows}, gs[1] = {cols * 2};
  cuuint32_t bd[2] = {bc, br}, es[2] = {1, 1};
  g_enc(m, CU_TENSOR_MAP_DATA_TYPE_BFLOAT16, 2, (void*)ptr, gd, gs, bd, es, CU_TENSOR_MAP_INTERLEAVE_NONE, sw,
        CU_TENSOR_MAP_L2_PROMOTION_L2_128B, CU_TENSOR_MAP_FLOAT_OOB_FILL_NONE);
}
void map3(CUtensorMap* m, const void* ptr, uint64_t rows, uint64_t cols, uint32_t br, uint32_t bch, uint32_t bc = 64) {
  cuuint64_t gd[3] = {bc, rows, cols / bc}, gs[2] = {cols * 2, bc * 2};
  cuuint32_t bd[3] = {bc, br, bch}, es[3] = {1, 1, 1};
  g_enc(m, CU_TENSOR_MAP_DATA_TYPE_BFLOAT16, 3, (void*)ptr, gd, gs, bd, es, CU_TENSOR_MAP_INTERLEAVE_NONE, bc == 64 ? CU_TENSOR_MAP_SWIZZLE_128B : CU_TENSOR_MAP_SWIZZLE_64B,
        CU_TENSOR_MAP_L2_PROMOTION_L2_128B, CU_TENSOR_MAP_FLOAT_OOB_FILL_NONE);
}

}

extern "C" void kernel_launch(void* const* d_in, const int* in_sizes, int n_in, void* d_out, int out_size) {
  const __nv_bfloat16* x = (const __nv_bfloat16*)d_in[0];
  const __nv_bfloat16* ckv = (const __nv_bfloat16*)d_in[1];
  const __nv_bfloat16* wq = (const __nv_bfloat16*)d_in[2];
  const __nv_bfloat16* wk = (const __nv_bfloat16*)d_in[3];
  const __nv_bfloat16* wv = (const __nv_bfloat16*)d_in[4];
  const __nv_bfloat16* wo = (const __nv_bfloat16*)d_in[5];
  const __nv_bfloat16* w_r = (const __nv_bfloat16*)d_in[7];
  const __nv_bfloat16* wgate = (const __nv_bfloat16*)d_in[8];
  const __nv_bfloat16* wup = (const __nv_bfloat16*)d_in[9];
  const __nv_bfloat16* wdown = (const __nv_bfloat16*)d_in[10];
  __nv_bfloat16* out = (__nv_bfloat16*)d_out;

  if (!g_enc) {
    void* fn = nullptr;
    cudaDriverEntryPointQueryResult qr;
    cudaGetDriverEntryPoint("cuTensorMapEncodeTiled", &fn, cudaEnableDefault, &qr);
    g_enc = (EncodeFn)fn;
    cudaFuncSetAttribute(fused_kernel, cudaFuncAttributeMaxDynamicSharedMemorySize, SMEM_BYTES);
  }
  void *xn, *qkv;
  cudaGetSymbolAddress(&xn, g_xn);
  cudaGetSymbolAddress(&qkv, g_qkv);

  Params p;
  map2(&p.xn, xn, SEQ, DM, 64, 128);
  map2(&p.ckv, ckv, SEQ, DC, 64, 128);
  map3(&p.wq, wq, DM, NQ, 64, 2);
  map3(&p.wk, wk, DC, NQ, 64, 2);
  map3(&p.wv, wv, DC, NQ, 64, 2);
  map3(&p.kv, qkv, 3 * SEQ, NQ, 128, 1);
  map2(&p.ctx_ld, qkv, SEQ, NQ, 64, 128);
  map3(&p.ctx_st, qkv, SEQ, NQ, 64, 1, 32);
  map3(&p.wo, wo, NQ, DM, 64, 1);
  map3(&p.x, x, SEQ, DM, 64, 1);
  map3(&p.wd, wdown, FF, DM, 32, 8);
  map2(&p.out, out, SEQ, DM, 64, 64);
  map2(&p.wg, wgate, DM, FF, 32, 128);
  map2(&p.wu, wup, DM, FF, 32, 128);
  fused_kernel<<<128, 384, SMEM_BYTES, cudaStreamPerThread>>>(x, wq, w_r, out, p);
}
```

```cpp
#include <cuda_runtime.h>
#include <cuda_bf16.h>
#include <cuda.h>
#include <stdint.h>
#include <type_traits>

#pragma nv_diag_suppress 549
namespace {

constexpr int SEQ = 2048, DM = 1024, NH = 32, HD = 128, DC = 512, NQ = NH * HD, FF = 3584;

__device__ __align__(1024) __nv_bfloat16 g_xn[SEQ * DM];
__device__ __align__(1024) __nv_bfloat16 g_qkv[3 * SEQ * NQ];
constexpr int XR_PS = 0;
constexpr int XR_KEY = 128;
constexpr int XR_FLAG = 132;
constexpr int XR_CAND = 136;
constexpr int XR_Y = 648;
constexpr int XR_SIZE = 1104;
__device__ __align__(1024) uint4 g_xr[128 * XR_SIZE];
constexpr int C_LN = 0, C_QKV = 16, C_CTX = 32, C_NUM = 64;
__device__ unsigned g_cnt[C_NUM];

#define TL(k, i, cond) do {} while (0)
#define TL_BYTES 0
#define TL_INIT() do {} while (0)
#define TL_DUMP() do {} while (0)
#define TC(g, i) do {} while (0)
#define TS(i) do {} while (0)
#undef TCLK
#define TCLK 0

__device__ __forceinline__ uint32_t s2u(const void* p) { return (uint32_t)__cvta_generic_to_shared(p); }
__device__ __forceinline__ void mbar_init(uint32_t b, uint32_t c) { asm volatile("mbarrier.init.shared::cta.b64 [%0], %1;" ::"r"(b), "r"(c) : "memory"); }
__device__ __forceinline__ void mbar_expect(uint32_t b, uint32_t bytes) { asm volatile("mbarrier.arrive.expect_tx.shared::cta.b64 _, [%0], %1;" ::"r"(b), "r"(bytes) : "memory"); }
__device__ __forceinline__ void mbar_arrive(uint32_t b) { asm volatile("mbarrier.arrive.shared::cta.b64 _, [%0];" ::"r"(b) : "memory"); }
__device__ __forceinline__ bool mbar_test(uint32_t b, uint32_t ph) {
  uint32_t ok;
  asm volatile("{\n.reg .pred p;\nmbarrier.test_wait.parity.shared::cta.b64 p, [%1], %2;\nselp.u32 %0, 1, 0, p;\n}" : "=r"(ok) : "r"(b), "r"(ph) : "memory");
  return ok;
}
__device__ __forceinline__ void mbar_wait(uint32_t b, uint32_t ph) {
  asm volatile(
      "{\n.reg .pred p;\n.reg .u32 n;\nmov.u32 n, 0;\n"
      "LW:\nmbarrier.try_wait.parity.shared::cta.b64 p, [%0], %1, 20000;\n@p bra LD;\n"
      "add.u32 n, n, 1;\nsetp.lt.u32 p, n, 0x40000;\n@p bra LW;\ntrap;\nLD:\n}" ::"r"(b), "r"(ph) : "memory");
}
__device__ __forceinline__ void mbar_wait_c(uint32_t b, uint32_t ph) {
  asm volatile(
      "{\n.reg .pred p;\n.reg .u32 n;\nmov.u32 n, 0;\n"
      "LW:\nmbarrier.try_wait.parity.shared::cta.b64 p, [%0], %1;\n@p bra LD;\n"
      "add.u32 n, n, 1;\nsetp.lt.u32 p, n, 0x100000;\n@p bra LW;\ntrap;\nLD:\n}" ::"r"(b), "r"(ph) : "memory");
}
__device__ __forceinline__ bool mbar_try(uint32_t b, uint32_t ph) {
  uint32_t ok;
  asm volatile("{\n.reg .pred p;\nmbarrier.try_wait.parity.shared::cta.b64 p, [%1], %2;\nselp.u32 %0, 1, 0, p;\n}" : "=r"(ok) : "r"(b), "r"(ph) : "memory");
  return ok;
}
#define UNLIKELY(c) __builtin_expect(!!(c), 0)
__device__ __forceinline__ uint32_t pinned(uint32_t v) { uint32_t r; asm volatile("mov.b32 %0, %1;" : "=r"(r) : "r"(v)); return r; }
__device__ __forceinline__ bool elect_one() {
  uint32_t p;
  asm volatile("{\n.reg .pred p;\nelect.sync _|p, 0xFFFFFFFF;\nselp.u32 %0, 1, 0, p;\n}" : "=r"(p));
  return p;
}
__device__ __forceinline__ int lane_id() { int r; asm volatile("mov.u32 %0, %%laneid;" : "=r"(r)); return r; }
template <bool SLEEP = false>
__device__ __forceinline__ void spin_until_ge(const unsigned* p, unsigned target) {
  asm volatile(
      "{\n.reg .pred p, q;\n.reg .u32 n, v;\nmov.u32 n, 0;\nsetp.ne.u32 q, %2, 0;\n"
      "LW:\nld.acquire.gpu.global.u32 v, [%0];\nsetp.ge.u32 p, v, %1;\n@p bra LD;\n@q nanosleep.u32 200;\n"
      "add.u32 n, n, 1;\nsetp.lt.u32 p, n, 0x400000;\n@p bra LW;\ntrap;\nLD:\n}" ::"l"(p), "r"(target), "n"((int)SLEEP) : "memory");
}
template <int N>
__device__ __forceinline__ void poll_chunks(uint4 (&v)[N], const uint4* p, int stride) {
  uint32_t m[N];
#pragma unroll
  for (int i = 0; i < N; i++) { m[i] = ~0u; v[i] = make_uint4(0, 0, 0, 0); }
#pragma unroll 1
  for (int n = 0; n < 0x400000; n++) {
    uint32_t a = 0;
#pragma unroll
    for (int i = 0; i < N; i++)
      asm volatile("{\n.reg .pred p;\nsetp.eq.u32 p, %5, 0xFFFFFFFF;\n@p ld.relaxed.gpu.global.v4.u32 {%0,%1,%2,%3}, [%4];\n}"
                   : "+r"(v[i].x), "+r"(v[i].y), "+r"(v[i].z), "+r"(v[i].w) : "l"(p + i * stride), "r"(m[i]) : "memory");
#pragma unroll
    for (int i = 0; i < N; i++) { m[i] = max(max(v[i].x, v[i].y), max(v[i].z, v[i].w)); a = max(a, m[i]); }
    if (__all_sync(~0u, a != 0xFFFFFFFFu)) break;
  }
}
__device__ __forceinline__ void fence_async_all() { asm volatile("fence.proxy.async;" ::: "memory"); }
__device__ __forceinline__ void bar_sync(int id, int n) { asm volatile("bar.sync %0, %1;" ::"r"(id), "r"(n) : "memory"); }
__device__ __forceinline__ void bar_arrive(int id, int n) { asm volatile("bar.arrive %0, %1;" ::"r"(id), "r"(n) : "memory"); }
__device__ __forceinline__ void cluster_arrive() { asm volatile("barrier.cluster.arrive.relaxed.aligned;" ::: "memory"); }
__device__ __forceinline__ void cluster_wait() { asm volatile("barrier.cluster.wait.acquire.aligned;" ::: "memory"); }
__device__ __forceinline__ void fence_gpu() { asm volatile("fence.acq_rel.gpu;" ::: "memory"); }
__device__ __forceinline__ void red_add(unsigned* p, unsigned v) { asm volatile("red.relaxed.gpu.global.add.u32 [%0], %1;" ::"l"(p), "r"(v) : "memory"); }
__device__ __forceinline__ void prefetch_tm(const CUtensorMap* m) { asm volatile("prefetch.tensormap [%0];" ::"l"(m) : "memory"); }

constexpr uint64_t EV_N = 0x1000000000000000ull, EV_F = 0x12F0000000000000ull;
__device__ __forceinline__ void tma_ld2(uint32_t dst, const CUtensorMap* m, uint32_t bar, int c0, int c1, bool ef = false) {
  asm volatile("cp.async.bulk.tensor.2d.shared::cta.global.mbarrier::complete_tx::bytes.L2::cache_hint [%0], [%1, {%3,%4}], [%2], %5;" ::"r"(dst), "l"(m), "r"(bar), "r"(c0), "r"(c1), "l"(ef ? EV_F : EV_N) : "memory");
}
__device__ __forceinline__ void tma_ld3(uint32_t dst, const CUtensorMap* m, uint32_t bar, int c0, int c1, int c2, bool ef = false) {
  asm volatile("cp.async.bulk.tensor.3d.shared::cta.global.mbarrier::complete_tx::bytes.L2::cache_hint [%0], [%1, {%3,%4,%5}], [%2], %6;" ::"r"(dst), "l"(m), "r"(bar), "r"(c0), "r"(c1), "r"(c2), "l"(ef ? EV_F : EV_N) : "memory");
}
__device__ __forceinline__ void tma_ld3_mc(uint32_t dst, const CUtensorMap* m, uint32_t bar, int c0, int c1, int c2, uint16_t mask, bool ef = false) {
  asm volatile("cp.async.bulk.tensor.3d.shared::cluster.global.mbarrier::complete_tx::bytes.multicast::cluster.L2::cache_hint [%0], [%1, {%3,%4,%5}], [%2], %6, %7;" ::"r"(dst), "l"(m), "r"(bar), "r"(c0), "r"(c1), "r"(c2), "h"(mask), "l"(ef ? EV_F : EV_N) : "memory");
}
__device__ __forceinline__ void tma_pf3(const CUtensorMap* m, int c0, int c1, int c2) {
  asm volatile("cp.async.bulk.prefetch.tensor.3d.L2.global [%0, {%1,%2,%3}];" ::"l"(m), "r"(c0), "r"(c1), "r"(c2) : "memory");
}
__device__ __forceinline__ void l2_prefetch(const void* p, uint32_t bytes) { asm volatile("cp.async.bulk.prefetch.L2.global [%0], %1;" ::"l"(p), "r"(bytes) : "memory"); }

__device__ __forceinline__ void wg_fence() { asm volatile("wgmma.fence.sync.aligned;" ::: "memory"); }
__device__ __forceinline__ void wg_commit() { asm volatile("wgmma.commit_group.sync.aligned;" ::: "memory"); }
template <int N> __device__ __forceinline__ void wg_wait() { asm volatile("wgmma.wait_group.sync.aligned %0;" ::"n"(N) : "memory"); }
template <int N> __device__ __forceinline__ void reg_alloc() { asm volatile("setmaxnreg.inc.sync.aligned.u32 %0;" ::"n"(N)); }
template <int N> __device__ __forceinline__ void reg_dealloc() { asm volatile("setmaxnreg.dec.sync.aligned.u32 %0;" ::"n"(N)); }
template <int N> __device__ __forceinline__ void fence_regs(float* d) {
#pragma unroll
  for (int i = 0; i < N; i++) asm volatile("" : "+f"(d[i])::"memory");
}
template <int N> __device__ __forceinline__ void fence_regs(uint32_t* d) {
#pragma unroll
  for (int i = 0; i < N; i++) asm volatile("" : "+r"(d[i])::"memory");
}

__device__ __forceinline__ uint64_t mk_desc(uint32_t addr, uint32_t lbo, uint32_t sbo, uint32_t swz) {
  uint32_t lo = ((addr & 0x3FFFF) >> 4) | ((lbo >> 4) << 16);
  uint32_t hi = (sbo >> 4) | (swz << 30);
  return ((uint64_t)hi << 32) | lo;
}
__device__ __forceinline__ uint64_t desc_add(uint64_t d, uint32_t bytes) {
  uint32_t lo = (uint32_t)d + (bytes >> 4);
  return (d & 0xFFFFFFFF00000000ull) | lo;
}

#define R8(b) "+f"(d[b + 0]), "+f"(d[b + 1]), "+f"(d[b + 2]), "+f"(d[b + 3]), "+f"(d[b + 4]), "+f"(d[b + 5]), "+f"(d[b + 6]), "+f"(d[b + 7])
#define REGS32 "%0,%1,%2,%3,%4,%5,%6,%7,%8,%9,%10,%11,%12,%13,%14,%15,%16,%17,%18,%19,%20,%21,%22,%23,%24,%25,%26,%27,%28,%29,%30,%31"
#define REGS64 REGS32 ",%32,%33,%34,%35,%36,%37,%38,%39,%40,%41,%42,%43,%44,%45,%46,%47,%48,%49,%50,%51,%52,%53,%54,%55,%56,%57,%58,%59,%60,%61,%62,%63"
#define REGS128 REGS64 ",%64,%65,%66,%67,%68,%69,%70,%71,%72,%73,%74,%75,%76,%77,%78,%79,%80,%81,%82,%83,%84,%85,%86,%87,%88,%89,%90,%91,%92,%93,%94,%95," \
               "%96,%97,%98,%99,%100,%101,%102,%103,%104,%105,%106,%107,%108,%109,%110,%111,%112,%113,%114,%115,%116,%117,%118,%119,%120,%121,%122,%123,%124,%125,%126,%127"

template <int TB>
__device__ __forceinline__ void mma_n256_ss(float (&d)[128], uint64_t a, uint64_t b, int acc) {
  asm volatile("{\n.reg .pred p;\nsetp.ne.b32 p, %130, 0;\n"
               "wgmma.mma_async.sync.aligned.m64n256k16.f32.bf16.bf16 {" REGS128 "}, %128, %129, p, 1, 1, 0, %131;\n}\n"
               : R8(0), R8(8), R8(16), R8(24), R8(32), R8(40), R8(48), R8(56), R8(64), R8(72), R8(80), R8(88), R8(96), R8(104), R8(112), R8(120)
               : "l"(a), "l"(b), "r"(acc), "n"(TB));
}
template <int TB>
__device__ __forceinline__ void mma_n128_ss(float* d, uint64_t a, uint64_t b, int acc) {
  asm volatile("{\n.reg .pred p;\nsetp.ne.b32 p, %66, 0;\n"
               "wgmma.mma_async.sync.aligned.m64n128k16.f32.bf16.bf16 {" REGS64 "}, %64, %65, p, 1, 1, 0, %67;\n}\n"
               : R8(0), R8(8), R8(16), R8(24), R8(32), R8(40), R8(48), R8(56)
               : "l"(a), "l"(b), "r"(acc), "n"(TB));
}
template <int TB>
__device__ __forceinline__ void mma_n128_rs(float* d, const uint32_t* a, uint64_t b, int acc) {
  asm volatile("{\n.reg .pred p;\nsetp.ne.b32 p, %69, 0;\n"
               "wgmma.mma_async.sync.aligned.m64n128k16.f32.bf16.bf16 {" REGS64 "}, {%64,%65,%66,%67}, %68, p, 1, 1, %70;\n}\n"
               : R8(0), R8(8), R8(16), R8(24), R8(32), R8(40), R8(48), R8(56)
               : "r"(a[0]), "r"(a[1]), "r"(a[2]), "r"(a[3]), "l"(b), "r"(acc), "n"(TB));
}
__device__ __forceinline__ void mma_n64_rs(float* d, const uint32_t* a, uint64_t b, int acc) {
  asm volatile("{\n.reg .pred p;\nsetp.ne.b32 p, %37, 0;\n"
               "wgmma.mma_async.sync.aligned.m64n64k16.f32.bf16.bf16 {" REGS32 "}, {%32,%33,%34,%35}, %36, p, 1, 1, 0;\n}\n"
               : R8(0), R8(8), R8(16), R8(24)
               : "r"(a[0]), "r"(a[1]), "r"(a[2]), "r"(a[3]), "l"(b), "r"(acc));
}
#define W8(b) "=f"(d[b + 0]), "=f"(d[b + 1]), "=f"(d[b + 2]), "=f"(d[b + 3]), "=f"(d[b + 4]), "=f"(d[b + 5]), "=f"(d[b + 6]), "=f"(d[b + 7])
__device__ __forceinline__ void mma_n128_rs0(float* d, const uint32_t* a, uint64_t b) {
  asm volatile("wgmma.mma_async.sync.aligned.m64n128k16.f32.bf16.bf16 {" REGS64 "}, {%64,%65,%66,%67}, %68, 0, 1, 1, 0;\n"
               : W8(0), W8(8), W8(16), W8(24), W8(32), W8(40), W8(48), W8(56)
               : "r"(a[0]), "r"(a[1]), "r"(a[2]), "r"(a[3]), "l"(b));
}
__device__ __forceinline__ void mma_n64_rs0(float* d, const uint32_t* a, uint64_t b) {
  asm volatile("wgmma.mma_async.sync.aligned.m64n64k16.f32.bf16.bf16 {" REGS32 "}, {%32,%33,%34,%35}, %36, 0, 1, 1, 0;\n"
               : W8(0), W8(8), W8(16), W8(24)
               : "r"(a[0]), "r"(a[1]), "r"(a[2]), "r"(a[3]), "l"(b));
}
__device__ __forceinline__ uint32_t pack_bf16(float lo, float hi) {
  uint32_t r;
  asm("cvt.rn.bf16x2.f32 %0, %1, %2;" : "=r"(r) : "f"(hi), "f"(lo));
  return r;
}
__device__ __forceinline__ float bf_lo(uint32_t v) { return __uint_as_float(v << 16); }
__device__ __forceinline__ float bf_hi(uint32_t v) { return __uint_as_float(v & 0xFFFF0000u); }
__device__ __forceinline__ float bf_round(float v) { return bf_lo(pack_bf16(v, v)); }
__device__ __forceinline__ void stsm4(uint32_t addr, uint32_t r0, uint32_t r1, uint32_t r2, uint32_t r3) {
  asm volatile("stmatrix.sync.aligned.m8n8.x4.shared.b16 [%0], {%1,%2,%3,%4};" ::"r"(addr), "r"(r0), "r"(r1), "r"(r2), "r"(r3) : "memory");
}
__device__ __forceinline__ uint4 lds128(uint32_t addr) {
  uint4 v;
  asm volatile("ld.shared.v4.u32 {%0,%1,%2,%3}, [%4];" : "=r"(v.x), "=r"(v.y), "=r"(v.z), "=r"(v.w) : "r"(addr));
  return v;
}
__device__ __forceinline__ float ex2(float x) {
  float y;
  asm("ex2.approx.ftz.f32 %0, %1;" : "=f"(y) : "f"(x));
  return y;
}
__device__ __forceinline__ void pin_order(float v, uint32_t dummy) {
  asm volatile("{\n.reg .pred p;\nsetp.eq.b32 p, %0, 0xFFFFFFFF;\n@p st.shared.b32 [%1], %0;\n}" ::"r"(__float_as_uint(v)), "r"(dummy) : "memory");
}
__device__ __forceinline__ float sigmoid(float x) {
  float y;
  asm("rcp.approx.ftz.f32 %0, %1;" : "=f"(y) : "f"(1.f + ex2(x * -1.4426950408889634f)));
  return y;
}
__device__ __forceinline__ void sched_fence(uint32_t dummy) {
  asm volatile("{\n.reg .pred p;\n.reg .u32 c;\nsetp.eq.b32 p, %0, 0xFFFFFFFF;\nmov.u32 c, %%clock;\n@p st.shared.b32 [%0], c;\n}" ::"r"(dummy) : "memory");
}
__device__ __forceinline__ void idle(int n) {
  asm volatile("{\n.reg .pred p;\n.reg .u32 a, b;\nmov.u32 a, %%clock;\nLI:\nmov.u32 b, %%clock;\nsub.u32 b, b, a;\nsetp.lt.u32 p, b, %0;\n@p bra LI;\n}" ::"r"(n) : "memory");
}
__device__ __forceinline__ void stage_store_128(uint32_t base, int lane, const uint32_t* pk) {
  const int row = (lane & 7) + ((lane >> 3) & 1) * 8;
  const uint32_t rb = base + row * 128;
  const int hi = lane >> 4;
#pragma unroll
  for (int j = 0; j < 8; j++) {
    const int chunk = 2 * j + hi;
    const uint32_t a = rb + (j >> 2) * 8192 + (((chunk & 7) ^ (lane & 7)) << 4);
    stsm4(a, pk[4 * j + 0], pk[4 * j + 1], pk[4 * j + 2], pk[4 * j + 3]);
  }
}
__device__ __forceinline__ void ln_round(float mean, float var, float& m_bf, float& inv_s) {
  const uint32_t mv = pack_bf16(mean, var);
  m_bf = bf_lo(mv);
  float sq, rc;
  asm("sqrt.approx.ftz.f32 %0, %1;" : "=f"(sq) : "f"(bf_round(bf_hi(mv) + 1e-5f)));
  asm("rcp.approx.ftz.f32 %0, %1;" : "=f"(rc) : "f"(bf_round(sq)));
  inv_s = rc;
}
__device__ __forceinline__ uint32_t hadd2_bf(uint32_t a, uint32_t b) {
  uint32_t r;
  asm("add.rn.bf16x2 %0, %1, %2;" : "=r"(r) : "r"(a), "r"(b));
  return r;
}
__device__ __forceinline__ uint32_t ln_apply(uint32_t h, uint32_t nm2, float inv_s) {
  const uint32_t d = hadd2_bf(h, nm2);
  return pack_bf16(bf_lo(d) * inv_s, bf_hi(d) * inv_s);
}
__device__ __forceinline__ void ldsm4(uint32_t* r, uint32_t addr) {
  asm volatile("ldmatrix.sync.aligned.m8n8.x4.shared.b16 {%0,%1,%2,%3}, [%4];" : "=r"(r[0]), "=r"(r[1]), "=r"(r[2]), "=r"(r[3]) : "r"(addr) : "memory");
}
__device__ __forceinline__ void mma16816(float* d, uint32_t a0, uint32_t a1, uint32_t a2, uint32_t a3, uint32_t b0, uint32_t b1) {
  asm volatile("mma.sync.aligned.m16n8k16.row.col.f32.bf16.bf16.f32 {%0,%1,%2,%3}, {%4,%5,%6,%7}, {%8,%9}, {%0,%1,%2,%3};"
               : "+f"(d[0]), "+f"(d[1]), "+f"(d[2]), "+f"(d[3]) : "r"(a0), "r"(a1), "r"(a2), "r"(a3), "r"(b0), "r"(b1));
}

template <class F>
__device__ __forceinline__ void unroll8(F f) {
  f(std::integral_constant<int, 0>{}); f(std::integral_constant<int, 1>{}); f(std::integral_constant<int, 2>{}); f(std::integral_constant<int, 3>{});
  f(std::integral_constant<int, 4>{}); f(std::integral_constant<int, 5>{}); f(std::integral_constant<int, 6>{}); f(std::integral_constant<int, 7>{});
}

constexpr float AT_C = 0.08838834764831845f * 1.4426950408889634f;
constexpr float AT_LO = 0x1p-40f, AT_HI = 0x1p40f;
constexpr int AT_R1 = 48;
template <int I0, int I1>
__device__ __forceinline__ void at_exp(float* S) {
#pragma unroll
  for (int i = I0; i < I1; i++) asm volatile("ex2.approx.ftz.f32 %0, %0;" : "+f"(S[i]));
}
template <int I0, int I1>
__device__ __forceinline__ void at_fin(const float* S, uint32_t* P) {
#pragma unroll
  for (int i = I0; i < I1; i += 4) {
    P[i / 2] = pack_bf16(S[i], S[i + 1]); P[i / 2 + 1] = pack_bf16(S[i + 2], S[i + 3]);
  }
}
__device__ __forceinline__ void at_sum(const uint32_t* P, bool half, float& l0, float& l1) {
  uint32_t u[4];
#pragma unroll
  for (int r = 0; r < 4; r++) {
    const uint32_t* q = P + (r >> 1) * 16 + (r & 1);
    u[r] = hadd2_bf(hadd2_bf(hadd2_bf(q[0], q[2]), hadd2_bf(q[4], q[6])), hadd2_bf(hadd2_bf(q[8], q[10]), hadd2_bf(q[12], q[14])));
  }
  u[0] = hadd2_bf(u[0], half ? 0u : u[2]);
  u[1] = hadd2_bf(u[1], half ? 0u : u[3]);
  l0 += bf_lo(u[0]) + bf_hi(u[0]);
  l1 += bf_lo(u[1]) + bf_hi(u[1]);
}
template <int j>
__device__ __forceinline__ void at_mask1(float* S, int d) {
  float dummy0 = 0.f, dummy1 = 0.f;
  float& lo0 = j < 7 ? S[4 * (j < 7 ? j + 1 : j) + 2] : dummy0;
  float& lo1 = j < 7 ? S[4 * (j < 7 ? j + 1 : j) + 3] : dummy1;
  asm("{\n.reg .pred p, q;\nsetp.lt.s32 p, %4, %5;\nsetp.le.s32 q, %4, %5;\n"
      "@p add.f32 %0, %0, 0fFF800000;\n@q add.f32 %1, %1, 0fFF800000;\n@p add.f32 %2, %2, 0fFF800000;\n@q add.f32 %3, %3, 0fFF800000;\n}"
      : "+f"(S[4 * j]), "+f"(S[4 * j + 1]), "+f"(lo0), "+f"(lo1) : "r"(d), "r"(8 * j));
}
__device__ __forceinline__ void at_mask(float* S, int r, int lane) {
  unroll8([&](auto jc) { at_mask1<decltype(jc)::value>(S, r + (lane >> 2) - (lane & 3) * 2); });
}
__device__ __forceinline__ uint32_t ldg32(const __nv_bfloat16* p) { return __ldcg(reinterpret_cast<const uint32_t*>(p)); }
__device__ __forceinline__ uint32_t ldg16x2(const __nv_bfloat16* p, int stride) {
  return (uint32_t)__ldcg(reinterpret_cast<const unsigned short*>(p)) | ((uint32_t)__ldcg(reinterpret_cast<const unsigned short*>(p + stride)) << 16);
}
__device__ __forceinline__ void slow_tile(float* O, uint32_t* Q, float& l0, float& l1, const __nv_bfloat16* wq, int row0, int head, int lane, uint32_t dummy) {
  const int r = lane >> 2, q = lane & 3;
#pragma unroll
  for (int i = 0; i < 64; i++) O[i] = 0.f;
  {
    const __nv_bfloat16* xa = g_xn + (size_t)(row0 + r) * DM + 2 * q;
    const __nv_bfloat16* wb = wq + (size_t)(2 * q) * NQ + head * HD + (r >> 1) * 8 + (r & 1);
#pragma unroll 1
    for (int k = 0; k < DM; k += 16) {
      const uint32_t a0 = ldg32(xa + k), a1 = ldg32(xa + k + 8 * DM), a2 = ldg32(xa + k + 8), a3 = ldg32(xa + k + 8 * DM + 8);
#pragma unroll
      for (int j = 0; j < 16; j++) {
        const __nv_bfloat16* wp = wb + (size_t)k * NQ + (j >> 2) * 32 + (j & 3) * 2;
        mma16816(O + 4 * j, a0, a1, a2, a3, ldg16x2(wp, NQ), ldg16x2(wp + 8 * NQ, NQ));
        if (j == 7) sched_fence(dummy);
      }
    }
  }
#pragma unroll
  for (int i = 0; i < 32; i++) Q[i] = pack_bf16(O[2 * i], O[2 * i + 1]);
#pragma unroll
  for (int i = 0; i < 64; i++) O[i] = 0.f;
  float m0 = -INFINITY, m1 = -INFINITY;
  l0 = l1 = 0.f;
#pragma unroll 1
  for (int kv = 0; kv <= row0; kv += 16) {
    float s[8] = {0.f, 0.f, 0.f, 0.f, 0.f, 0.f, 0.f, 0.f};
    const __nv_bfloat16* kp = g_qkv + (size_t)(SEQ + kv + r) * NQ + head * HD + 2 * q;
#pragma unroll
    for (int k = 0; k < 8; k++) {
      mma16816(s, Q[4 * k], Q[4 * k + 1], Q[4 * k + 2], Q[4 * k + 3], ldg32(kp + 16 * k), ldg32(kp + 16 * k + 8));
      mma16816(s + 4, Q[4 * k], Q[4 * k + 1], Q[4 * k + 2], Q[4 * k + 3], ldg32(kp + 8 * NQ + 16 * k), ldg32(kp + 8 * NQ + 16 * k + 8));
    }
#pragma unroll
    for (int i = 0; i < 8; i++)
      if (kv + (i >> 2) * 8 + 2 * q + (i & 1) > row0 + r + (i & 2) * 4) s[i] = -INFINITY;
    float a = fmaxf(fmaxf(fmaxf(s[0], s[1]), fmaxf(s[4], s[5])), m0), b = fmaxf(fmaxf(fmaxf(s[2], s[3]), fmaxf(s[6], s[7])), m1);
    a = fmaxf(a, __shfl_xor_sync(~0u, a, 1)); b = fmaxf(b, __shfl_xor_sync(~0u, b, 1));
    a = fmaxf(a, __shfl_xor_sync(~0u, a, 2)); b = fmaxf(b, __shfl_xor_sync(~0u, b, 2));
    const float c0 = ex2(m0 - a), c1 = ex2(m1 - b);
    m0 = a; m1 = b;
#pragma unroll
    for (int i = 0; i < 8; i++) s[i] = ex2(s[i] - ((i & 2) ? b : a));
    l0 = l0 * c0 + (s[0] + s[1]) + (s[4] + s[5]);
    l1 = l1 * c1 + (s[2] + s[3]) + (s[6] + s[7]);
    sched_fence(dummy);
    const uint32_t p0 = pack_bf16(s[0], s[1]), p1 = pack_bf16(s[2], s[3]), p2 = pack_bf16(s[4], s[5]), p3 = pack_bf16(s[6], s[7]);
    const __nv_bfloat16* vp = g_qkv + (size_t)(2 * SEQ + kv + 2 * q) * NQ + head * HD + r;
#pragma unroll
    for (int j = 0; j < 16; j++) {
      O[4 * j] *= c0; O[4 * j + 1] *= c0; O[4 * j + 2] *= c1; O[4 * j + 3] *= c1;
      mma16816(O + 4 * j, p0, p1, p2, p3, ldg16x2(vp + 8 * j, NQ), ldg16x2(vp + 8 * NQ + 8 * j, NQ));
      if (j == 7) sched_fence(dummy);
    }
  }
}

constexpr int P1_STAGE = 49152;
constexpr int SLOT = 32768;
constexpr int OFF_R3 = 0;
constexpr int OFF_BAR = 229376;
constexpr int OFF_MISC = OFF_BAR + 8 * 58;
constexpr int SMEM_BYTES = OFF_MISC + 2080 + TL_BYTES;
enum : int {
  B_FULL1 = 0, B_KF = 4, B_VF = 6, B_FULL3 = 8, B_XF = 14, B_LN = 15, B_DEP = 16, B_OUT2 = 22, B_FIN = 23, B_SET2 = 25, B_QP = 26, B_WF2 = 29,
  B_WF = 30, B_WR = 31,
  B_XE = 33, B_PUB = 34, B_OUT = 40, B_OUT3 = 41,
  B_EMPTY1 = 42, B_KE = 46, B_VE = 48, B_EMPTY3 = 50, B_WE = 56, B_NUM = 57
};
constexpr int OFF_STG = SLOT, SL_SCR = 2;
constexpr int PRE = 3;
constexpr int LN_PF = 5, LN_PFN = 2, LN_LD = 4;
constexpr int WQ_0 = 18, WQ_D = 2;
constexpr int KV_PF = 11, W_G0 = 23;
constexpr int X_KB = 20, G_KB = 35;
constexpr int SL_NS = 600, SET_NS = 50;
constexpr int OUT_CLK = 500, Y_CLK = 400;
struct Params {
  CUtensorMap xn, ckv, wq, wk, wv, kv, ctx_ld, ctx_st, wo, x, wd, wg, wu, out;
};

__global__ void __cluster_dims__(2, 1, 1) __launch_bounds__(384, 1)
fused_kernel(const __nv_bfloat16* __restrict__ x, const __nv_bfloat16* __restrict__ wq, const __nv_bfloat16* __restrict__ w_r,
             __nv_bfloat16* __restrict__ out, const __grid_constant__ Params p) {
  extern __shared__ __align__(1024) uint8_t sp[];
  const uint32_t sb = s2u(sp);
  const uint32_t bar = sb + OFF_BAR;
  auto B = [&](int i) { return bar + 8 * i; };
  const int tid = threadIdx.x, warp = __shfl_sync(~0u, tid >> 5, 0), wg = warp >> 2, lane = tid & 31;
  const int cta = blockIdx.x, rank = cta & 1, cl = cta >> 1;
  const int mp = cl < 4 ? 1 : (cl < 36 ? (cl & 7) : (0x3207654 >> (4 * ((cl - 36) % 7))) & 7);
  const int gq = cl < 4 ? 4 + cl : (cl < 36 ? (cl - 4) >> 3 : 4 + (cl - 36) / 7);
  const int mt = 2 * mp + rank;
  const int ti = (gq & 3) * 2 + rank, hh = mp * 2 + (gq >> 2);
  const int rid = mt * 8 + gq;
  const int fid = mt * 7 + gq - 1;
  const bool ffn = gq > 0;
  uint4* const xr = g_xr + rid * XR_SIZE;
  TL_INIT();
  TL(0, 0, tid == 128);
  if (warp == 0) {
    if (elect_one()) {
#pragma unroll
      for (int kb = 0; kb < PRE; kb++) mbar_init(B(B_FULL1 + kb), 1);
      asm volatile("fence.mbarrier_init.release.cluster;" ::: "memory");
    }
    __syncwarp();
    cluster_arrive();
    if (elect_one()) {
#pragma unroll
      for (int kb = 0; kb < PRE; kb++) {
        mbar_expect(B(B_FULL1 + kb), P1_STAGE);
        tma_ld2(sb + kb * P1_STAGE, &p.ckv, B(B_FULL1 + kb), kb * 64, mt * 128);
        tma_ld3(sb + kb * P1_STAGE + 16384 + rank * 16384, &p.wk, B(B_FULL1 + kb), 0, kb * 64, (gq + 8) * 4 + rank * 2);
        tma_ld3(sb + kb * P1_STAGE + 32768 - rank * 16384, &p.wk, B(B_FULL1 + kb), 0, kb * 64, (gq + 8) * 4 + 2 - rank * 2);
      }
    }
  } else if (elect_one()) {
#pragma unroll 1
    for (int i = PRE + warp - 1; i < B_NUM; i += 11)
      mbar_init(B(i), i >= B_EMPTY1 ? 16 : (i >= B_XE ? 8 : (i >= B_WF ? 2 : 1)));
    asm volatile("fence.mbarrier_init.release.cluster;" ::: "memory");
  }
  __syncwarp();
  if (warp) cluster_arrive();
  if (wg == 0) {
    reg_dealloc<40>();
    if (warp == 1 && elect_one()) {
      if (mt >= 2 * PRE) tma_pf3(&p.wk, 0, mp * 64, (gq + 8) * 4 + rank * 2);
      if (gq >= PRE) asm volatile("cp.async.bulk.prefetch.tensor.2d.L2.global [%0, {%1,%2}];" ::"l"(&p.ckv), "r"(gq * 64), "r"(mt * 128) : "memory");
    } else if (warp == 2 && elect_one()) {
      prefetch_tm(&p.wv); prefetch_tm(&p.wq); prefetch_tm(&p.xn);
    }
    __syncwarp();
    cluster_wait();
    if (warp == 0) {
      int st = PRE; uint32_t ph = 1;
#pragma unroll 1
      for (int t = 0; t < 6; t++) {
        const CUtensorMap* ma = t >= 4 ? &p.xn : &p.ckv;
        const CUtensorMap* mb = t >= 4 ? &p.wq : ((t & 1) ? &p.wv : &p.wk);
        const int nk = t >= 4 ? 16 : 8;
        const int row = (t < 4 ? mt : (t == 4 ? 15 - ti : ti)) * 128;
        const int col = t < 4 ? (gq + ((t >> 1) ^ 1) * 8) * 4 + rank * 2 : (hh + rank * 16) * 2;
        if (t >= 4) mbar_wait(B(B_DEP + t - 4), 0);
#pragma unroll 1
        for (int kb = t ? 0 : PRE; kb < nk; kb++) {
          const uint32_t d = sb + st * P1_STAGE, fb = B(B_FULL1 + st);
          const int n = t * 8 + kb;
          const bool la = t == 0 || t >= 4 || (kb & 5) == 5, lb = t < 5 || kb >= 4;
          const int k0 = (t == 5 ? (kb + 12) & 15 : kb ^ ((t & kb & 1) * 4)) * 64;
          mbar_wait_c(B(B_EMPTY1 + st), ph);
          if (elect_one()) {
            mbar_expect(fb, la * 16384 + lb * 32768);
            if (la) tma_ld2(t == 0 && (kb & 5) == 4 ? sb + 6 * SLOT + (kb & 2) * 8192 : d, ma, fb, k0, row);
            if (lb) tma_ld3_mc(d + 16384 + rank * 16384, mb, fb, 0, k0, col, 3);
          }
          if (t < 5 && elect_one()) {
            if (n >= LN_PF && n < LN_PF + LN_PFN) l2_prefetch(x + (size_t)cta * 16 * DM + (n - LN_PF) * (16 * DM / LN_PFN), 32768 / LN_PFN);
            if (n == LN_LD) mbar_arrive(B(B_LN));
            if (t < 3 && kb == (t ? 0 : 4)) tma_pf3((t & 1) ? &p.wk : &p.wv, 0, mp * 64, (gq + (((t + 1) >> 1) ^ 1) * 8) * 4 + rank * 2);
            if (n >= WQ_0 && n < WQ_0 + 4 * WQ_D && (n - WQ_0) % WQ_D == 0) tma_pf3(&p.wq, 0, ((n - WQ_0) / WQ_D * 4 + (gq & 3)) * 64, (hh + rank * 16) * 2);
          }
          if (++st == 4) { st = 0; ph ^= 1; }
        }
      }
      if (elect_one()) { prefetch_tm(&p.kv); prefetch_tm(&p.ctx_ld); prefetch_tm(&p.wo); prefetch_tm(&p.wg); prefetch_tm(&p.wu); }
      int seq0, seq1;
      {
        const int G = ti & 6, own = rank ? G + 33 : 31 - G, j = 18 - lane;
        seq0 = lane < 13 - G ? (lane < G ? lane : lane + 2) : (lane <= 14 - G ? 14 - lane : (lane == 15 - G ? own : (lane == 16 - G ? G + 32 : 16 - lane)));
        seq1 = lane <= G + 1 ? lane : (lane == G + 2 ? G + 32 : (lane == G + 3 ? own : (j > G + 1 ? j : j - 2)));
      }
      auto load_kv = [&](int g, int isv) {
        const int h2 = g >= 17, sx = g - 17 * h2, b = __shfl_sync(~0u, h2 ? seq1 : seq0, sx);
        const int row = (1 + isv) * SEQ + (b & 15) * 128, col = (hh + 16 * h2) * 2;
        const uint32_t d = sb + (isv ? 2 + 2 * (g & 1) : (g & 1)) * SLOT, fb = B(B_KF + 2 * isv + (g & 1));
        const bool ef = (b & 8) || sx >= 11;
        const int n3 = g - KV_PF;
        const int pb = ti >= 6 && n3 >= 0 && n3 < 16 ? (n3 < 4 ? n3 : (n3 >= 12 ? 23 - n3 : ((n3 & 1) ? (n3 + 3) >> 1 : 17 - (n3 >> 1)))) : -1;
        mbar_wait_c(g < 2 ? B(B_EMPTY1 + (isv ? 1 + 2 * g : g)) : B(B_KE + 2 * isv + (g & 1)), g < 2 ? 1 : ((g >> 1) & 1) ^ 1);
        if (elect_one()) {
          mbar_expect(fb, b < 32 ? SLOT : 0);
          if (b < 16) {
            tma_ld3_mc(d + rank * 16384, &p.kv, fb, 0, row, col + rank, 3, ef);
          } else if (b < 32) {
            tma_ld3(d, &p.kv, fb, 0, row, col, ef);
            tma_ld3(d + 16384, &p.kv, fb, 0, row, col + 1, ef);
          }
          if (pb >= 0) tma_pf3(&p.kv, 0, (1 + isv) * SEQ + pb * 128, (hh + 16) * 2 + rank);
        }
      };
      int nw = ffn ? 0 : 12;
      auto load_w = [&]() {
        const int c = nw < 8 ? (nw >> 2) + (nw & 2) : nw >> 1;
        if (elect_one()) {
          if (!(nw & 3)) mbar_expect(B(B_WF - (nw >> 3)), 32768);
          tma_ld2(sb + (c < 2 ? 3 : 4) * SLOT + c * 16384 + (nw & 1) * 8192, (nw & 1) ? &p.wg : &p.wu, B(B_WF - (nw >> 3)), fid * 32, c * 128, true);
        }
        nw++;
      };
#pragma unroll 1
      for (int g = 0; g < 34; g++) {
        if (g == 0 || g == KV_PF) mbar_wait(B(B_DEP + 2 + (g > 0)), 0);
        load_kv(g, 0);
        if (g > 0) load_kv(g - 1, 1);
        if (g >= W_G0 && nw < 12 && __all_sync(~0u, mbar_test(B(B_QP + (nw >> 2)), 0))) load_w();
      }
      load_kv(33, 1);
#pragma unroll 1
      while (nw < 12) { mbar_wait(B(B_QP + (nw >> 2)), 0); load_w(); }
      if (elect_one()) { prefetch_tm(&p.wd); prefetch_tm(&p.x); prefetch_tm(&p.out); }
      auto load3 = [&](int kb, int sl) {
        if (elect_one()) {
          mbar_expect(B(B_FULL3 + sl), SLOT);
          tma_ld2(sb + OFF_R3 + sl * SLOT, &p.ctx_ld, B(B_FULL3 + sl), kb * 64, mt * 128, true);
          tma_ld3_mc(sb + OFF_R3 + sl * SLOT + 16384 + rank * 8192, &p.wo, B(B_FULL3 + sl), 0, kb * 64, gq * 2 + rank, 3);
        }
      };
      mbar_wait(B(B_DEP + 4), 0);
#pragma unroll
      for (int kb = 0; kb < 5; kb++) {
        mbar_wait_c(B(kb == 3 ? B_WE : (kb == 4 ? B_VE + 1 : B_KE + kb)), 0);
        load3(kb, kb);
      }
      if (elect_one()) mbar_arrive(B(B_FULL3 + 5));
#pragma unroll 1
      for (int r = 1; r < 11; r++) {
#pragma unroll
        for (int j = 0; j < 6; j++) {
          if (j == 5 && r == 10) break;
          if (j == 3 && r == 5) mbar_wait(B(B_DEP + 5), 0);
          mbar_wait_c(B(B_EMPTY3 + j), ~r & 1);
          load3(r * 6 + j - 1, j);
          if (j == 5 && r == 9 && elect_one()) l2_prefetch(xr, XR_CAND * 16);
        }
      }
      if (ffn) {
#pragma unroll
        for (int j = 1; j >= 0; j--) {
          mbar_wait(B(B_EMPTY3 + 5 * j), j);
          if (elect_one()) {
            mbar_expect(B(B_FULL3 + 5 * j), SLOT);
            tma_ld3(sb + OFF_R3 + 5 * j * SLOT, &p.wd, B(B_FULL3 + 5 * j), 0, fid * 32, 8 * j, true);
          }
        }
      }
    } else {
      if (warp >= 2) {
#pragma unroll 1
        for (int i = tid - 64; i < XR_CAND; i += 64) xr[i] = make_uint4(~0u, ~0u, ~0u, ~0u);
        if (warp == 2) { __syncwarp(); if (lane == 0) mbar_arrive(B(B_WR)); }
      }
      if (warp == 3) {
        float ws = 0.f;
#pragma unroll
        for (int j = 0; j < 4; j++) {
          const uint4 q = __ldg(reinterpret_cast<const uint4*>(w_r) + j * 32 + lane);
          ws += bf_lo(q.x) + bf_hi(q.x) + bf_lo(q.y) + bf_hi(q.y) + bf_lo(q.z) + bf_hi(q.z) + bf_lo(q.w) + bf_hi(q.w);
        }
#pragma unroll
        for (int o = 16; o; o >>= 1) ws += __shfl_xor_sync(~0u, ws, o);
        uint2* tab = reinterpret_cast<uint2*>(sp + OFF_MISC + 512);
        tab[lane] = make_uint2(0x3F803F80u, 0x3F803F80u);
        tab[32 + lane] = __ldg(reinterpret_cast<const uint2*>(w_r + gq * 128) + lane);
        if (lane == 0) *reinterpret_cast<float*>(sp + OFF_MISC + 1024) = ws;
        __syncwarp();
        if (lane == 0) mbar_arrive(B(B_WR));
      }
      if (tid == 32) TS(0);
      mbar_wait(B(B_LN), 0);
      const uint4* src = reinterpret_cast<const uint4*>(x + (size_t)(cta * 16 + warp - 1) * DM) + lane;
      uint4* dst = reinterpret_cast<uint4*>(g_xn + (size_t)(cta * 16 + warp - 1) * DM) + lane;
      uint4 v[4];
#pragma unroll
      for (int j = 0; j < 4; j++) v[j] = __ldcs(src + j * 32);
#pragma unroll 1
      for (int r = warp - 1; r < 16; r += 3) {
        float a0 = 0.f, a1 = 0.f, b0 = 0.f, b1 = 0.f;
#pragma unroll
        for (int j = 0; j < 4; j++) {
          const uint32_t u[4] = {v[j].x, v[j].y, v[j].z, v[j].w};
#pragma unroll
          for (int i = 0; i < 4; i++) { const float a = bf_lo(u[i]), b = bf_hi(u[i]); a0 += a; a1 += b; b0 = fmaf(a, a, b0); b1 = fmaf(b, b, b1); }
        }
        a0 += a1; b0 += b1;
#pragma unroll
        for (int o = 16; o; o >>= 1) { a0 += __shfl_xor_sync(~0u, a0, o); b0 += __shfl_xor_sync(~0u, b0, o); }
        const float mean = a0 * (1.f / DM);
        float mb, inv;
        ln_round(mean, fmaxf(fmaf(b0, 1.f / DM, -mean * mean), 0.f), mb, inv);
        inv *= AT_C;
        const uint32_t nm2 = pack_bf16(-mb, -mb);
        src += 384;
#pragma unroll
        for (int j = 0; j < 4; j++) {
          dst[j * 32] = make_uint4(ln_apply(v[j].x, nm2, inv), ln_apply(v[j].y, nm2, inv), ln_apply(v[j].z, nm2, inv), ln_apply(v[j].w, nm2, inv));
          sched_fence(sb + lane);
          if (r < 13) v[j] = __ldcs(src + j * 32);
        }
        dst += 384;
      }
      __syncwarp();
      if (lane == 0) {
        fence_gpu();
        red_add(&g_cnt[C_LN + (cta >> 3)], 1);
      }
      TL(3, warp, lane == 0);
      __syncwarp();
      if (warp == 3) {
        if (lane == 0) {
#pragma unroll 1
          for (int i = 0; i < 6; i++) {
            const int c = i < 2 ? C_LN + (i ? ti : 15 - ti) : (i < 4 ? C_QKV + (i - 2) * 8 + mp : C_CTX + (i - 4) * 16 + mt);
            spin_until_ge<true>(&g_cnt[c], i < 2 ? 24 : 16);
            fence_async_all();
            mbar_arrive(B(B_DEP + i));
            TL(3, 4 + i, true);
          }
        }
      } else if (warp == 1 && elect_one()) {
        mbar_wait(B(B_WR), 0);
#pragma unroll 1
        for (int i = 0; i < 6; i++) {
          const int c = i < 2 ? C_QKV + gq + (i ^ 1) * 8 : C_CTX + (i >> 2) * 16 + ((i == 3 || i == 4) ? ti : 15 - ti);
          mbar_wait(B(B_PUB + i), 0);
          if (i >= 2 && i < 5) {
            asm volatile("fence.proxy.async.shared::cta;" ::: "memory");
#pragma unroll 1
            for (int n = 0; n < 8; n++) {
              const int h = n >> 2, a = n & 3;
              asm volatile("cp.async.bulk.tensor.3d.global.shared::cta.bulk_group [%0, {%2,%3,%4}], [%1];" ::"l"(&p.ctx_st),
                           "r"(sb + (i == 4 ? 6 * SLOT + h * 16384 : (3 + 2 * h) * SLOT + (i - 2) * 16384) + a * 4096),
                           "r"(0), "r"((i == 2 ? 15 - ti : ti) * 128 + h * 64), "r"((hh + (i >> 2) * 16) * 4 + a) : "memory");
              asm volatile("cp.async.bulk.commit_group;\ncp.async.bulk.wait_group.read 0;" ::: "memory");
            }
            mbar_arrive(B(B_QP + i - 2));
            asm volatile("cp.async.bulk.wait_group 0;" ::: "memory");
          }
          fence_gpu();
          red_add(&g_cnt[c], 1);
          TS(1 + i);
        }
      }
      if (warp == 2) {
#pragma unroll 1
        for (int n = 0; n < 8; n++) {
          if (!(n & 3)) mbar_wait(B(B_XE), n >> 2);
          if ((n < 4 || ffn) && elect_one()) {
            const uint32_t fb = B(n < 4 ? B_XF : B_WF2), d = sb + 6 * SLOT + (n & 3) * 8192;
            if (!(n & 3)) mbar_expect(fb, 32768);
            if (n < 4) tma_ld3(d, &p.x, fb, 0, mt * 128 + (n >> 1) * 64, gq * 2 + (n & 1), true);
            else tma_ld2(d, (n & 1) ? &p.wg : &p.wu, fb, fid * 32, (4 + (n >> 1)) * 128, true);
          }
          __nanosleep(SL_NS);
        }
#pragma unroll 1
        for (int i = XR_CAND + lane; i < XR_SIZE; i += 32) { xr[i] = make_uint4(~0u, ~0u, ~0u, ~0u); __nanosleep(SET_NS); }
        __syncwarp();
        if (lane == 0) { fence_gpu(); mbar_arrive(B(B_SET2)); }
        TL(2, 26, lane == 0);
        __syncwarp();
      }
      __syncwarp();
      cluster_arrive();
      if (warp == 3) {
        mbar_wait(B(B_OUT), 0);
        uint4 kv[2];
        poll_chunks(kv, g_xr + ((lane >> 1) * 8 + gq) * XR_SIZE + XR_KEY + (lane & 1) * 2, 1);
        const uint32_t a1 = max(kv[0].x, kv[0].z), a2 = max(min(kv[0].x, kv[0].z), max(kv[0].y, kv[0].w));
        const uint32_t b1 = max(kv[1].x, kv[1].z), b2 = max(min(kv[1].x, kv[1].z), max(kv[1].y, kv[1].w));
        const uint32_t k1 = max(a1, b1), k2 = max(min(a1, b1), max(a2, b2));
        const uint32_t m1 = __reduce_max_sync(~0u, k1);
        const uint32_t m2 = __reduce_max_sync(~0u, k1 == m1 ? k2 : k1);
        auto cand = [&](uint32_t k) { return (((~k >> 7) & 15) * (8 * XR_SIZE) + ((~k >> 4) & 7) * 64) * 16; };
        const uint32_t o1 = cand(m1), o2 = cand(m2) + (((m1 ^ m2) & 0x7FF0) ? 0 : 256);
        if (lane == 0) {
          *reinterpret_cast<uint4*>(sp + OFF_MISC) = make_uint4(m1, m2, o1, o2);
          mbar_arrive(B(B_OUT2));
        }
        const uint32_t key = (lane & 4) ? m2 : m1;
        const uint4* src = g_xr + (((~key >> 7) & 15) * 8 + (rid >> 4)) * XR_SIZE;
        poll_chunks(kv, g_xr + (((lane & 4) ? o2 : o1) >> 4) + (rid >> 4) * XR_SIZE + XR_CAND + (rid & 12) + (lane & 3), 32);
        uint32_t u = key >> 16;
        u = (u & 0x8000u) ? (u & 0x7FFFu) : (~u & 0xFFFFu);
        const float rs = bf_round(sigmoid(__uint_as_float(u << 16)));
        if (lane < 8)
          *reinterpret_cast<uint4*>(sp + OFF_MISC + 128 + lane * 16) = make_uint4((rid & 2) ? ((rid & 1) ? kv[0].w : kv[0].z) : ((rid & 1) ? kv[0].y : kv[0].x),
              (rid & 2) ? ((rid & 1) ? kv[1].w : kv[1].z) : ((rid & 1) ? kv[1].y : kv[1].x), __float_as_uint(rs), 0);
#pragma unroll 1
        for (int n = 0; n < 0x400000; n++) {
          uint32_t v;
          asm volatile("ld.acquire.gpu.global.u32 %0, [%1];" : "=r"(v) : "l"(src + XR_FLAG) : "memory");
          if (__all_sync(~0u, v == 0)) break;
        }
        __syncwarp();
        if (lane == 0) mbar_arrive(B(B_FIN));
      }
      if (warp == 1 && elect_one()) {
        mbar_wait(B(B_OUT3), 0);
        auto owner = [&]() {
          uint2 top;
          asm volatile("ld.shared.v2.u32 {%0,%1}, [%2];" : "=r"(top.x), "=r"(top.y) : "r"(sb + OFF_MISC) : "memory");
          return (0x7FFF - (top.x & 0x7FFF)) >> 7 == mt || (0x7FFF - (top.y & 0x7FFF)) >> 7 == mt;
        };
#pragma unroll 1
        for (int n = 0; n < 4; n++) {
          if (n && !(mbar_test(B(B_OUT2), 0) && owner())) idle(OUT_CLK);
          asm volatile("cp.async.bulk.tensor.2d.global.shared::cta.bulk_group [%0, {%2,%3}], [%1];" ::"l"(&p.out), "r"(sb + OFF_STG + n * 8192),
                       "r"(gq * 128 + (n & 1) * 64), "r"(mt * 128 + (n >> 1) * 64) : "memory");
        }
        asm volatile("cp.async.bulk.commit_group;" ::: "memory");
        mbar_wait(B(B_OUT2), 0);
        if (owner()) {
          asm volatile("cp.async.bulk.wait_group 0;" ::: "memory");
          asm volatile("st.release.gpu.global.u32 [%0], 0;" ::"l"(xr + XR_FLAG) : "memory");
        } else {
          asm volatile("cp.async.bulk.wait_group.read 0;" ::: "memory");
        }
        TL(2, 25, true);
      }
    }
    __syncwarp();
    if (warp == 0) cluster_arrive();
    cluster_wait();
    TL_DUMP();
    if (tid == 32) TS(8);
  } else {
    reg_alloc<232>();
    cluster_wait();
    const int w = wg - 1, cw = warp - 4;
    int lane = lane_id();
    const uint32_t stg = sb + OFF_STG + w * 16384 + (cw & 3) * 2048;
    auto publish = [&](int i) { __syncwarp(); if (lane == 0) mbar_arrive(B(B_PUB + i)); };
    uint32_t rbar;
    asm("mapa.shared::cluster.u32 %0, %1, %2;" : "=r"(rbar) : "r"(bar), "r"(lane & 1));
    auto release2 = [&](int i) { if (lane < 2) asm volatile("mbarrier.arrive.shared::cluster.b64 _, [%0];" ::"r"(rbar + 8 * i) : "memory"); };
    float R[128];
    float O[64], acc[64];
    uint32_t pk[64];
    uint32_t* const Q = pk;
    uint32_t P[32];
    auto packed = [&](int i) {
      const float* v = R + 16 * (i >> 1) + 2 * (i & 1);
      return make_uint4(pack_bf16(v[0], v[1]), pack_bf16(v[4], v[5]), pack_bf16(v[8], v[9]), pack_bf16(v[12], v[13]));
    };
    const uint32_t q_st = sb + (cw & 3) * 1024 + (lane >> 2) * 64 + (((lane & 3) ^ (lane >> 3)) << 4);
    const uint32_t q_ld = sb + (cw & 3) * 1024 + (lane & 15) * 64 + (((lane >> 4) ^ ((lane >> 1) & 3)) << 4);
    auto park = [&](uint32_t off, int i, uint4 v) {
      asm volatile("st.shared.v4.u32 [%0], {%1,%2,%3,%4};" ::"r"(q_st + off + (i >> 1) * 4096 + (i & 1) * 512), "r"(v.x), "r"(v.y), "r"(v.z), "r"(v.w) : "memory");
    };
    auto load_q = [&](uint32_t off, int k) { ldsm4(Q + 4 * k, ((q_ld + off) ^ ((k & 1) << 5)) + (k >> 1) * 4096); };
    {
      TL(0, 1, tid == 128);
      __nv_bfloat16* pdst = g_qkv;
      auto put2 = [&](int j) {
#pragma unroll
        for (int i = (j >> 1) * 4 + (j & 1); i < (j >> 1) * 4 + 4; i += 2)
          __stcs(reinterpret_cast<uint4*>(pdst + (i & 1) * 8 * NQ + (i >> 1) * 32), make_uint4(pk[4 * i], pk[4 * i + 1], pk[4 * i + 2], pk[4 * i + 3]));
      };
      const uint64_t da0 = mk_desc(sb + w * 8192, 16, 1024, 1);
      const uint64_t db0 = mk_desc(sb + 16384, 8192, 1024, 1);
      int st = 0; uint32_t ph = 0;
      auto issue = [&](int accum, auto between, bool res = false) {
        mbar_wait_c(B(B_FULL1 + st), ph);
        const uint64_t da = desc_add(da0, res ? 6 * SLOT + st * 8192 : st * P1_STAGE), db = desc_add(db0, st * P1_STAGE);
        between();
        wg_fence();
#pragma unroll
        for (int k = 0; k < 4; k++) mma_n256_ss<1>(R, desc_add(da, k * 32), desc_add(db, k * 2048), k == 0 ? accum : 1);
        wg_commit();
      };
      issue(0, []() {});
#pragma unroll 1
      for (int t = 0;; t++) {
        const int nk = t >= 4 ? 16 : 8;
        const bool tr = t > 0 && t < 5;
        TL(0, 2 + 2 * t + 16 * w, (tid & 127) == 0);
        int prev = st;
        if (++st == 4) { st = 0; ph ^= 1; }
#pragma unroll 1
        for (int kb = 1; kb < nk; kb++) {
          if (kb == nk - 1 && w == 1) bar_sync(5, 256);
          issue(1, []() {}, t < 4 && (kb & 5) == 4);
          if (kb == nk - 1 && w == 0) bar_arrive(5, 256);
          if (tr) {
#pragma unroll
            for (int i = 1; i < 8; i++) if (kb == i) put2(i);
            if (kb == 7 && !(t & 1)) publish((t >> 1) - 1);
          } else if (t == 5) {
            if (kb == 2) {
#pragma unroll
              for (int i = 0; i < 8; i++) park(6 * SLOT + w * 16384, i, make_uint4(pk[4 * i], pk[4 * i + 1], pk[4 * i + 2], pk[4 * i + 3]));
              __syncwarp();
            }
            if (kb == 4) {
#pragma unroll
              for (int k = 0; k < 8; k++) load_q(6 * SLOT + w * 16384, k);
              __syncwarp();
            }
            if (kb == 6) {
#pragma unroll
              for (int i = 0; i < 8; i++) park(6 * SLOT + w * 16384, i, make_uint4(pk[32 + 4 * i], pk[33 + 4 * i], pk[34 + 4 * i], pk[35 + 4 * i]));
            }
          }
          wg_wait<1>();
          release2(B_EMPTY1 + prev);
          prev = st;
          if (++st == 4) { st = 0; ph ^= 1; }
        }
        if (t == 5) break;
        issue(0, [&]() {
          sched_fence(q_st);
          wg_wait<0>();
          fence_regs<128>(R);
          TL(0, 3 + 2 * t + 16 * w, (tid & 127) == 0);
#pragma unroll
          for (int i = 0; i < 16; i++) { const uint4 v = packed(i); pk[4 * i] = v.x; pk[4 * i + 1] = v.y; pk[4 * i + 2] = v.z; pk[4 * i + 3] = v.w; }
          release2(B_EMPTY1 + prev);
          fence_regs<128>(R);
        });
        if (w == 1) bar_arrive(4, 256);
        sched_fence(q_st);
        pdst = g_qkv + (size_t)(((t & 1) + 1) * SEQ + mt * 128 + cw * 16 + (lane >> 2)) * NQ + (gq + ((t >> 1) ^ 1) * 8) * 256 + (lane & 3) * 8;
        if (t < 4) put2(0);
        if (w == 0) bar_sync(4, 256);
      }
      if (w == 1) bar_arrive(6, 256);
      mbar_wait_c(B(B_KF), 0);
      sched_fence(q_st);
      wg_wait<0>();
      fence_regs<128>(R);
      release2(B_EMPTY1 + 3);
      TL(0, 13 + 16 * w, (tid & 127) == 0);
    }
    auto issue3 = [&](int st, uint32_t ph, int accum) {
      mbar_wait_c(B(B_FULL3 + st), ph);
      const uint64_t da = mk_desc(sb + OFF_R3 + w * 8192 + st * SLOT, 16, 1024, 1), db = mk_desc(sb + OFF_R3 + 16384 + st * SLOT, 8192, 1024, 1);
      wg_fence();
#pragma unroll
      for (int k = 0; k < 4; k++) mma_n128_ss<1>(acc, desc_add(da, k * 32), desc_add(db, k * 2048), k == 0 ? accum : 1);
      wg_commit();
    };
    uint32_t wf[128];
    auto w_addr = [&](uint32_t off, int m) {
      const uint32_t w_ld = sb + ((lane >> 3) & 1) * 8192 + ((cw >> 1) * 32 + (lane & 7) + (lane >> 4) * 8) * 64 + ((((cw & 1) * 2) ^ ((lane >> 1) & 3)) << 4);
      return ((w_ld + off) ^ ((m & 1) << 4)) + (m >> 2) * 16384 + ((m >> 1) & 1) * 1024;
    };
    auto grab = [&](uint32_t* d, uint32_t off, int m0, int m1) {
#pragma unroll
      for (int m = m0; m < m1; m++)
        asm volatile("ldmatrix.sync.aligned.m8n8.x4.trans.shared.b16 {%0,%1,%2,%3}, [%4];"
                     : "=r"(d[4 * m]), "=r"(d[4 * m + 1]), "=r"(d[4 * m + 2]), "=r"(d[4 * m + 3]) : "r"(w_addr(off, m)) : "memory");
    };
    float inv[2] = {0.f, 0.f};
    auto scaled = [&](int i) {
      const float* o = O + 16 * (i >> 1) + 2 * (i & 1);
      const float c = inv[i & 1];
      return make_uint4(pack_bf16(o[0] * c, o[1] * c), pack_bf16(o[4] * c, o[5] * c), pack_bf16(o[8] * c, o[9] * c), pack_bf16(o[12] * c, o[13] * c));
    };
    {
      const int wrow = cw * 16;
      const uint64_t dk0 = mk_desc(sb, 16, 1024, 1);
      const uint64_t dv0 = mk_desc(sb + 2 * SLOT, 16384, 1024, 1);
      const uint32_t pin = sb + OFF_MISC + 1028;
      float l0 = 0.f, l1 = 0.f;
      int g = 0, t = 0;
      uint32_t fail = 0;
      auto piece = [&](int tt) { return (uint32_t)(tt == 3 ? 6 * SLOT + w * 16384 : (3 + 2 * w) * SLOT + (tt - 1) * 16384); };
      uint32_t par = 0;
      auto issue_s = [&](float* S) {
        const uint64_t dk = desc_add(dk0, par * 16);
        mma_n128_rs0(S, Q, dk);
#pragma unroll
        for (int k = 1; k < 8; k++) mma_n128_rs<0>(S, Q + 4 * k, desc_add(dk, (k >> 2) * 16384 + (k & 3) * 32), 1);
        wg_commit();
      };
      auto issue_pv = [&](bool half, int accum) {
        const uint64_t dv = desc_add(dv0, ((g - 1) & 1) * 2 * SLOT);
        wg_fence();
#pragma unroll
        for (int k = 0; k < 4; k++) mma_n128_rs<1>(O, P + 4 * k, desc_add(dv, k * 2048), k == 0 ? accum : 1);
        wg_commit();
        if (UNLIKELY(half)) {
          wg_fence();
          wg_commit();
        } else {
          wg_fence();
#pragma unroll
          for (int k = 4; k < 8; k++) mma_n128_rs<1>(O, P + 4 * k, desc_add(dv, k * 2048), 1);
          wg_commit();
        }
        bar_arrive(2 - w, 256);
        wg_wait<2>();
        fence_regs<32>(Q);
      };
      auto release_k = [&]() { release2(B_KE); rbar ^= 8; };
      auto pv_done = [&]() {
        TC(g, 3);
        sched_fence(q_st);
        wg_wait<0>();
        fence_regs<64>(O); fence_regs<32>(P);
        TC(g, 4);
        release2(B_VE);
      };
      auto row_inv = [&](bool go) {
        float a = l0 + __shfl_xor_sync(~0u, l0, 1), b = l1 + __shfl_xor_sync(~0u, l1, 1);
        a += __shfl_xor_sync(~0u, a, 2); b += __shfl_xor_sync(~0u, b, 2);
        const bool ok = __all_sync(~0u, a >= AT_LO && a <= AT_HI && b >= AT_LO && b <= AT_HI) != 0;
        asm("rcp.approx.ftz.f32 %0, %1;" : "=f"(inv[0]) : "f"(a));
        asm("rcp.approx.ftz.f32 %0, %1;" : "=f"(inv[1]) : "f"(b));
        fail |= (uint32_t)(go && !ok) << t;
        l0 = go ? 0.f : l0; l1 = go ? 0.f : l1;
        t += go;
      };
      const uint64_t m_first = 1ull | (1ull << (16 - ti)) | (1ull << 17) | (1ull << (18 + ti));
      const uint64_t m_diag = (1ull << (15 - ti - 2 * rank)) | (1ull << (16 - ti)) | (9ull << (17 + ti));
      enum { F_FIRST = 1, F_DIAG = 2, F_LAST = 4, F_PFIRST = 8, F_PHALF = 16, F_STOP = 32 };
      auto kind = [&](int gn) {
        const uint32_t a = (uint32_t)((m_first << 1) >> gn), d = (uint32_t)((m_diag << 1) >> gn);
        return ((a >> 1) & 1) * F_FIRST | ((d >> 1) & 1) * F_DIAG | ((a >> 2) & 1) * F_LAST | (a & 1) * F_PFIRST |
               (w == 0 ? (d & 1) * F_PHALF | ((d >> 1) & 1) * F_STOP : 0) | (gn == 34 ? F_STOP : 0);
      };
      uint32_t kinds;
      {
        uint32_t qt[64];
#pragma unroll
        for (int i = 0; i < 16; i++) { const uint4 v = packed(i); qt[4 * i] = v.x; qt[4 * i + 1] = v.y; qt[4 * i + 2] = v.z; qt[4 * i + 3] = v.w; }
        fence_regs<64>(qt);
        sched_fence(q_st);
        float S[64];
        wg_fence();
        issue_s(S);
        bar_arrive(w ? 1 : 7, 256);
        bar_sync(6 + w, 256);
        sched_fence(q_st);
        TL(1, 0, tid == 128);
#pragma unroll
        for (int i = 0; i < 16; i++) park(piece(1), i, make_uint4(qt[4 * i], qt[4 * i + 1], qt[4 * i + 2], qt[4 * i + 3]));
        kinds = pinned(kind(lane + 3));
        sched_fence(q_st);
        wg_wait<0>();
        fence_regs<64>(S);
        release_k();
        TL(1, 1, tid == 128);
        const bool kok = mbar_try(B(B_KF + 1), 0);
        at_exp<0, 32>(S);
        sched_fence(q_st);
        at_exp<32, 64>(S); at_fin<0, 64>(S, P);
        if (UNLIKELY(!kok)) mbar_wait_c(B(B_KF + 1), 0);
        TL(1, 2, tid == 128);
      }
      uint32_t f = F_PFIRST, fn;
      auto shadow = [&]() {
        const bool vok = mbar_try(B(B_VF + ((g - 1) & 1)), ((g - 1) >> 1) & 1);
        at_sum(P, f & F_PHALF, l0, l1);
        fn = __shfl_sync(~0u, kinds, max(g - 2, 0));
        if (UNLIKELY(!vok)) mbar_wait_c(B(B_VF + ((g - 1) & 1)), ((g - 1) >> 1) & 1);
      };
      auto hand_over = [&]() { __syncwarp(); if (lane == 0 && !((fail >> (t - 1)) & 1)) mbar_arrive(B(B_PUB + 1 + t)); };
      auto exp_q = [&](float* S, auto kc, auto nc) {
        constexpr int k = decltype(kc)::value, n = decltype(nc)::value;
        asm volatile("{\n.reg .pred p;\nsetp.ne.b32 p, %5, 0;\n@p ldmatrix.sync.aligned.m8n8.x4.shared.b16 {%0,%1,%2,%3}, [%4];\n}"
                     : "+r"(Q[4 * k]), "+r"(Q[4 * k + 1]), "+r"(Q[4 * k + 2]), "+r"(Q[4 * k + 3])
                     : "r"(((q_ld + piece(t + 1)) ^ ((k & 1) << 5)) + (k >> 1) * 4096), "r"(f & F_LAST) : "memory");
        at_exp<n * k, n * k + n>(S);
      };
      g = 1; par = SLOT / 16;
#pragma unroll 1
      for (;;) {
        {
          TC(g, 0);
          bar_sync(1 + w, 256);
          fence_regs<32>(Q);
          float S[64];
          wg_fence();
          issue_s(S);
          sched_fence(q_st);
          TC(g, 1);
          shadow();
          fence_regs<64>(O); fence_regs<32>(P);
          issue_pv(f & F_PHALF, ~f & F_PFIRST);
          fence_regs<64>(S);
          TC(g, 2);
          release_k();
          at_exp<0, 8>(S);
          const bool first = f & F_FIRST;
          if (UNLIKELY(f & (F_FIRST | F_LAST | F_DIAG))) {
            row_inv(first);
            at_mask(S + 32, (f & F_DIAG) ? wrow - 64 : 64, lane);
            unroll8([&](auto kc) { exp_q(S + 8, kc, std::integral_constant<int, AT_R1 / 8 - 1>{}); });
          } else {
            at_exp<8, AT_R1>(S);
          }
          pv_done();
          g = pinned(g + 1); par = pinned(par ^ (SLOT / 16)); f = fn;
          const bool kok = mbar_try(B(B_KF + (g & 1)), g < 34 ? (g >> 1) & 1 : 0);
          if (UNLIKELY(first)) {
            unroll8([&](auto ic) {
              constexpr int i = decltype(ic)::value, n = (64 - AT_R1) / 8;
              at_exp<AT_R1 + n * i, AT_R1 + n * i + n>(S);
              park(piece(t), i, scaled(i));
            });
            at_fin<0, 64>(S, P);
            hand_over();
          } else {
            at_exp<AT_R1, 64>(S); at_fin<0, 64>(S, P);
          }
          TC(g - 1, 5);
          if (!TCLK) TL(1, 1 + g, tid == 128);
          if (kok && !(f & F_STOP)) continue;
          if (UNLIKELY(!kok)) mbar_wait_c(B(B_KF + (g & 1)), (g >> 1) & 1);
          if (g == 34) break;
        }
#pragma unroll 1
        while (f & F_STOP) {
          TC(g, 0);
          bar_sync(1, 256);
          fence_regs<64>(O); fence_regs<32>(Q); fence_regs<32>(P);
          float S[32];
          const uint64_t dk = desc_add(dk0, par * 16);
          wg_fence();
          mma_n64_rs0(S, Q, dk);
#pragma unroll
          for (int k = 1; k < 8; k++) mma_n64_rs(S, Q + 4 * k, desc_add(dk, (k >> 2) * 16384 + (k & 3) * 32), 1);
          wg_commit();
          TC(g, 1);
          mbar_wait_c(B(B_VF + ((g - 1) & 1)), ((g - 1) >> 1) & 1);
          issue_pv(f & F_PHALF, ~f & F_PFIRST);
          fence_regs<32>(S);
          TC(g, 2);
          release_k();
          const bool first = f & F_FIRST;
          at_sum(P, f & F_PHALF, l0, l1);
          fn = __shfl_sync(~0u, kinds, g - 2);
          row_inv(first);
          pv_done();
          sched_fence(q_st);
          at_mask(S, wrow, lane);
          unroll8([&](auto kc) { exp_q(S, kc, std::integral_constant<int, 4>{}); });
          g++; par ^= SLOT / 16; f = fn;
          at_fin<0, 32>(S, P);
          if (first) {
#pragma unroll
            for (int i = 0; i < 8; i++) park(piece(t), i, scaled(i));
            hand_over();
          }
          TC(g - 1, 5);
          if (!TCLK) TL(1, 1 + g, tid == 128);
          mbar_wait_c(B(B_KF + (g & 1)), (g >> 1) & 1);
        }
      }
      const bool wok = mbar_test(B(ffn ? B_WF : B_QP + 1), 0);
      grab(wf, 3 * SLOT, 0, 8);
      mbar_wait_c(B(B_VF + 1), 0);
      bar_sync(1 + w, 256);
      fence_regs<64>(O); fence_regs<32>(P);
      wg_fence();
#pragma unroll
      for (int k = 0; k < 8; k++) mma_n128_rs<1>(O, P + 4 * k, desc_add(dv0, 2 * SLOT + k * 2048), 1);
      wg_commit();
      if (w == 0) bar_arrive(2, 256);
      pin_order(__uint_as_float(wf[28] & wf[24]), pin);
      __syncwarp();
      if (wok) release2(B_WE);
      TL(3, 12 + 16 * w, (tid & 127) == 0);
      sched_fence(q_st);
      at_sum(P, false, l0, l1);
      row_inv(true);
      sched_fence(q_st);
      wg_wait<0>();
      fence_regs<64>(O); fence_regs<32>(P);
      release2(B_VE + 1);
      if (UNLIKELY(!wok || fail != 0)) {
#pragma unroll 1
        for (int tt = 0; tt < 4; tt++) {
          if (!((tt < 3 ? fail >> tt : fail != 0) & 1)) continue;
          slow_tile(O, P, l0, l1, wq, (((tt + 1) & 2) ? ti : 15 - ti) * 128 + wrow, hh + (tt & 2) * 8, lane, q_st);
          row_inv(false);
          if (tt < 3) {
#pragma unroll
            for (int i = 0; i < 8; i++) park(piece(tt + 1), i, scaled(i));
            publish(2 + tt);
          }
        }
        if (!wok) {
          mbar_wait_c(B(ffn ? B_WF : B_QP + 1), 0);
          grab(wf, 3 * SLOT, 0, 8);
          pin_order(__uint_as_float(wf[28] & wf[24]), pin);
          __syncwarp();
          release2(B_WE);
        }
      }
      TL(3, 13 + 16 * w, (tid & 127) == 0);
      issue3(0, 0, 0);
      TL(3, 14 + 16 * w, (tid & 127) == 0);
      TL(1, 36, tid == 128);
    }
    uint32_t hp[32];
    lane = lane_id();
    {
      int st = 1, prev = 0; uint32_t ph = 0;
      __nv_bfloat16* dst = g_qkv + (size_t)((15 - ti) * 128 + cw * 16 + (lane >> 2)) * NQ + (hh + 16) * 128 + (lane & 3) * 8;
      auto kblock = [&](auto between, int lim = 6) {
        issue3(st, ph, 1);
        between();
        wg_wait<1>();
        release2(B_EMPTY3 + prev);
        prev = st;
        if (++st == lim) { st = 0; ph ^= 1; }
      };
      uint4 ob[8];
      kblock([&]() { sched_fence(rbar); ob[0] = scaled(0); ob[1] = scaled(2); ob[2] = scaled(1); ob[3] = scaled(3); sched_fence(rbar); });
      kblock([&]() { sched_fence(rbar); ob[4] = scaled(4); ob[5] = scaled(6); ob[6] = scaled(5); ob[7] = scaled(7); sched_fence(rbar); grab(wf + 32, 5 * SLOT, 0, 8); });
#pragma unroll 1
      for (int kb = 3; kb < 11; kb++) {
        kblock([&]() {
          sched_fence(rbar);
#pragma unroll
          for (int i = 0; i < 8; i++)
            if (kb == 3 + i) *reinterpret_cast<uint4*>(dst + (i & 2) * 4 * NQ + (i & 1) * 32 + (i & 4) * 16) = ob[i];
          TL(3, 14 + kb + 16 * w, (tid & 127) == 0);
          if (kb == 8) TL(2, 2, tid == 128);
        }, kb == 4 ? 5 : 6);
        if (kb == 4) release2(B_EMPTY3 + 5);
      }
      publish(5);
      kblock([&]() { mbar_wait_c(B(ffn ? B_WF2 : B_QP + 2), 0); grab(wf + 32, 5 * SLOT, 8, 16); });
#pragma unroll 1
      for (int kb = 12; kb < G_KB; kb++) {
        kblock([&]() { if ((kb & 7) == 0) TL(2, 1 + (kb >> 3), tid == 128); });
        if (kb == X_KB && lane == 0) mbar_arrive(B(B_XE));
      }
      kblock([&]() {
        mbar_wait_c(B(B_XF), 0);
#pragma unroll
        for (int i = 0; i < 8; i++)
          ldsm4(hp + 4 * i, sb + 6 * SLOT + w * 16384 + ((cw & 3) * 16 + (lane & 15)) * 128 + (i >> 2) * 8192 + ((((i & 3) * 2 + (lane >> 4)) ^ (lane & 7)) << 4));
      });
#pragma unroll 1
      for (int kb = G_KB + 1; kb < 64; kb++) {
        kblock([&]() { if ((kb & 7) == 0) TL(2, 1 + (kb >> 3), tid == 128); });
        if (kb == G_KB + 2 && lane == 0) mbar_arrive(B(B_XE));
      }
    }
    lane = lane_id();
    const int r0 = lane >> 2, q4 = lane & 3, ct = cw * 32 + lane;
    uint32_t tb[16];
    mbar_wait_c(B(B_WR), 0);
#pragma unroll
    for (int i = 0; i < 4; i++) ldsm4(tb + 4 * i, sb + OFF_MISC + 512 + (lane & 1) * 256 + (lane >> 3) * 16 + i * 64);
    mbar_wait_c(B(B_SET2), 0);
    float4* const psd = reinterpret_cast<float4*>(xr + XR_PS + cw * 16 + r0);
    const uint4* const pss = g_xr + (mt * 8 + (ct & 1) * 4) * XR_SIZE + XR_PS + (ct >> 1);
    sched_fence(stg);
    wg_wait<0>();
    fence_regs<64>(acc);
    TL(2, 10, tid == 128);
    {
      float d[2][4] = {}, qa[2][4] = {}, qb[2][4] = {};
#pragma unroll
      for (int j = 0; j < 16; j++) {
        hp[2 * j] = hadd2_bf(hp[2 * j], pack_bf16(acc[4 * j], acc[4 * j + 1]));
        hp[2 * j + 1] = hadd2_bf(hp[2 * j + 1], pack_bf16(acc[4 * j + 2], acc[4 * j + 3]));
        if (j & 1) {
          mma16816(d[(j >> 1) & 1], hp[2 * j - 2], hp[2 * j - 1], hp[2 * j], hp[2 * j + 1], tb[j - 1], tb[j]);
          mma16816(qa[(j >> 1) & 1], hp[2 * j - 2], hp[2 * j - 1], hp[2 * j], hp[2 * j + 1], hp[2 * j - 2], hp[2 * j]);
          mma16816(qb[(j >> 1) & 1], hp[2 * j - 2], hp[2 * j - 1], hp[2 * j], hp[2 * j + 1], hp[2 * j - 1], hp[2 * j + 1]);
        }
      }
      if (q4 == (r0 >> 1)) {
        __stcg(psd, make_float4(d[0][0] + d[1][0], (r0 & 1) ? qa[0][1] + qa[1][1] : qa[0][0] + qa[1][0], d[0][1] + d[1][1], 0.f));
        __stcg(psd + 8, make_float4(d[0][2] + d[1][2], (r0 & 1) ? qb[0][3] + qb[1][3] : qb[0][2] + qb[1][2], d[0][3] + d[1][3], 0.f));
      }
    }
    TL(2, 11, tid == 128);
    mbar_wait_c(B(B_EMPTY3 + 1), 0);
    stage_store_128(stg, lane, hp);
    if (ffn) mbar_wait_c(B(B_WF2), 1);
    grab(wf + 96, 6 * SLOT, 0, 8);
    const float wsum = *reinterpret_cast<const float*>(sp + OFF_MISC + 1024);
    __syncwarp();
    {
      uint4 ps[4];
      poll_chunks(ps, pss, XR_SIZE);
      TL(2, 12, tid == 128);
      auto F = [](uint32_t u) { return __uint_as_float(u); };
      float s1 = (F(ps[0].x) + F(ps[1].x)) + (F(ps[2].x) + F(ps[3].x)), s2 = (F(ps[0].y) + F(ps[1].y)) + (F(ps[2].y) + F(ps[3].y));
      float s3 = (F(ps[0].z) + F(ps[1].z)) + (F(ps[2].z) + F(ps[3].z));
      __syncwarp();
      s1 += __shfl_xor_sync(~0u, s1, 1); s2 += __shfl_xor_sync(~0u, s2, 1); s3 += __shfl_xor_sync(~0u, s3, 1);
      const float mean = s1 * (1.f / DM);
      float mb, inv;
      ln_round(mean, fmaxf(fmaf(s2, 1.f / DM, -mean * mean), 0.f), mb, inv);
      const uint32_t u = pack_bf16(0.f, fmaf(s3 - mb * wsum, inv, 0.f));
      const uint32_t key = (u ^ ((((int)u >> 31) & 0x7FFF0000u) | 0x80000000u)) | (0x7FFFu - (mt * 128 + (ct >> 1)));
      const uint32_t nm2 = pack_bf16(-mb, -mb);
      const uint32_t c1 = __reduce_max_sync(~0u, key);
      const uint32_t c2 = __reduce_max_sync(~0u, key == c1 ? 0u : key);
      if (lane == 0) {
        __stcg(reinterpret_cast<uint2*>(psd) + (XR_KEY - XR_PS) * 2 - cw * 31, make_uint2(c1, c2));
        mbar_arrive(B(B_OUT));
      }
      TL(2, 13, tid == 128);
      const int row = (0x7FFF - (((lane >> 4) ? c2 : c1) & 0x7FFF)) & 15;
      const uint32_t rn = __shfl_sync(~0u, nm2, row * 2);
      const float ri = __shfl_sync(~0u, inv, row * 2);
      uint32_t v[4];
#pragma unroll
      for (int i = 0; i < 4; i++)
        asm volatile("ld.shared.u32 %0, [%1];" : "=r"(v[i]) : "r"(stg + ((lane >> 3) & 1) * 8192 + row * 128 + ((((lane & 4) + i) ^ (row & 7)) << 4) + q4 * 4) : "memory");
      __stcg(xr + XR_CAND + cw * 64 + 32 + lane, make_uint4(ln_apply(v[0], rn, ri), ln_apply(v[1], rn, ri), ln_apply(v[2], rn, ri), ln_apply(v[3], rn, ri)));
      __stcg(xr + XR_CAND + cw * 64 + lane, make_uint4(v[0], v[1], v[2], v[3]));
      sched_fence(stg);
      const uint32_t na = __shfl_sync(~0u, nm2, r0 * 2), nb = __shfl_sync(~0u, nm2, r0 * 2 + 16);
      const float ia = __shfl_sync(~0u, inv, r0 * 2), ib = __shfl_sync(~0u, inv, r0 * 2 + 16);
#pragma unroll
      for (int i = 0; i < 32; i++) hp[i] = hadd2_bf(hp[i], ln_apply(hp[i], (i & 1) ? nb : na, (i & 1) ? ib : ia));
      __syncwarp();
      stage_store_128(stg, lane, hp);
      asm volatile("fence.proxy.async.shared::cta;" ::: "memory");
      publish(B_OUT3 - B_PUB);
    }
    uint32_t wd[16][4];
    sched_fence(stg);
    if (ffn) mbar_wait_c(B(B_FULL3 + 5 * w), 1 - w);
    auto load_wd = [&](int h) {
#pragma unroll
      for (int i = h; i < 16; i += 2)
        asm volatile("ldmatrix.sync.aligned.m8n8.x4.trans.shared.b16 {%0,%1,%2,%3}, [%4];"
                     : "=r"(wd[i][0]), "=r"(wd[i][1]), "=r"(wd[i][2]), "=r"(wd[i][3])
                     : "r"(sb + OFF_R3 + 5 * w * SLOT + (2 * (cw & 3) + (i >> 3)) * 4096 + (h * 16 + (lane & 7) + (lane >> 4) * 8) * 128 +
                           (((2 * ((i >> 1) & 3) + ((lane >> 3) & 1)) ^ (lane & 7)) << 4)) : "memory");
    };
    load_wd(0);
    __syncwarp();
    cluster_arrive();
    const char* xsrc = reinterpret_cast<const char*>(g_xr + (r0 >> 1) * XR_SIZE + XR_CAND + 32 + (cw >> 1) * 4 + q4);
    asm volatile("" : "+l"(xsrc));
    sched_fence(stg);
    TL(2, 22, tid == 128);
    mbar_wait_c(B(B_OUT2), 0);
    TL(2, 14, tid == 128);
    if (ffn) {
      uint4 xb[2];
      poll_chunks(xb, reinterpret_cast<const uint4*>(xsrc + *reinterpret_cast<const uint32_t*>(sp + OFF_MISC + 8 + (r0 & 1) * 4)), 4 * XR_SIZE);
      __syncwarp();
      TL(2, 15, tid == 128);
      float d[8][4] = {};
#pragma unroll
      for (int n = 0; n < 32; n++) {
        if (n == 8) { sched_fence(stg); load_wd(1); }
        const int s = (n >> 4) * 4 + ((n >> 1) & 3), m = ((n >> 3) & 1) * 2 + (n & 1);
        const uint32_t* a = wf + 16 * s + 4 * m;
        mma16816(d[n & 7], a[0], a[1], a[2], a[3], (m & 2) ? xb[s >> 2].z : xb[s >> 2].x, (m & 2) ? xb[s >> 2].w : xb[s >> 2].y);
      }
      float v[8];
#pragma unroll
      for (int i = 0; i < 8; i++) {
        const float lo = (q4 & 1) ? d[2 + (i >> 2)][i & 3] : d[i >> 2][i & 3], hi = (q4 & 1) ? d[6 + (i >> 2)][i & 3] : d[4 + (i >> 2)][i & 3];
        v[i] = (q4 & 2) ? hi : lo;
      }
#pragma unroll
      for (int i = 0; i < 4; i++) v[i] = ((q4 & 2) ? v[i + 4] : v[i]) + __shfl_xor_sync(~0u, (q4 & 2) ? v[i] : v[i + 4], 2);
#pragma unroll
      for (int i = 0; i < 2; i++) v[i] = ((q4 & 1) ? v[i + 2] : v[i]) + __shfl_xor_sync(~0u, (q4 & 1) ? v[i] : v[i + 2], 1);
      float4* red = reinterpret_cast<float4*>(sp + SL_SCR * SLOT);
      reinterpret_cast<float2*>(red + cw * 16 + (q4 >> 1) * 8 + r0)[q4 & 1] = make_float2(v[0], v[1]);
      bar_sync(3, 256);
      TL(2, 16, tid == 128);
      const float4 z0 = red[lane], z1 = red[32 + lane], z2 = red[64 + lane], z3 = red[96 + lane];
      const uint32_t ub = pack_bf16((z0.x + z1.x) + (z2.x + z3.x), (z0.y + z1.y) + (z2.y + z3.y));
      const uint32_t gb = pack_bf16((z0.z + z1.z) + (z2.z + z3.z), (z0.w + z1.w) + (z2.w + z3.w));
      const float g0 = bf_lo(gb), g1 = bf_hi(gb);
      const uint32_t sg = pack_bf16(g0 * sigmoid(g0), g1 * sigmoid(g1));
      const uint32_t act = pack_bf16(bf_lo(sg) * bf_lo(ub), bf_hi(sg) * bf_hi(ub));
      const uint32_t pr = __byte_perm(act, __shfl_xor_sync(~0u, act, 1), (lane & 1) ? 0x3276 : 0x5410);
      const int src = q4 * 2 + (r0 & 1);
      const uint32_t a0 = __shfl_sync(~0u, pr, src), a1 = __shfl_sync(~0u, pr, src + 8), a2 = __shfl_sync(~0u, pr, src + 16), a3 = __shfl_sync(~0u, pr, src + 24);
      TL(2, 17, tid == 128);
      float y[8][4] = {};
#pragma unroll
      for (int i = 0; i < 8; i++) mma16816(y[i], wd[2 * i][0], wd[2 * i][1], wd[2 * i][2], wd[2 * i][3], a0, a1);
#pragma unroll
      for (int i = 0; i < 8; i++) mma16816(y[i], wd[2 * i + 1][0], wd[2 * i + 1][1], wd[2 * i + 1][2], wd[2 * i + 1][3], a2, a3);
      float2* yd = reinterpret_cast<float2*>(g_xr + (cw * 16 + 2 * q4) * XR_SIZE + XR_Y + fid * 4) + r0;
#pragma unroll
      for (int j = 0; j < 2; j++) {
        float v[4];
#pragma unroll
        for (int e = 0; e < 4; e++) {
          const float lo = (q4 & 1) ? y[4 * j + 1][e] : y[4 * j][e], hi = (q4 & 1) ? y[4 * j + 3][e] : y[4 * j + 2][e];
          v[e] = (q4 & 2) ? hi : lo;
        }
        __stcg(yd + j * 16 * XR_SIZE, make_float2(v[0], v[1]));
        __stcg(yd + j * 16 * XR_SIZE + 2 * XR_SIZE, make_float2(v[2], v[3]));
      }
    }
    TL(2, 18, tid == 128);
    cluster_wait();
    if (rid == 127 && ct < C_NUM) g_cnt[ct] = 0;
    if (cw < 2) {
      const int tok = (lane >> 1) & 1, pair = cw * 2 + (lane & 1);
      uint32_t* const dst = reinterpret_cast<uint32_t*>(out + (size_t)(~*reinterpret_cast<const uint32_t*>(sp + OFF_MISC + tok * 4) & 0x7FF) * DM) + rid * 4 + pair;
      idle(ffn ? Y_CLK : Y_CLK + 2000);
      const bool fin = mbar_test(B(B_FIN), 0);
      uint4 op = lds128(sb + OFF_MISC + 128 + (tok * 4 + pair) * 16);
      uint4 z[7];
      poll_chunks(z, xr + XR_Y + (lane >> 1) * 4 + pair, 64);
      __syncwarp();
      TL(2, 19, tid == 128);
      if (!fin) { mbar_wait_c(B(B_FIN), 0); op = lds128(sb + OFF_MISC + 128 + (tok * 4 + pair) * 16); }
      auto F = [](uint32_t u) { return __uint_as_float(u); };
      const float v0 = ((F(z[0].x) + F(z[1].x)) + (F(z[2].x) + F(z[3].x))) + ((F(z[4].x) + F(z[5].x)) + F(z[6].x));
      const float v1 = ((F(z[0].y) + F(z[1].y)) + (F(z[2].y) + F(z[3].y))) + ((F(z[4].y) + F(z[5].y)) + F(z[6].y));
      const float v2 = ((F(z[0].z) + F(z[1].z)) + (F(z[2].z) + F(z[3].z))) + ((F(z[4].z) + F(z[5].z)) + F(z[6].z));
      const float v3 = ((F(z[0].w) + F(z[1].w)) + (F(z[2].w) + F(z[3].w))) + ((F(z[4].w) + F(z[5].w)) + F(z[6].w));
      float ya = (tok ? v1 : v0) + __shfl_xor_sync(~0u, tok ? v0 : v1, 2), yb = (tok ? v3 : v2) + __shfl_xor_sync(~0u, tok ? v2 : v3, 2);
#pragma unroll
      for (int o = 4; o < 32; o <<= 1) { ya += __shfl_xor_sync(~0u, ya, o); yb += __shfl_xor_sync(~0u, yb, o); }
      const uint32_t yp = pack_bf16(ya, yb);
      if (lane < 4) *dst = hadd2_bf(op.x, hadd2_bf(op.y, pack_bf16(bf_lo(yp) * F(op.z), bf_hi(yp) * F(op.z))));
      TL(2, 21, tid == 128);
    }
    TL(2, 20, tid == 128);
    TL_DUMP();
  }
}

typedef CUresult (*EncodeFn)(CUtensorMap*, CUtensorMapDataType, cuuint32_t, void*, const cuuint64_t*, const cuuint64_t*, const cuuint32_t*,
                             const cuuint32_t*, CUtensorMapInterleave, CUtensorMapSwizzle, CUtensorMapL2promotion, CUtensorMapFloatOOBfill);
EncodeFn g_enc = nullptr;

void map2(CUtensorMap* m, const void* ptr, uint64_t rows, uint64_t cols, uint32_t bc, uint32_t br) {
  const CUtensorMapSwizzle sw = bc == 64 ? CU_TENSOR_MAP_SWIZZLE_128B : CU_TENSOR_MAP_SWIZZLE_64B;
  cuuint64_t gd[2] = {cols, rows}, gs[1] = {cols * 2};
  cuuint32_t bd[2] = {bc, br}, es[2] = {1, 1};
  g_enc(m, CU_TENSOR_MAP_DATA_TYPE_BFLOAT16, 2, (void*)ptr, gd, gs, bd, es, CU_TENSOR_MAP_INTERLEAVE_NONE, sw,
        CU_TENSOR_MAP_L2_PROMOTION_L2_128B, CU_TENSOR_MAP_FLOAT_OOB_FILL_NONE);
}
void map3(CUtensorMap* m, const void* ptr, uint64_t rows, uint64_t cols, uint32_t br, uint32_t bch, uint32_t bc = 64) {
  cuuint64_t gd[3] = {bc, rows, cols / bc}, gs[2] = {cols * 2, bc * 2};
  cuuint32_t bd[3] = {bc, br, bch}, es[3] = {1, 1, 1};
  g_enc(m, CU_TENSOR_MAP_DATA_TYPE_BFLOAT16, 3, (void*)ptr, gd, gs, bd, es, CU_TENSOR_MAP_INTERLEAVE_NONE, bc == 64 ? CU_TENSOR_MAP_SWIZZLE_128B : CU_TENSOR_MAP_SWIZZLE_64B,
        CU_TENSOR_MAP_L2_PROMOTION_L2_128B, CU_TENSOR_MAP_FLOAT_OOB_FILL_NONE);
}

}

extern "C" void kernel_launch(void* const* d_in, const int* in_sizes, int n_in, void* d_out, int out_size) {
  const __nv_bfloat16* x = (const __nv_bfloat16*)d_in[0];
  const __nv_bfloat16* ckv = (const __nv_bfloat16*)d_in[1];
  const __nv_bfloat16* wq = (const __nv_bfloat16*)d_in[2];
  const __nv_bfloat16* wk = (const __nv_bfloat16*)d_in[3];
  const __nv_bfloat16* wv = (const __nv_bfloat16*)d_in[4];
  const __nv_bfloat16* wo = (const __nv_bfloat16*)d_in[5];
  const __nv_bfloat16* w_r = (const __nv_bfloat16*)d_in[7];
  const __nv_bfloat16* wgate = (const __nv_bfloat16*)d_in[8];
  const __nv_bfloat16* wup = (const __nv_bfloat16*)d_in[9];
  const __nv_bfloat16* wdown = (const __nv_bfloat16*)d_in[10];
  __nv_bfloat16* out = (__nv_bfloat16*)d_out;

  if (!g_enc) {
    void* fn = nullptr;
    cudaDriverEntryPointQueryResult qr;
    cudaGetDriverEntryPoint("cuTensorMapEncodeTiled", &fn, cudaEnableDefault, &qr);
    g_enc = (EncodeFn)fn;
    cudaFuncSetAttribute(fused_kernel, cudaFuncAttributeMaxDynamicSharedMemorySize, SMEM_BYTES);
  }
  void *xn, *qkv;
  cudaGetSymbolAddress(&xn, g_xn);
  cudaGetSymbolAddress(&qkv, g_qkv);

  Params p;
  map2(&p.xn, xn, SEQ, DM, 64, 128);
  map2(&p.ckv, ckv, SEQ, DC, 64, 128);
  map3(&p.wq, wq, DM, NQ, 64, 2);
  map3(&p.wk, wk, DC, NQ, 64, 2);
  map3(&p.wv, wv, DC, NQ, 64, 2);
  map3(&p.kv, qkv, 3 * SEQ, NQ, 128, 1);
  map2(&p.ctx_ld, qkv, SEQ, NQ, 64, 128);
  map3(&p.ctx_st, qkv, SEQ, NQ, 64, 1, 32);
  map3(&p.wo, wo, NQ, DM, 64, 1);
  map3(&p.x, x, SEQ, DM, 64, 1);
  map3(&p.wd, wdown, FF, DM, 32, 8);
  map2(&p.out, out, SEQ, DM, 64, 64);
  map2(&p.wg, wgate, DM, FF, 32, 128);
  map2(&p.wu, wup, DM, FF, 32, 128);
  fused_kernel<<<128, 384, SMEM_BYTES, cudaStreamPerThread>>>(x, wq, w_r, out, p);
}
```

```cpp
#include <cuda_runtime.h>
#include <cuda_bf16.h>
#include <cuda.h>
#include <stdint.h>
#include <type_traits>

#pragma nv_diag_suppress 549
namespace {

constexpr int SEQ = 2048, DM = 1024, NH = 32, HD = 128, DC = 512, NQ = NH * HD, FF = 3584;

__device__ __align__(1024) __nv_bfloat16 g_xn[SEQ * DM];
__device__ __align__(1024) __nv_bfloat16 g_qkv[3 * SEQ * NQ];
constexpr int XR_PS = 0;
constexpr int XR_KEY = 128;
constexpr int XR_FLAG = 132;
constexpr int XR_CAND = 136;
constexpr int XR_Y = 648;
constexpr int XR_SIZE = 1104;
__device__ __align__(1024) uint4 g_xr[128 * XR_SIZE];
constexpr int C_LN = 0, C_QKV = 16, C_CTX = 32, C_NUM = 64;
__device__ unsigned g_cnt[C_NUM];

#define TL(k, i, cond) do {} while (0)
#define TL_BYTES 0
#define TL_INIT() do {} while (0)
#define TL_DUMP() do {} while (0)
#define TC(g, i) do {} while (0)
#define TS(i) do {} while (0)
#undef TCLK
#define TCLK 0

__device__ __forceinline__ uint32_t s2u(const void* p) { return (uint32_t)__cvta_generic_to_shared(p); }
__device__ __forceinline__ void mbar_init(uint32_t b, uint32_t c) { asm volatile("mbarrier.init.shared::cta.b64 [%0], %1;" ::"r"(b), "r"(c) : "memory"); }
__device__ __forceinline__ void mbar_expect(uint32_t b, uint32_t bytes) { asm volatile("mbarrier.arrive.expect_tx.shared::cta.b64 _, [%0], %1;" ::"r"(b), "r"(bytes) : "memory"); }
__device__ __forceinline__ void mbar_arrive(uint32_t b) { asm volatile("mbarrier.arrive.shared::cta.b64 _, [%0];" ::"r"(b) : "memory"); }
__device__ __forceinline__ bool mbar_test(uint32_t b, uint32_t ph) {
  uint32_t ok;
  asm volatile("{\n.reg .pred p;\nmbarrier.test_wait.parity.shared::cta.b64 p, [%1], %2;\nselp.u32 %0, 1, 0, p;\n}" : "=r"(ok) : "r"(b), "r"(ph) : "memory");
  return ok;
}
__device__ __forceinline__ void mbar_wait(uint32_t b, uint32_t ph) {
  asm volatile(
      "{\n.reg .pred p;\n.reg .u32 n;\nmov.u32 n, 0;\n"
      "LW:\nmbarrier.try_wait.parity.shared::cta.b64 p, [%0], %1, 20000;\n@p bra LD;\n"
      "add.u32 n, n, 1;\nsetp.lt.u32 p, n, 0x40000;\n@p bra LW;\ntrap;\nLD:\n}" ::"r"(b), "r"(ph) : "memory");
}
__device__ __forceinline__ void mbar_wait_c(uint32_t b, uint32_t ph) {
  asm volatile(
      "{\n.reg .pred p;\n.reg .u32 n;\nmov.u32 n, 0;\n"
      "LW:\nmbarrier.try_wait.parity.shared::cta.b64 p, [%0], %1;\n@p bra LD;\n"
      "add.u32 n, n, 1;\nsetp.lt.u32 p, n, 0x100000;\n@p bra LW;\ntrap;\nLD:\n}" ::"r"(b), "r"(ph) : "memory");
}
__device__ __forceinline__ bool mbar_try(uint32_t b, uint32_t ph) {
  uint32_t ok;
  asm volatile("{\n.reg .pred p;\nmbarrier.try_wait.parity.shared::cta.b64 p, [%1], %2;\nselp.u32 %0, 1, 0, p;\n}" : "=r"(ok) : "r"(b), "r"(ph) : "memory");
  return ok;
}
#define UNLIKELY(c) __builtin_expect(!!(c), 0)
__device__ __forceinline__ uint32_t pinned(uint32_t v) { uint32_t r; asm volatile("mov.b32 %0, %1;" : "=r"(r) : "r"(v)); return r; }
__device__ __forceinline__ bool elect_one() {
  uint32_t p;
  asm volatile("{\n.reg .pred p;\nelect.sync _|p, 0xFFFFFFFF;\nselp.u32 %0, 1, 0, p;\n}" : "=r"(p));
  return p;
}
__device__ __forceinline__ int lane_id() { int r; asm volatile("mov.u32 %0, %%laneid;" : "=r"(r)); return r; }
template <bool SLEEP = false>
__device__ __forceinline__ void spin_until_ge(const unsigned* p, unsigned target) {
  asm volatile(
      "{\n.reg .pred p, q;\n.reg .u32 n, v;\nmov.u32 n, 0;\nsetp.ne.u32 q, %2, 0;\n"
      "LW:\nld.acquire.gpu.global.u32 v, [%0];\nsetp.ge.u32 p, v, %1;\n@p bra LD;\n@q nanosleep.u32 200;\n"
      "add.u32 n, n, 1;\nsetp.lt.u32 p, n, 0x400000;\n@p bra LW;\ntrap;\nLD:\n}" ::"l"(p), "r"(target), "n"((int)SLEEP) : "memory");
}
template <int N>
__device__ __forceinline__ void poll_chunks(uint4 (&v)[N], const uint4* p, int stride) {
  uint32_t m[N];
#pragma unroll
  for (int i = 0; i < N; i++) { m[i] = ~0u; v[i] = make_uint4(0, 0, 0, 0); }
#pragma unroll 1
  for (int n = 0; n < 0x400000; n++) {
    uint32_t a = 0;
#pragma unroll
    for (int i = 0; i < N; i++)
      asm volatile("{\n.reg .pred p;\nsetp.eq.u32 p, %5, 0xFFFFFFFF;\n@p ld.relaxed.gpu.global.v4.u32 {%0,%1,%2,%3}, [%4];\n}"
                   : "+r"(v[i].x), "+r"(v[i].y), "+r"(v[i].z), "+r"(v[i].w) : "l"(p + i * stride), "r"(m[i]) : "memory");
#pragma unroll
    for (int i = 0; i < N; i++) { m[i] = max(max(v[i].x, v[i].y), max(v[i].z, v[i].w)); a = max(a, m[i]); }
    if (__all_sync(~0u, a != 0xFFFFFFFFu)) break;
  }
}
__device__ __forceinline__ void fence_async_all() { asm volatile("fence.proxy.async;" ::: "memory"); }
__device__ __forceinline__ void bar_sync(int id, int n) { asm volatile("bar.sync %0, %1;" ::"r"(id), "r"(n) : "memory"); }
__device__ __forceinline__ void bar_arrive(int id, int n) { asm volatile("bar.arrive %0, %1;" ::"r"(id), "r"(n) : "memory"); }
__device__ __forceinline__ void cluster_arrive() { asm volatile("barrier.cluster.arrive.relaxed.aligned;" ::: "memory"); }
__device__ __forceinline__ void cluster_wait() { asm volatile("barrier.cluster.wait.acquire.aligned;" ::: "memory"); }
__device__ __forceinline__ void fence_gpu() { asm volatile("fence.acq_rel.gpu;" ::: "memory"); }
__device__ __forceinline__ void red_add(unsigned* p, unsigned v) { asm volatile("red.relaxed.gpu.global.add.u32 [%0], %1;" ::"l"(p), "r"(v) : "memory"); }
__device__ __forceinline__ void prefetch_tm(const CUtensorMap* m) { asm volatile("prefetch.tensormap [%0];" ::"l"(m) : "memory"); }

constexpr uint64_t EV_N = 0x1000000000000000ull, EV_F = 0x12F0000000000000ull;
__device__ __forceinline__ void tma_ld2(uint32_t dst, const CUtensorMap* m, uint32_t bar, int c0, int c1, bool ef = false) {
  asm volatile("cp.async.bulk.tensor.2d.shared::cta.global.mbarrier::complete_tx::bytes.L2::cache_hint [%0], [%1, {%3,%4}], [%2], %5;" ::"r"(dst), "l"(m), "r"(bar), "r"(c0), "r"(c1), "l"(ef ? EV_F : EV_N) : "memory");
}
__device__ __forceinline__ void tma_ld3(uint32_t dst, const CUtensorMap* m, uint32_t bar, int c0, int c1, int c2, bool ef = false) {
  asm volatile("cp.async.bulk.tensor.3d.shared::cta.global.mbarrier::complete_tx::bytes.L2::cache_hint [%0], [%1, {%3,%4,%5}], [%2], %6;" ::"r"(dst), "l"(m), "r"(bar), "r"(c0), "r"(c1), "r"(c2), "l"(ef ? EV_F : EV_N) : "memory");
}
__device__ __forceinline__ void tma_ld3_mc(uint32_t dst, const CUtensorMap* m, uint32_t bar, int c0, int c1, int c2, uint16_t mask, bool ef = false) {
  asm volatile("cp.async.bulk.tensor.3d.shared::cluster.global.mbarrier::complete_tx::bytes.multicast::cluster.L2::cache_hint [%0], [%1, {%3,%4,%5}], [%2], %6, %7;" ::"r"(dst), "l"(m), "r"(bar), "r"(c0), "r"(c1), "r"(c2), "h"(mask), "l"(ef ? EV_F : EV_N) : "memory");
}
__device__ __forceinline__ void tma_pf3(const CUtensorMap* m, int c0, int c1, int c2) {
  asm volatile("cp.async.bulk.prefetch.tensor.3d.L2.global [%0, {%1,%2,%3}];" ::"l"(m), "r"(c0), "r"(c1), "r"(c2) : "memory");
}
__device__ __forceinline__ void l2_prefetch(const void* p, uint32_t bytes) { asm volatile("cp.async.bulk.prefetch.L2.global [%0], %1;" ::"l"(p), "r"(bytes) : "memory"); }

__device__ __forceinline__ void wg_fence() { asm volatile("wgmma.fence.sync.aligned;" ::: "memory"); }
__device__ __forceinline__ void wg_commit() { asm volatile("wgmma.commit_group.sync.aligned;" ::: "memory"); }
template <int N> __device__ __forceinline__ void wg_wait() { asm volatile("wgmma.wait_group.sync.aligned %0;" ::"n"(N) : "memory"); }
template <int N> __device__ __forceinline__ void reg_alloc() { asm volatile("setmaxnreg.inc.sync.aligned.u32 %0;" ::"n"(N)); }
template <int N> __device__ __forceinline__ void reg_dealloc() { asm volatile("setmaxnreg.dec.sync.aligned.u32 %0;" ::"n"(N)); }
template <int N> __device__ __forceinline__ void fence_regs(float* d) {
#pragma unroll
  for (int i = 0; i < N; i++) asm volatile("" : "+f"(d[i])::"memory");
}
template <int N> __device__ __forceinline__ void fence_regs(uint32_t* d) {
#pragma unroll
  for (int i = 0; i < N; i++) asm volatile("" : "+r"(d[i])::"memory");
}

__device__ __forceinline__ uint64_t mk_desc(uint32_t addr, uint32_t lbo, uint32_t sbo, uint32_t swz) {
  uint32_t lo = ((addr & 0x3FFFF) >> 4) | ((lbo >> 4) << 16);
  uint32_t hi = (sbo >> 4) | (swz << 30);
  return ((uint64_t)hi << 32) | lo;
}
__device__ __forceinline__ uint64_t desc_add(uint64_t d, uint32_t bytes) {
  uint32_t lo = (uint32_t)d + (bytes >> 4);
  return (d & 0xFFFFFFFF00000000ull) | lo;
}

#define R8(b) "+f"(d[b + 0]), "+f"(d[b + 1]), "+f"(d[b + 2]), "+f"(d[b + 3]), "+f"(d[b + 4]), "+f"(d[b + 5]), "+f"(d[b + 6]), "+f"(d[b + 7])
#define REGS32 "%0,%1,%2,%3,%4,%5,%6,%7,%8,%9,%10,%11,%12,%13,%14,%15,%16,%17,%18,%19,%20,%21,%22,%23,%24,%25,%26,%27,%28,%29,%30,%31"
#define REGS64 REGS32 ",%32,%33,%34,%35,%36,%37,%38,%39,%40,%41,%42,%43,%44,%45,%46,%47,%48,%49,%50,%51,%52,%53,%54,%55,%56,%57,%58,%59,%60,%61,%62,%63"
#define REGS128 REGS64 ",%64,%65,%66,%67,%68,%69,%70,%71,%72,%73,%74,%75,%76,%77,%78,%79,%80,%81,%82,%83,%84,%85,%86,%87,%88,%89,%90,%91,%92,%93,%94,%95," \
               "%96,%97,%98,%99,%100,%101,%102,%103,%104,%105,%106,%107,%108,%109,%110,%111,%112,%113,%114,%115,%116,%117,%118,%119,%120,%121,%122,%123,%124,%125,%126,%127"

template <int TB>
__device__ __forceinline__ void mma_n256_ss(float (&d)[128], uint64_t a, uint64_t b, int acc) {
  asm volatile("{\n.reg .pred p;\nsetp.ne.b32 p, %130, 0;\n"
               "wgmma.mma_async.sync.aligned.m64n256k16.f32.bf16.bf16 {" REGS128 "}, %128, %129, p, 1, 1, 0, %131;\n}\n"
               : R8(0), R8(8), R8(16), R8(24), R8(32), R8(40), R8(48), R8(56), R8(64), R8(72), R8(80), R8(88), R8(96), R8(104), R8(112), R8(120)
               : "l"(a), "l"(b), "r"(acc), "n"(TB));
}
template <int TB>
__device__ __forceinline__ void mma_n128_ss(float* d, uint64_t a, uint64_t b, int acc) {
  asm volatile("{\n.reg .pred p;\nsetp.ne.b32 p, %66, 0;\n"
               "wgmma.mma_async.sync.aligned.m64n128k16.f32.bf16.bf16 {" REGS64 "}, %64, %65, p, 1, 1, 0, %67;\n}\n"
               : R8(0), R8(8), R8(16), R8(24), R8(32), R8(40), R8(48), R8(56)
               : "l"(a), "l"(b), "r"(acc), "n"(TB));
}
template <int TB>
__device__ __forceinline__ void mma_n128_rs(float* d, const uint32_t* a, uint64_t b, int acc) {
  asm volatile("{\n.reg .pred p;\nsetp.ne.b32 p, %69, 0;\n"
               "wgmma.mma_async.sync.aligned.m64n128k16.f32.bf16.bf16 {" REGS64 "}, {%64,%65,%66,%67}, %68, p, 1, 1, %70;\n}\n"
               : R8(0), R8(8), R8(16), R8(24), R8(32), R8(40), R8(48), R8(56)
               : "r"(a[0]), "r"(a[1]), "r"(a[2]), "r"(a[3]), "l"(b), "r"(acc), "n"(TB));
}
__device__ __forceinline__ void mma_n64_rs(float* d, const uint32_t* a, uint64_t b, int acc) {
  asm volatile("{\n.reg .pred p;\nsetp.ne.b32 p, %37, 0;\n"
               "wgmma.mma_async.sync.aligned.m64n64k16.f32.bf16.bf16 {" REGS32 "}, {%32,%33,%34,%35}, %36, p, 1, 1, 0;\n}\n"
               : R8(0), R8(8), R8(16), R8(24)
               : "r"(a[0]), "r"(a[1]), "r"(a[2]), "r"(a[3]), "l"(b), "r"(acc));
}
#define W8(b) "=f"(d[b + 0]), "=f"(d[b + 1]), "=f"(d[b + 2]), "=f"(d[b + 3]), "=f"(d[b + 4]), "=f"(d[b + 5]), "=f"(d[b + 6]), "=f"(d[b + 7])
__device__ __forceinline__ void mma_n128_rs0(float* d, const uint32_t* a, uint64_t b) {
  asm volatile("wgmma.mma_async.sync.aligned.m64n128k16.f32.bf16.bf16 {" REGS64 "}, {%64,%65,%66,%67}, %68, 0, 1, 1, 0;\n"
               : W8(0), W8(8), W8(16), W8(24), W8(32), W8(40), W8(48), W8(56)
               : "r"(a[0]), "r"(a[1]), "r"(a[2]), "r"(a[3]), "l"(b));
}
__device__ __forceinline__ void mma_n64_rs0(float* d, const uint32_t* a, uint64_t b) {
  asm volatile("wgmma.mma_async.sync.aligned.m64n64k16.f32.bf16.bf16 {" REGS32 "}, {%32,%33,%34,%35}, %36, 0, 1, 1, 0;\n"
               : W8(0), W8(8), W8(16), W8(24)
               : "r"(a[0]), "r"(a[1]), "r"(a[2]), "r"(a[3]), "l"(b));
}
__device__ __forceinline__ uint32_t pack_bf16(float lo, float hi) {
  uint32_t r;
  asm("cvt.rn.bf16x2.f32 %0, %1, %2;" : "=r"(r) : "f"(hi), "f"(lo));
  return r;
}
__device__ __forceinline__ float bf_lo(uint32_t v) { return __uint_as_float(v << 16); }
__device__ __forceinline__ float bf_hi(uint32_t v) { return __uint_as_float(v & 0xFFFF0000u); }
__device__ __forceinline__ float bf_round(float v) { return bf_lo(pack_bf16(v, v)); }
__device__ __forceinline__ void stsm4(uint32_t addr, uint32_t r0, uint32_t r1, uint32_t r2, uint32_t r3) {
  asm volatile("stmatrix.sync.aligned.m8n8.x4.shared.b16 [%0], {%1,%2,%3,%4};" ::"r"(addr), "r"(r0), "r"(r1), "r"(r2), "r"(r3) : "memory");
}
__device__ __forceinline__ uint4 lds128(uint32_t addr) {
  uint4 v;
  asm volatile("ld.shared.v4.u32 {%0,%1,%2,%3}, [%4];" : "=r"(v.x), "=r"(v.y), "=r"(v.z), "=r"(v.w) : "r"(addr));
  return v;
}
__device__ __forceinline__ float ex2(float x) {
  float y;
  asm("ex2.approx.ftz.f32 %0, %1;" : "=f"(y) : "f"(x));
  return y;
}
__device__ __forceinline__ void pin_order(float v, uint32_t dummy) {
  asm volatile("{\n.reg .pred p;\nsetp.eq.b32 p, %0, 0xFFFFFFFF;\n@p st.shared.b32 [%1], %0;\n}" ::"r"(__float_as_uint(v)), "r"(dummy) : "memory");
}
__device__ __forceinline__ float sigmoid(float x) {
  float y;
  asm("rcp.approx.ftz.f32 %0, %1;" : "=f"(y) : "f"(1.f + ex2(x * -1.4426950408889634f)));
  return y;
}
__device__ __forceinline__ void sched_fence(uint32_t dummy) {
  asm volatile("{\n.reg .pred p;\n.reg .u32 c;\nsetp.eq.b32 p, %0, 0xFFFFFFFF;\nmov.u32 c, %%clock;\n@p st.shared.b32 [%0], c;\n}" ::"r"(dummy) : "memory");
}
__device__ __forceinline__ void idle(int n) {
  asm volatile("{\n.reg .pred p;\n.reg .u32 a, b;\nmov.u32 a, %%clock;\nLI:\nmov.u32 b, %%clock;\nsub.u32 b, b, a;\nsetp.lt.u32 p, b, %0;\n@p bra LI;\n}" ::"r"(n) : "memory");
}
__device__ __forceinline__ void stage_store_128(uint32_t base, int lane, const uint32_t* pk) {
  const int row = (lane & 7) + ((lane >> 3) & 1) * 8;
  const uint32_t rb = base + row * 128;
  const int hi = lane >> 4;
#pragma unroll
  for (int j = 0; j < 8; j++) {
    const int chunk = 2 * j + hi;
    const uint32_t a = rb + (j >> 2) * 8192 + (((chunk & 7) ^ (lane & 7)) << 4);
    stsm4(a, pk[4 * j + 0], pk[4 * j + 1], pk[4 * j + 2], pk[4 * j + 3]);
  }
}
__device__ __forceinline__ void ln_round(float mean, float var, float& m_bf, float& inv_s) {
  const uint32_t mv = pack_bf16(mean, var);
  m_bf = bf_lo(mv);
  float sq, rc;
  asm("sqrt.approx.ftz.f32 %0, %1;" : "=f"(sq) : "f"(bf_round(bf_hi(mv) + 1e-5f)));
  asm("rcp.approx.ftz.f32 %0, %1;" : "=f"(rc) : "f"(bf_round(sq)));
  inv_s = rc;
}
__device__ __forceinline__ uint32_t hadd2_bf(uint32_t a, uint32_t b) {
  uint32_t r;
  asm("add.rn.bf16x2 %0, %1, %2;" : "=r"(r) : "r"(a), "r"(b));
  return r;
}
__device__ __forceinline__ uint2 ln_split(float inv_s) {
  const uint32_t hi = pack_bf16(inv_s, inv_s);
  const float lo = inv_s - bf_lo(hi);
  return make_uint2(hi, pack_bf16(lo, lo));
}
__device__ __forceinline__ uint32_t ln_apply(uint32_t h, uint32_t nm2, uint2 inv) {
  uint32_t r;
  asm("{\n.reg .b32 d, t;\nadd.rn.bf16x2 d, %1, %2;\nmul.rn.bf16x2 t, d, %4;\nfma.rn.bf16x2 %0, d, %3, t;\n}" : "=r"(r) : "r"(h), "r"(nm2), "r"(inv.x), "r"(inv.y));
  return r;
}
__device__ __forceinline__ void ldsm4(uint32_t* r, uint32_t addr) {
  asm volatile("ldmatrix.sync.aligned.m8n8.x4.shared.b16 {%0,%1,%2,%3}, [%4];" : "=r"(r[0]), "=r"(r[1]), "=r"(r[2]), "=r"(r[3]) : "r"(addr) : "memory");
}
__device__ __forceinline__ void mma16816(float* d, uint32_t a0, uint32_t a1, uint32_t a2, uint32_t a3, uint32_t b0, uint32_t b1) {
  asm volatile("mma.sync.aligned.m16n8k16.row.col.f32.bf16.bf16.f32 {%0,%1,%2,%3}, {%4,%5,%6,%7}, {%8,%9}, {%0,%1,%2,%3};"
               : "+f"(d[0]), "+f"(d[1]), "+f"(d[2]), "+f"(d[3]) : "r"(a0), "r"(a1), "r"(a2), "r"(a3), "r"(b0), "r"(b1));
}

template <class F>
__device__ __forceinline__ void unroll8(F f) {
  f(std::integral_constant<int, 0>{}); f(std::integral_constant<int, 1>{}); f(std::integral_constant<int, 2>{}); f(std::integral_constant<int, 3>{});
  f(std::integral_constant<int, 4>{}); f(std::integral_constant<int, 5>{}); f(std::integral_constant<int, 6>{}); f(std::integral_constant<int, 7>{});
}

constexpr float AT_C = 0.08838834764831845f * 1.4426950408889634f;
constexpr float AT_LO = 0x1p-40f, AT_HI = 0x1p40f;
constexpr int AT_R1 = 48;
template <int I0, int I1>
__device__ __forceinline__ void at_exp(float* S) {
#pragma unroll
  for (int i = I0; i < I1; i++) asm volatile("ex2.approx.ftz.f32 %0, %0;" : "+f"(S[i]));
}
template <int I0, int I1>
__device__ __forceinline__ void at_fin(const float* S, uint32_t* P) {
#pragma unroll
  for (int i = I0; i < I1; i += 4) {
    P[i / 2] = pack_bf16(S[i], S[i + 1]); P[i / 2 + 1] = pack_bf16(S[i + 2], S[i + 3]);
  }
}
__device__ __forceinline__ void at_sum(const uint32_t* P, bool half, float& l0, float& l1) {
  uint32_t u[4];
#pragma unroll
  for (int r = 0; r < 4; r++) {
    const uint32_t* q = P + (r >> 1) * 16 + (r & 1);
    u[r] = hadd2_bf(hadd2_bf(hadd2_bf(q[0], q[2]), hadd2_bf(q[4], q[6])), hadd2_bf(hadd2_bf(q[8], q[10]), hadd2_bf(q[12], q[14])));
  }
  u[0] = hadd2_bf(u[0], half ? 0u : u[2]);
  u[1] = hadd2_bf(u[1], half ? 0u : u[3]);
  l0 += bf_lo(u[0]) + bf_hi(u[0]);
  l1 += bf_lo(u[1]) + bf_hi(u[1]);
}
template <int j>
__device__ __forceinline__ void at_mask1(float* S, int d) {
  float dummy0 = 0.f, dummy1 = 0.f;
  float& lo0 = j < 7 ? S[4 * (j < 7 ? j + 1 : j) + 2] : dummy0;
  float& lo1 = j < 7 ? S[4 * (j < 7 ? j + 1 : j) + 3] : dummy1;
  asm("{\n.reg .pred p, q;\nsetp.lt.s32 p, %4, %5;\nsetp.le.s32 q, %4, %5;\n"
      "@p add.f32 %0, %0, 0fFF800000;\n@q add.f32 %1, %1, 0fFF800000;\n@p add.f32 %2, %2, 0fFF800000;\n@q add.f32 %3, %3, 0fFF800000;\n}"
      : "+f"(S[4 * j]), "+f"(S[4 * j + 1]), "+f"(lo0), "+f"(lo1) : "r"(d), "r"(8 * j));
}
__device__ __forceinline__ void at_mask(float* S, int r, int lane) {
  unroll8([&](auto jc) { at_mask1<decltype(jc)::value>(S, r + (lane >> 2) - (lane & 3) * 2); });
}
__device__ __forceinline__ uint32_t ldg32(const __nv_bfloat16* p) { return __ldcg(reinterpret_cast<const uint32_t*>(p)); }
__device__ __forceinline__ uint32_t ldg16x2(const __nv_bfloat16* p, int stride) {
  return (uint32_t)__ldcg(reinterpret_cast<const unsigned short*>(p)) | ((uint32_t)__ldcg(reinterpret_cast<const unsigned short*>(p + stride)) << 16);
}
__device__ __forceinline__ void slow_tile(float* O, uint32_t* Q, float& l0, float& l1, const __nv_bfloat16* wq, int row0, int head, int lane, uint32_t dummy) {
  const int r = lane >> 2, q = lane & 3;
#pragma unroll
  for (int i = 0; i < 64; i++) O[i] = 0.f;
  {
    const __nv_bfloat16* xa = g_xn + (size_t)(row0 + r) * DM + 2 * q;
    const __nv_bfloat16* wb = wq + (size_t)(2 * q) * NQ + head * HD + (r >> 1) * 8 + (r & 1);
#pragma unroll 1
    for (int k = 0; k < DM; k += 16) {
      const uint32_t a0 = ldg32(xa + k), a1 = ldg32(xa + k + 8 * DM), a2 = ldg32(xa + k + 8), a3 = ldg32(xa + k + 8 * DM + 8);
#pragma unroll
      for (int j = 0; j < 16; j++) {
        const __nv_bfloat16* wp = wb + (size_t)k * NQ + (j >> 2) * 32 + (j & 3) * 2;
        mma16816(O + 4 * j, a0, a1, a2, a3, ldg16x2(wp, NQ), ldg16x2(wp + 8 * NQ, NQ));
        if (j == 7) sched_fence(dummy);
      }
    }
  }
#pragma unroll
  for (int i = 0; i < 32; i++) Q[i] = pack_bf16(O[2 * i], O[2 * i + 1]);
#pragma unroll
  for (int i = 0; i < 64; i++) O[i] = 0.f;
  float m0 = -INFINITY, m1 = -INFINITY;
  l0 = l1 = 0.f;
#pragma unroll 1
  for (int kv = 0; kv <= row0; kv += 16) {
    float s[8] = {0.f, 0.f, 0.f, 0.f, 0.f, 0.f, 0.f, 0.f};
    const __nv_bfloat16* kp = g_qkv + (size_t)(SEQ + kv + r) * NQ + head * HD + 2 * q;
#pragma unroll
    for (int k = 0; k < 8; k++) {
      mma16816(s, Q[4 * k], Q[4 * k + 1], Q[4 * k + 2], Q[4 * k + 3], ldg32(kp + 16 * k), ldg32(kp + 16 * k + 8));
      mma16816(s + 4, Q[4 * k], Q[4 * k + 1], Q[4 * k + 2], Q[4 * k + 3], ldg32(kp + 8 * NQ + 16 * k), ldg32(kp + 8 * NQ + 16 * k + 8));
    }
#pragma unroll
    for (int i = 0; i < 8; i++)
      if (kv + (i >> 2) * 8 + 2 * q + (i & 1) > row0 + r + (i & 2) * 4) s[i] = -INFINITY;
    float a = fmaxf(fmaxf(fmaxf(s[0], s[1]), fmaxf(s[4], s[5])), m0), b = fmaxf(fmaxf(fmaxf(s[2], s[3]), fmaxf(s[6], s[7])), m1);
    a = fmaxf(a, __shfl_xor_sync(~0u, a, 1)); b = fmaxf(b, __shfl_xor_sync(~0u, b, 1));
    a = fmaxf(a, __shfl_xor_sync(~0u, a, 2)); b = fmaxf(b, __shfl_xor_sync(~0u, b, 2));
    const float c0 = ex2(m0 - a), c1 = ex2(m1 - b);
    m0 = a; m1 = b;
#pragma unroll
    for (int i = 0; i < 8; i++) s[i] = ex2(s[i] - ((i & 2) ? b : a));
    l0 = l0 * c0 + (s[0] + s[1]) + (s[4] + s[5]);
    l1 = l1 * c1 + (s[2] + s[3]) + (s[6] + s[7]);
    sched_fence(dummy);
    const uint32_t p0 = pack_bf16(s[0], s[1]), p1 = pack_bf16(s[2], s[3]), p2 = pack_bf16(s[4], s[5]), p3 = pack_bf16(s[6], s[7]);
    const __nv_bfloat16* vp = g_qkv + (size_t)(2 * SEQ + kv + 2 * q) * NQ + head * HD + r;
#pragma unroll
    for (int j = 0; j < 16; j++) {
      O[4 * j] *= c0; O[4 * j + 1] *= c0; O[4 * j + 2] *= c1; O[4 * j + 3] *= c1;
      mma16816(O + 4 * j, p0, p1, p2, p3, ldg16x2(vp + 8 * j, NQ), ldg16x2(vp + 8 * NQ + 8 * j, NQ));
      if (j == 7) sched_fence(dummy);
    }
  }
}

constexpr int P1_STAGE = 49152;
constexpr int SLOT = 32768;
constexpr int OFF_R3 = 0;
constexpr int OFF_BAR = 229376;
constexpr int OFF_MISC = OFF_BAR + 8 * 58;
constexpr int SMEM_BYTES = OFF_MISC + 2080 + TL_BYTES;
enum : int {
  B_FULL1 = 0, B_KF = 4, B_VF = 6, B_FULL3 = 8, B_XF = 14, B_LN = 15, B_DEP = 16, B_OUT2 = 22, B_FIN = 23, B_SET2 = 25, B_QP = 26, B_WF2 = 29,
  B_WF = 30, B_WR = 31,
  B_XE = 33, B_PUB = 34, B_OUT = 40, B_OUT3 = 41,
  B_EMPTY1 = 42, B_KE = 46, B_VE = 48, B_EMPTY3 = 50, B_WE = 56, B_NUM = 57
};
constexpr int OFF_STG = SLOT, SL_SCR = 2;
constexpr int PRE = 3;
constexpr int LN_PF = 5, LN_PFN = 2, LN_LD = 4;
constexpr int WQ_0 = 18, WQ_D = 2;
constexpr int KV_PF = 11, W_G0 = 23;
constexpr int X_KB = 20, G_KB = 35;
constexpr int SL_NS = 600, SET_NS = 50;
constexpr int OUT_CLK = 500, Y_CLK = 400;
struct Params {
  CUtensorMap xn, ckv, wq, wk, wv, kv, ctx_ld, ctx_st, wo, x, wd, wg, wu, out;
};

__global__ void __cluster_dims__(2, 1, 1) __launch_bounds__(384, 1)
fused_kernel(const __nv_bfloat16* __restrict__ x, const __nv_bfloat16* __restrict__ wq, const __nv_bfloat16* __restrict__ w_r,
             __nv_bfloat16* __restrict__ out, const __grid_constant__ Params p) {
  extern __shared__ __align__(1024) uint8_t sp[];
  const uint32_t sb = s2u(sp);
  const uint32_t bar = sb + OFF_BAR;
  auto B = [&](int i) { return bar + 8 * i; };
  const int tid = threadIdx.x, warp = __shfl_sync(~0u, tid >> 5, 0), wg = warp >> 2, lane = tid & 31;
  const int cta = blockIdx.x, rank = cta & 1, cl = cta >> 1;
  const int mp = cl < 4 ? 1 : (cl < 36 ? (cl & 7) : (0x3207654 >> (4 * ((cl - 36) % 7))) & 7);
  const int gq = cl < 4 ? 4 + cl : (cl < 36 ? (cl - 4) >> 3 : 4 + (cl - 36) / 7);
  const int mt = 2 * mp + rank;
  const int ti = (gq & 3) * 2 + rank, hh = mp * 2 + (gq >> 2);
  const int rid = mt * 8 + gq;
  const int fid = mt * 7 + gq - 1;
  const bool ffn = gq > 0;
  uint4* const xr = g_xr + rid * XR_SIZE;
  TL_INIT();
  TL(0, 0, tid == 128);
  if (warp == 0) {
    if (elect_one()) {
#pragma unroll
      for (int kb = 0; kb < PRE; kb++) mbar_init(B(B_FULL1 + kb), 1);
      asm volatile("fence.mbarrier_init.release.cluster;" ::: "memory");
    }
    __syncwarp();
    cluster_arrive();
    if (elect_one()) {
#pragma unroll
      for (int kb = 0; kb < PRE; kb++) {
        mbar_expect(B(B_FULL1 + kb), P1_STAGE);
        tma_ld2(sb + kb * P1_STAGE, &p.ckv, B(B_FULL1 + kb), kb * 64, mt * 128);
        tma_ld3(sb + kb * P1_STAGE + 16384 + rank * 16384, &p.wk, B(B_FULL1 + kb), 0, kb * 64, (gq + 8) * 4 + rank * 2);
        tma_ld3(sb + kb * P1_STAGE + 32768 - rank * 16384, &p.wk, B(B_FULL1 + kb), 0, kb * 64, (gq + 8) * 4 + 2 - rank * 2);
      }
    }
  } else if (elect_one()) {
#pragma unroll 1
    for (int i = PRE + warp - 1; i < B_NUM; i += 11)
      mbar_init(B(i), i >= B_EMPTY1 ? 16 : (i >= B_XE ? 8 : (i >= B_WF ? 2 : 1)));
    asm volatile("fence.mbarrier_init.release.cluster;" ::: "memory");
  }
  __syncwarp();
  if (warp) cluster_arrive();
  if (wg == 0) {
    reg_dealloc<40>();
    if (warp == 1 && elect_one()) {
      if (mt >= 2 * PRE) tma_pf3(&p.wk, 0, mp * 64, (gq + 8) * 4 + rank * 2);
      if (gq >= PRE) asm volatile("cp.async.bulk.prefetch.tensor.2d.L2.global [%0, {%1,%2}];" ::"l"(&p.ckv), "r"(gq * 64), "r"(mt * 128) : "memory");
    } else if (warp == 2 && elect_one()) {
      prefetch_tm(&p.wv); prefetch_tm(&p.wq); prefetch_tm(&p.xn);
    }
    __syncwarp();
    cluster_wait();
    if (warp == 0) {
      int st = PRE; uint32_t ph = 1;
#pragma unroll 1
      for (int t = 0; t < 6; t++) {
        const CUtensorMap* ma = t >= 4 ? &p.xn : &p.ckv;
        const CUtensorMap* mb = t >= 4 ? &p.wq : ((t & 1) ? &p.wv : &p.wk);
        const int nk = t >= 4 ? 16 : 8;
        const int row = (t < 4 ? mt : (t == 4 ? 15 - ti : ti)) * 128;
        const int col = t < 4 ? (gq + ((t >> 1) ^ 1) * 8) * 4 + rank * 2 : (hh + rank * 16) * 2;
        if (t >= 4) mbar_wait(B(B_DEP + t - 4), 0);
#pragma unroll 1
        for (int kb = t ? 0 : PRE; kb < nk; kb++) {
          const uint32_t d = sb + st * P1_STAGE, fb = B(B_FULL1 + st);
          const int n = t * 8 + kb;
          const bool la = t == 0 || t >= 4 || (kb & 5) == 5, lb = t < 5 || kb >= 4;
          const int k0 = (t == 5 ? (kb + 12) & 15 : kb ^ ((t & kb & 1) * 4)) * 64;
          mbar_wait_c(B(B_EMPTY1 + st), ph);
          if (elect_one()) {
            mbar_expect(fb, la * 16384 + lb * 32768);
            if (la) tma_ld2(t == 0 && (kb & 5) == 4 ? sb + 6 * SLOT + (kb & 2) * 8192 : d, ma, fb, k0, row);
            if (lb) tma_ld3_mc(d + 16384 + rank * 16384, mb, fb, 0, k0, col, 3);
          }
          if (t < 5 && elect_one()) {
            if (n >= LN_PF && n < LN_PF + LN_PFN) l2_prefetch(x + (size_t)cta * 16 * DM + (n - LN_PF) * (16 * DM / LN_PFN), 32768 / LN_PFN);
            if (n == LN_LD) mbar_arrive(B(B_LN));
            if (t < 3 && kb == (t ? 0 : 4)) tma_pf3((t & 1) ? &p.wk : &p.wv, 0, mp * 64, (gq + (((t + 1) >> 1) ^ 1) * 8) * 4 + rank * 2);
            if (n >= WQ_0 && n < WQ_0 + 4 * WQ_D && (n - WQ_0) % WQ_D == 0) tma_pf3(&p.wq, 0, ((n - WQ_0) / WQ_D * 4 + (gq & 3)) * 64, (hh + rank * 16) * 2);
          }
          if (++st == 4) { st = 0; ph ^= 1; }
        }
      }
      if (elect_one()) { prefetch_tm(&p.kv); prefetch_tm(&p.ctx_ld); prefetch_tm(&p.wo); prefetch_tm(&p.wg); prefetch_tm(&p.wu); }
      int seq0, seq1;
      {
        const int G = ti & 6, own = rank ? G + 33 : 31 - G, j = 18 - lane;
        seq0 = lane < 13 - G ? (lane < G ? lane : lane + 2) : (lane <= 14 - G ? 14 - lane : (lane == 15 - G ? own : (lane == 16 - G ? G + 32 : 16 - lane)));
        seq1 = lane <= G + 1 ? lane : (lane == G + 2 ? G + 32 : (lane == G + 3 ? own : (j > G + 1 ? j : j - 2)));
      }
      auto load_kv = [&](int g, int isv) {
        const int h2 = g >= 17, sx = g - 17 * h2, b = __shfl_sync(~0u, h2 ? seq1 : seq0, sx);
        const int row = (1 + isv) * SEQ + (b & 15) * 128, col = (hh + 16 * h2) * 2;
        const uint32_t d = sb + (isv ? 2 + 2 * (g & 1) : (g & 1)) * SLOT, fb = B(B_KF + 2 * isv + (g & 1));
        const bool ef = (b & 8) || sx >= 11;
        const int n3 = g - KV_PF;
        const int pb = ti >= 6 && n3 >= 0 && n3 < 16 ? (n3 < 4 ? n3 : (n3 >= 12 ? 23 - n3 : ((n3 & 1) ? (n3 + 3) >> 1 : 17 - (n3 >> 1)))) : -1;
        mbar_wait_c(g < 2 ? B(B_EMPTY1 + (isv ? 1 + 2 * g : g)) : B(B_KE + 2 * isv + (g & 1)), g < 2 ? 1 : ((g >> 1) & 1) ^ 1);
        if (elect_one()) {
          mbar_expect(fb, b < 32 ? SLOT : 0);
          if (b < 16) {
            tma_ld3_mc(d + rank * 16384, &p.kv, fb, 0, row, col + rank, 3, ef);
          } else if (b < 32) {
            tma_ld3(d, &p.kv, fb, 0, row, col, ef);
            tma_ld3(d + 16384, &p.kv, fb, 0, row, col + 1, ef);
          }
          if (pb >= 0) tma_pf3(&p.kv, 0, (1 + isv) * SEQ + pb * 128, (hh + 16) * 2 + rank);
        }
      };
      int nw = ffn ? 0 : 12;
      auto load_w = [&]() {
        const int c = nw < 8 ? (nw >> 2) + (nw & 2) : nw >> 1;
        if (elect_one()) {
          if (!(nw & 3)) mbar_expect(B(B_WF - (nw >> 3)), 32768);
          tma_ld2(sb + (c < 2 ? 3 : 4) * SLOT + c * 16384 + (nw & 1) * 8192, (nw & 1) ? &p.wg : &p.wu, B(B_WF - (nw >> 3)), fid * 32, c * 128, true);
        }
        nw++;
      };
#pragma unroll 1
      for (int g = 0; g < 34; g++) {
        if (g == 0 || g == KV_PF) mbar_wait(B(B_DEP + 2 + (g > 0)), 0);
        load_kv(g, 0);
        if (g > 0) load_kv(g - 1, 1);
        if (g >= W_G0 && nw < 12 && __all_sync(~0u, mbar_test(B(B_QP + (nw >> 2)), 0))) load_w();
      }
      load_kv(33, 1);
#pragma unroll 1
      while (nw < 12) { mbar_wait(B(B_QP + (nw >> 2)), 0); load_w(); }
      if (elect_one()) { prefetch_tm(&p.wd); prefetch_tm(&p.x); prefetch_tm(&p.out); }
      auto load3 = [&](int kb, int sl) {
        if (elect_one()) {
          mbar_expect(B(B_FULL3 + sl), SLOT);
          tma_ld2(sb + OFF_R3 + sl * SLOT, &p.ctx_ld, B(B_FULL3 + sl), kb * 64, mt * 128, true);
          tma_ld3_mc(sb + OFF_R3 + sl * SLOT + 16384 + rank * 8192, &p.wo, B(B_FULL3 + sl), 0, kb * 64, gq * 2 + rank, 3);
        }
      };
      mbar_wait(B(B_DEP + 4), 0);
#pragma unroll
      for (int kb = 0; kb < 5; kb++) {
        mbar_wait_c(B(kb == 3 ? B_WE : (kb == 4 ? B_VE + 1 : B_KE + kb)), 0);
        load3(kb, kb);
      }
      if (elect_one()) mbar_arrive(B(B_FULL3 + 5));
#pragma unroll 1
      for (int r = 1; r < 11; r++) {
#pragma unroll
        for (int j = 0; j < 6; j++) {
          if (j == 5 && r == 10) break;
          if (j == 3 && r == 5) mbar_wait(B(B_DEP + 5), 0);
          mbar_wait_c(B(B_EMPTY3 + j), ~r & 1);
          load3(r * 6 + j - 1, j);
          if (j == 5 && r == 9 && elect_one()) l2_prefetch(xr, XR_CAND * 16);
        }
      }
      if (ffn) {
#pragma unroll
        for (int j = 1; j >= 0; j--) {
          mbar_wait(B(B_EMPTY3 + 5 * j), j);
          if (elect_one()) {
            mbar_expect(B(B_FULL3 + 5 * j), SLOT);
            tma_ld3(sb + OFF_R3 + 5 * j * SLOT, &p.wd, B(B_FULL3 + 5 * j), 0, fid * 32, 8 * j, true);
          }
        }
      }
    } else {
      if (warp >= 2) {
#pragma unroll 1
        for (int i = tid - 64; i < XR_CAND; i += 64) xr[i] = make_uint4(~0u, ~0u, ~0u, ~0u);
        if (warp == 2) { __syncwarp(); if (lane == 0) mbar_arrive(B(B_WR)); }
      }
      if (warp == 3) {
        float ws = 0.f;
#pragma unroll
        for (int j = 0; j < 4; j++) {
          const uint4 q = __ldg(reinterpret_cast<const uint4*>(w_r) + j * 32 + lane);
          ws += bf_lo(q.x) + bf_hi(q.x) + bf_lo(q.y) + bf_hi(q.y) + bf_lo(q.z) + bf_hi(q.z) + bf_lo(q.w) + bf_hi(q.w);
        }
#pragma unroll
        for (int o = 16; o; o >>= 1) ws += __shfl_xor_sync(~0u, ws, o);
        uint2* tab = reinterpret_cast<uint2*>(sp + OFF_MISC + 512);
        tab[lane] = make_uint2(0x3F803F80u, 0x3F803F80u);
        tab[32 + lane] = __ldg(reinterpret_cast<const uint2*>(w_r + gq * 128) + lane);
        if (lane == 0) *reinterpret_cast<float*>(sp + OFF_MISC + 1024) = ws;
        __syncwarp();
        if (lane == 0) mbar_arrive(B(B_WR));
      }
      if (tid == 32) TS(0);
      mbar_wait(B(B_LN), 0);
      const uint4* src = reinterpret_cast<const uint4*>(x + (size_t)(cta * 16 + warp - 1) * DM) + lane;
      uint4* dst = reinterpret_cast<uint4*>(g_xn + (size_t)(cta * 16 + warp - 1) * DM) + lane;
      uint4 v[4];
#pragma unroll
      for (int j = 0; j < 4; j++) v[j] = __ldcs(src + j * 32);
#pragma unroll 1
      for (int r = warp - 1; r < 16; r += 3) {
        float a0 = 0.f, a1 = 0.f, b0 = 0.f, b1 = 0.f;
#pragma unroll
        for (int j = 0; j < 4; j++) {
          const uint32_t u[4] = {v[j].x, v[j].y, v[j].z, v[j].w};
#pragma unroll
          for (int i = 0; i < 4; i++) { const float a = bf_lo(u[i]), b = bf_hi(u[i]); a0 += a; a1 += b; b0 = fmaf(a, a, b0); b1 = fmaf(b, b, b1); }
        }
        a0 += a1; b0 += b1;
#pragma unroll
        for (int o = 16; o; o >>= 1) { a0 += __shfl_xor_sync(~0u, a0, o); b0 += __shfl_xor_sync(~0u, b0, o); }
        const float mean = a0 * (1.f / DM);
        float mb, inv;
        ln_round(mean, fmaxf(fmaf(b0, 1.f / DM, -mean * mean), 0.f), mb, inv);
        const uint2 iv = ln_split(inv * AT_C);
        const uint32_t nm2 = pack_bf16(-mb, -mb);
        src += 384;
#pragma unroll
        for (int j = 0; j < 4; j++) {
          dst[j * 32] = make_uint4(ln_apply(v[j].x, nm2, iv), ln_apply(v[j].y, nm2, iv), ln_apply(v[j].z, nm2, iv), ln_apply(v[j].w, nm2, iv));
          sched_fence(sb + lane);
          if (r < 13) v[j] = __ldcs(src + j * 32);
        }
        dst += 384;
      }
      __syncwarp();
      if (lane == 0) {
        fence_gpu();
        red_add(&g_cnt[C_LN + (cta >> 3)], 1);
      }
      TL(3, warp, lane == 0);
      __syncwarp();
      if (warp == 3) {
        if (lane == 0) {
#pragma unroll 1
          for (int i = 0; i < 6; i++) {
            const int c = i < 2 ? C_LN + (i ? ti : 15 - ti) : (i < 4 ? C_QKV + (i - 2) * 8 + mp : C_CTX + (i - 4) * 16 + mt);
            spin_until_ge<true>(&g_cnt[c], i < 2 ? 24 : 16);
            fence_async_all();
            mbar_arrive(B(B_DEP + i));
            TL(3, 4 + i, true);
          }
        }
      } else if (warp == 1 && elect_one()) {
        mbar_wait(B(B_WR), 0);
#pragma unroll 1
        for (int i = 0; i < 6; i++) {
          const int c = i < 2 ? C_QKV + gq + (i ^ 1) * 8 : C_CTX + (i >> 2) * 16 + ((i == 3 || i == 4) ? ti : 15 - ti);
          mbar_wait(B(B_PUB + i), 0);
          if (i >= 2 && i < 5) {
            asm volatile("fence.proxy.async.shared::cta;" ::: "memory");
#pragma unroll 1
            for (int n = 0; n < 8; n++) {
              const int h = n >> 2, a = n & 3;
              asm volatile("cp.async.bulk.tensor.3d.global.shared::cta.bulk_group [%0, {%2,%3,%4}], [%1];" ::"l"(&p.ctx_st),
                           "r"(sb + (i == 4 ? 6 * SLOT + h * 16384 : (3 + 2 * h) * SLOT + (i - 2) * 16384) + a * 4096),
                           "r"(0), "r"((i == 2 ? 15 - ti : ti) * 128 + h * 64), "r"((hh + (i >> 2) * 16) * 4 + a) : "memory");
              asm volatile("cp.async.bulk.commit_group;\ncp.async.bulk.wait_group.read 0;" ::: "memory");
            }
            mbar_arrive(B(B_QP + i - 2));
            asm volatile("cp.async.bulk.wait_group 0;" ::: "memory");
          }
          fence_gpu();
          red_add(&g_cnt[c], 1);
          TS(1 + i);
        }
      }
      if (warp == 2) {
#pragma unroll 1
        for (int n = 0; n < 8; n++) {
          if (!(n & 3)) mbar_wait(B(B_XE), n >> 2);
          if ((n < 4 || ffn) && elect_one()) {
            const uint32_t fb = B(n < 4 ? B_XF : B_WF2), d = sb + 6 * SLOT + (n & 3) * 8192;
            if (!(n & 3)) mbar_expect(fb, 32768);
            if (n < 4) tma_ld3(d, &p.x, fb, 0, mt * 128 + (n >> 1) * 64, gq * 2 + (n & 1), true);
            else tma_ld2(d, (n & 1) ? &p.wg : &p.wu, fb, fid * 32, (4 + (n >> 1)) * 128, true);
          }
          __nanosleep(SL_NS);
        }
#pragma unroll 1
        for (int i = XR_CAND + lane; i < XR_SIZE; i += 32) { xr[i] = make_uint4(~0u, ~0u, ~0u, ~0u); __nanosleep(SET_NS); }
        __syncwarp();
        if (lane == 0) { fence_gpu(); mbar_arrive(B(B_SET2)); }
        TL(2, 26, lane == 0);
        __syncwarp();
      }
      __syncwarp();
      cluster_arrive();
      if (warp == 3) {
        mbar_wait(B(B_OUT), 0);
        uint4 kv[2];
        poll_chunks(kv, g_xr + ((lane >> 1) * 8 + gq) * XR_SIZE + XR_KEY + (lane & 1) * 2, 1);
        const uint32_t a1 = max(kv[0].x, kv[0].z), a2 = max(min(kv[0].x, kv[0].z), max(kv[0].y, kv[0].w));
        const uint32_t b1 = max(kv[1].x, kv[1].z), b2 = max(min(kv[1].x, kv[1].z), max(kv[1].y, kv[1].w));
        const uint32_t k1 = max(a1, b1), k2 = max(min(a1, b1), max(a2, b2));
        const uint32_t m1 = __reduce_max_sync(~0u, k1);
        const uint32_t m2 = __reduce_max_sync(~0u, k1 == m1 ? k2 : k1);
        auto cand = [&](uint32_t k) { return (((~k >> 7) & 15) * (8 * XR_SIZE) + ((~k >> 4) & 7) * 64) * 16; };
        const uint32_t o1 = cand(m1), o2 = cand(m2) + (((m1 ^ m2) & 0x7FF0) ? 0 : 256);
        if (lane == 0) {
          *reinterpret_cast<uint4*>(sp + OFF_MISC) = make_uint4(m1, m2, o1, o2);
          mbar_arrive(B(B_OUT2));
        }
        const uint32_t key = (lane & 4) ? m2 : m1;
        const uint4* src = g_xr + (((~key >> 7) & 15) * 8 + (rid >> 4)) * XR_SIZE;
        poll_chunks(kv, g_xr + (((lane & 4) ? o2 : o1) >> 4) + (rid >> 4) * XR_SIZE + XR_CAND + (rid & 12) + (lane & 3), 32);
        uint32_t u = key >> 16;
        u = (u & 0x8000u) ? (u & 0x7FFFu) : (~u & 0xFFFFu);
        const float rs = bf_round(sigmoid(__uint_as_float(u << 16)));
        if (lane < 8)
          *reinterpret_cast<uint4*>(sp + OFF_MISC + 128 + lane * 16) = make_uint4((rid & 2) ? ((rid & 1) ? kv[0].w : kv[0].z) : ((rid & 1) ? kv[0].y : kv[0].x),
              (rid & 2) ? ((rid & 1) ? kv[1].w : kv[1].z) : ((rid & 1) ? kv[1].y : kv[1].x), __float_as_uint(rs), 0);
#pragma unroll 1
        for (int n = 0; n < 0x400000; n++) {
          uint32_t v;
          asm volatile("ld.acquire.gpu.global.u32 %0, [%1];" : "=r"(v) : "l"(src + XR_FLAG) : "memory");
          if (__all_sync(~0u, v == 0)) break;
        }
        __syncwarp();
        if (lane == 0) mbar_arrive(B(B_FIN));
      }
      if (warp == 1 && elect_one()) {
        mbar_wait(B(B_OUT3), 0);
        asm volatile("fence.proxy.async.shared::cta;" ::: "memory");
        auto owner = [&]() {
          uint2 top;
          asm volatile("ld.shared.v2.u32 {%0,%1}, [%2];" : "=r"(top.x), "=r"(top.y) : "r"(sb + OFF_MISC) : "memory");
          return (0x7FFF - (top.x & 0x7FFF)) >> 7 == mt || (0x7FFF - (top.y & 0x7FFF)) >> 7 == mt;
        };
#pragma unroll 1
        for (int n = 0; n < 4; n++) {
          if (n && !(mbar_test(B(B_OUT2), 0) && owner())) idle(OUT_CLK);
          asm volatile("cp.async.bulk.tensor.2d.global.shared::cta.bulk_group [%0, {%2,%3}], [%1];" ::"l"(&p.out), "r"(sb + OFF_STG + n * 8192),
                       "r"(gq * 128 + (n & 1) * 64), "r"(mt * 128 + (n >> 1) * 64) : "memory");
        }
        asm volatile("cp.async.bulk.commit_group;" ::: "memory");
        mbar_wait(B(B_OUT2), 0);
        if (owner()) {
          asm volatile("cp.async.bulk.wait_group 0;" ::: "memory");
          asm volatile("st.release.gpu.global.u32 [%0], 0;" ::"l"(xr + XR_FLAG) : "memory");
        } else {
          asm volatile("cp.async.bulk.wait_group.read 0;" ::: "memory");
        }
        TL(2, 25, true);
      }
    }
    __syncwarp();
    if (warp == 0) cluster_arrive();
    cluster_wait();
    TL_DUMP();
    if (tid == 32) TS(8);
  } else {
    reg_alloc<232>();
    cluster_wait();
    const int w = wg - 1, cw = warp - 4;
    int lane = lane_id();
    const uint32_t stg = sb + OFF_STG + w * 16384 + (cw & 3) * 2048;
    auto publish = [&](int i) { __syncwarp(); if (lane == 0) mbar_arrive(B(B_PUB + i)); };
    uint32_t rbar;
    asm("mapa.shared::cluster.u32 %0, %1, %2;" : "=r"(rbar) : "r"(bar), "r"(lane & 1));
    auto release2 = [&](int i) { if (lane < 2) asm volatile("mbarrier.arrive.shared::cluster.b64 _, [%0];" ::"r"(rbar + 8 * i) : "memory"); };
    float R[128];
    float O[64], acc[64];
    uint32_t pk[64];
    uint32_t* const Q = pk;
    uint32_t P[32];
    auto packed = [&](int i) {
      const float* v = R + 16 * (i >> 1) + 2 * (i & 1);
      return make_uint4(pack_bf16(v[0], v[1]), pack_bf16(v[4], v[5]), pack_bf16(v[8], v[9]), pack_bf16(v[12], v[13]));
    };
    const uint32_t q_st = sb + (cw & 3) * 1024 + (lane >> 2) * 64 + (((lane & 3) ^ (lane >> 3)) << 4);
    const uint32_t q_ld = sb + (cw & 3) * 1024 + (lane & 15) * 64 + (((lane >> 4) ^ ((lane >> 1) & 3)) << 4);
    auto park = [&](uint32_t off, int i, uint4 v) {
      asm volatile("st.shared.v4.u32 [%0], {%1,%2,%3,%4};" ::"r"(q_st + off + (i >> 1) * 4096 + (i & 1) * 512), "r"(v.x), "r"(v.y), "r"(v.z), "r"(v.w) : "memory");
    };
    auto load_q = [&](uint32_t off, int k) { ldsm4(Q + 4 * k, ((q_ld + off) ^ ((k & 1) << 5)) + (k >> 1) * 4096); };
    {
      TL(0, 1, tid == 128);
      __nv_bfloat16* pdst = g_qkv;
      auto put2 = [&](int j) {
#pragma unroll
        for (int i = (j >> 1) * 4 + (j & 1); i < (j >> 1) * 4 + 4; i += 2)
          __stcs(reinterpret_cast<uint4*>(pdst + (i & 1) * 8 * NQ + (i >> 1) * 32), make_uint4(pk[4 * i], pk[4 * i + 1], pk[4 * i + 2], pk[4 * i + 3]));
      };
      const uint64_t da0 = mk_desc(sb + w * 8192, 16, 1024, 1);
      const uint64_t db0 = mk_desc(sb + 16384, 8192, 1024, 1);
      int st = 0; uint32_t ph = 0;
      auto issue = [&](int accum, auto between, bool res = false) {
        mbar_wait_c(B(B_FULL1 + st), ph);
        const uint64_t da = desc_add(da0, res ? 6 * SLOT + st * 8192 : st * P1_STAGE), db = desc_add(db0, st * P1_STAGE);
        between();
        wg_fence();
#pragma unroll
        for (int k = 0; k < 4; k++) mma_n256_ss<1>(R, desc_add(da, k * 32), desc_add(db, k * 2048), k == 0 ? accum : 1);
        wg_commit();
      };
      issue(0, []() {});
#pragma unroll 1
      for (int t = 0;; t++) {
        const int nk = t >= 4 ? 16 : 8;
        const bool tr = t > 0 && t < 5;
        TL(0, 2 + 2 * t + 16 * w, (tid & 127) == 0);
        int prev = st;
        if (++st == 4) { st = 0; ph ^= 1; }
#pragma unroll 1
        for (int kb = 1; kb < nk; kb++) {
          if (kb == nk - 1 && w == 1) bar_sync(5, 256);
          issue(1, []() {}, t < 4 && (kb & 5) == 4);
          if (kb == nk - 1 && w == 0) bar_arrive(5, 256);
          if (tr) {
#pragma unroll
            for (int i = 1; i < 8; i++) if (kb == i) put2(i);
            if (kb == 7 && !(t & 1)) publish((t >> 1) - 1);
          } else if (t == 5) {
            if (kb == 2) {
#pragma unroll
              for (int i = 0; i < 8; i++) park(6 * SLOT + w * 16384, i, make_uint4(pk[4 * i], pk[4 * i + 1], pk[4 * i + 2], pk[4 * i + 3]));
              __syncwarp();
            }
            if (kb == 4) {
#pragma unroll
              for (int k = 0; k < 8; k++) load_q(6 * SLOT + w * 16384, k);
              __syncwarp();
            }
            if (kb == 6) {
#pragma unroll
              for (int i = 0; i < 8; i++) park(6 * SLOT + w * 16384, i, make_uint4(pk[32 + 4 * i], pk[33 + 4 * i], pk[34 + 4 * i], pk[35 + 4 * i]));
            }
          }
          wg_wait<1>();
          release2(B_EMPTY1 + prev);
          prev = st;
          if (++st == 4) { st = 0; ph ^= 1; }
        }
        if (t == 5) break;
        issue(0, [&]() {
          sched_fence(q_st);
          wg_wait<0>();
          fence_regs<128>(R);
          TL(0, 3 + 2 * t + 16 * w, (tid & 127) == 0);
#pragma unroll
          for (int i = 0; i < 16; i++) { const uint4 v = packed(i); pk[4 * i] = v.x; pk[4 * i + 1] = v.y; pk[4 * i + 2] = v.z; pk[4 * i + 3] = v.w; }
          release2(B_EMPTY1 + prev);
          fence_regs<128>(R);
        });
        if (w == 1) bar_arrive(4, 256);
        sched_fence(q_st);
        pdst = g_qkv + (size_t)(((t & 1) + 1) * SEQ + mt * 128 + cw * 16 + (lane >> 2)) * NQ + (gq + ((t >> 1) ^ 1) * 8) * 256 + (lane & 3) * 8;
        if (t < 4) put2(0);
        if (w == 0) bar_sync(4, 256);
      }
      if (w == 1) bar_arrive(6, 256);
      mbar_wait_c(B(B_KF), 0);
      sched_fence(q_st);
      wg_wait<0>();
      fence_regs<128>(R);
      release2(B_EMPTY1 + 3);
      TL(0, 13 + 16 * w, (tid & 127) == 0);
    }
    auto issue3 = [&](int st, uint32_t ph, int accum) {
      mbar_wait_c(B(B_FULL3 + st), ph);
      const uint64_t da = mk_desc(sb + OFF_R3 + w * 8192 + st * SLOT, 16, 1024, 1), db = mk_desc(sb + OFF_R3 + 16384 + st * SLOT, 8192, 1024, 1);
      wg_fence();
#pragma unroll
      for (int k = 0; k < 4; k++) mma_n128_ss<1>(acc, desc_add(da, k * 32), desc_add(db, k * 2048), k == 0 ? accum : 1);
      wg_commit();
    };
    uint32_t wf[128];
    auto w_addr = [&](uint32_t off, int m) {
      const uint32_t w_ld = sb + ((lane >> 3) & 1) * 8192 + ((cw >> 1) * 32 + (lane & 7) + (lane >> 4) * 8) * 64 + ((((cw & 1) * 2) ^ ((lane >> 1) & 3)) << 4);
      return ((w_ld + off) ^ ((m & 1) << 4)) + (m >> 2) * 16384 + ((m >> 1) & 1) * 1024;
    };
    auto grab = [&](uint32_t* d, uint32_t off, int m0, int m1) {
#pragma unroll
      for (int m = m0; m < m1; m++)
        asm volatile("ldmatrix.sync.aligned.m8n8.x4.trans.shared.b16 {%0,%1,%2,%3}, [%4];"
                     : "=r"(d[4 * m]), "=r"(d[4 * m + 1]), "=r"(d[4 * m + 2]), "=r"(d[4 * m + 3]) : "r"(w_addr(off, m)) : "memory");
    };
    float inv[2] = {0.f, 0.f};
    auto scaled = [&](int i) {
      const float* o = O + 16 * (i >> 1) + 2 * (i & 1);
      const float c = inv[i & 1];
      return make_uint4(pack_bf16(o[0] * c, o[1] * c), pack_bf16(o[4] * c, o[5] * c), pack_bf16(o[8] * c, o[9] * c), pack_bf16(o[12] * c, o[13] * c));
    };
    {
      const int wrow = cw * 16;
      const uint64_t dk0 = mk_desc(sb, 16, 1024, 1);
      const uint64_t dv0 = mk_desc(sb + 2 * SLOT, 16384, 1024, 1);
      const uint32_t pin = sb + OFF_MISC + 1028;
      float l0 = 0.f, l1 = 0.f;
      int g = 0, t = 0;
      uint32_t fail = 0;
      auto piece = [&](int tt) { return (uint32_t)(tt == 3 ? 6 * SLOT + w * 16384 : (3 + 2 * w) * SLOT + (tt - 1) * 16384); };
      uint32_t par = 0;
      auto issue_s = [&](float* S) {
        const uint64_t dk = desc_add(dk0, par * 16);
        mma_n128_rs0(S, Q, dk);
#pragma unroll
        for (int k = 1; k < 8; k++) mma_n128_rs<0>(S, Q + 4 * k, desc_add(dk, (k >> 2) * 16384 + (k & 3) * 32), 1);
        wg_commit();
      };
      auto issue_pv = [&](bool half, int accum) {
        const uint64_t dv = desc_add(dv0, ((g - 1) & 1) * 2 * SLOT);
        wg_fence();
#pragma unroll
        for (int k = 0; k < 4; k++) mma_n128_rs<1>(O, P + 4 * k, desc_add(dv, k * 2048), k == 0 ? accum : 1);
        wg_commit();
        if (UNLIKELY(half)) {
          wg_fence();
          wg_commit();
        } else {
          wg_fence();
#pragma unroll
          for (int k = 4; k < 8; k++) mma_n128_rs<1>(O, P + 4 * k, desc_add(dv, k * 2048), 1);
          wg_commit();
        }
        bar_arrive(2 - w, 256);
        wg_wait<2>();
        fence_regs<32>(Q);
      };
      auto release_k = [&]() { release2(B_KE); rbar ^= 8; };
      auto pv_done = [&]() {
        TC(g, 3);
        sched_fence(q_st);
        wg_wait<0>();
        fence_regs<64>(O); fence_regs<32>(P);
        TC(g, 4);
        release2(B_VE);
      };
      auto row_inv = [&](bool go) {
        float a = l0 + __shfl_xor_sync(~0u, l0, 1), b = l1 + __shfl_xor_sync(~0u, l1, 1);
        a += __shfl_xor_sync(~0u, a, 2); b += __shfl_xor_sync(~0u, b, 2);
        const bool ok = __all_sync(~0u, a >= AT_LO && a <= AT_HI && b >= AT_LO && b <= AT_HI) != 0;
        asm("rcp.approx.ftz.f32 %0, %1;" : "=f"(inv[0]) : "f"(a));
        asm("rcp.approx.ftz.f32 %0, %1;" : "=f"(inv[1]) : "f"(b));
        fail |= (uint32_t)(go && !ok) << t;
        l0 = go ? 0.f : l0; l1 = go ? 0.f : l1;
        t += go;
      };
      const uint64_t m_first = 1ull | (1ull << (16 - ti)) | (1ull << 17) | (1ull << (18 + ti));
      const uint64_t m_diag = (1ull << (15 - ti - 2 * rank)) | (1ull << (16 - ti)) | (9ull << (17 + ti));
      enum { F_FIRST = 1, F_DIAG = 2, F_LAST = 4, F_PFIRST = 8, F_PHALF = 16, F_STOP = 32 };
      auto kind = [&](int gn) {
        const uint32_t a = (uint32_t)((m_first << 1) >> gn), d = (uint32_t)((m_diag << 1) >> gn);
        return ((a >> 1) & 1) * F_FIRST | ((d >> 1) & 1) * F_DIAG | ((a >> 2) & 1) * F_LAST | (a & 1) * F_PFIRST |
               (w == 0 ? (d & 1) * F_PHALF | ((d >> 1) & 1) * F_STOP : 0) | (gn == 34 ? F_STOP : 0);
      };
      uint32_t kinds;
      {
        uint32_t qt[64];
#pragma unroll
        for (int i = 0; i < 16; i++) { const uint4 v = packed(i); qt[4 * i] = v.x; qt[4 * i + 1] = v.y; qt[4 * i + 2] = v.z; qt[4 * i + 3] = v.w; }
        fence_regs<64>(qt);
        sched_fence(q_st);
        float S[64];
        wg_fence();
        issue_s(S);
        bar_arrive(w ? 1 : 7, 256);
        bar_sync(6 + w, 256);
        sched_fence(q_st);
        TL(1, 0, tid == 128);
#pragma unroll
        for (int i = 0; i < 16; i++) park(piece(1), i, make_uint4(qt[4 * i], qt[4 * i + 1], qt[4 * i + 2], qt[4 * i + 3]));
        kinds = pinned(kind(lane + 3));
        sched_fence(q_st);
        wg_wait<0>();
        fence_regs<64>(S);
        release_k();
        TL(1, 1, tid == 128);
        const bool kok = mbar_try(B(B_KF + 1), 0);
        at_exp<0, 32>(S);
        sched_fence(q_st);
        at_exp<32, 64>(S); at_fin<0, 64>(S, P);
        if (UNLIKELY(!kok)) mbar_wait_c(B(B_KF + 1), 0);
        TL(1, 2, tid == 128);
      }
      uint32_t f = F_PFIRST, fn;
      auto shadow = [&]() {
        const bool vok = mbar_try(B(B_VF + ((g - 1) & 1)), ((g - 1) >> 1) & 1);
        at_sum(P, f & F_PHALF, l0, l1);
        fn = __shfl_sync(~0u, kinds, max(g - 2, 0));
        if (UNLIKELY(!vok)) mbar_wait_c(B(B_VF + ((g - 1) & 1)), ((g - 1) >> 1) & 1);
      };
      auto hand_over = [&]() { __syncwarp(); if (lane == 0 && !((fail >> (t - 1)) & 1)) mbar_arrive(B(B_PUB + 1 + t)); };
      auto exp_q = [&](float* S, auto kc, auto nc) {
        constexpr int k = decltype(kc)::value, n = decltype(nc)::value;
        asm volatile("{\n.reg .pred p;\nsetp.ne.b32 p, %5, 0;\n@p ldmatrix.sync.aligned.m8n8.x4.shared.b16 {%0,%1,%2,%3}, [%4];\n}"
                     : "+r"(Q[4 * k]), "+r"(Q[4 * k + 1]), "+r"(Q[4 * k + 2]), "+r"(Q[4 * k + 3])
                     : "r"(((q_ld + piece(t + 1)) ^ ((k & 1) << 5)) + (k >> 1) * 4096), "r"(f & F_LAST) : "memory");
        at_exp<n * k, n * k + n>(S);
      };
      g = 1; par = SLOT / 16;
#pragma unroll 1
      for (;;) {
        {
          TC(g, 0);
          bar_sync(1 + w, 256);
          fence_regs<32>(Q);
          float S[64];
          wg_fence();
          issue_s(S);
          sched_fence(q_st);
          TC(g, 1);
          shadow();
          fence_regs<64>(O); fence_regs<32>(P);
          issue_pv(f & F_PHALF, ~f & F_PFIRST);
          fence_regs<64>(S);
          TC(g, 2);
          release_k();
          at_exp<0, 8>(S);
          const bool first = f & F_FIRST;
          if (UNLIKELY(f & (F_FIRST | F_LAST | F_DIAG))) {
            row_inv(first);
            at_mask(S + 32, (f & F_DIAG) ? wrow - 64 : 64, lane);
            unroll8([&](auto kc) { exp_q(S + 8, kc, std::integral_constant<int, AT_R1 / 8 - 1>{}); });
          } else {
            at_exp<8, AT_R1>(S);
          }
          pv_done();
          g = pinned(g + 1); par = pinned(par ^ (SLOT / 16)); f = fn;
          const bool kok = mbar_try(B(B_KF + (g & 1)), g < 34 ? (g >> 1) & 1 : 0);
          if (UNLIKELY(first)) {
            unroll8([&](auto ic) {
              constexpr int i = decltype(ic)::value, n = (64 - AT_R1) / 8;
              at_exp<AT_R1 + n * i, AT_R1 + n * i + n>(S);
              park(piece(t), i, scaled(i));
            });
            at_fin<0, 64>(S, P);
            hand_over();
          } else {
            at_exp<AT_R1, 64>(S); at_fin<0, 64>(S, P);
          }
          TC(g - 1, 5);
          if (!TCLK) TL(1, 1 + g, tid == 128);
          if (kok && !(f & F_STOP)) continue;
          if (UNLIKELY(!kok)) mbar_wait_c(B(B_KF + (g & 1)), (g >> 1) & 1);
          if (g == 34) break;
        }
#pragma unroll 1
        while (f & F_STOP) {
          TC(g, 0);
          bar_sync(1, 256);
          fence_regs<64>(O); fence_regs<32>(Q); fence_regs<32>(P);
          float S[32];
          const uint64_t dk = desc_add(dk0, par * 16);
          wg_fence();
          mma_n64_rs0(S, Q, dk);
#pragma unroll
          for (int k = 1; k < 8; k++) mma_n64_rs(S, Q + 4 * k, desc_add(dk, (k >> 2) * 16384 + (k & 3) * 32), 1);
          wg_commit();
          TC(g, 1);
          mbar_wait_c(B(B_VF + ((g - 1) & 1)), ((g - 1) >> 1) & 1);
          issue_pv(f & F_PHALF, ~f & F_PFIRST);
          fence_regs<32>(S);
          TC(g, 2);
          release_k();
          const bool first = f & F_FIRST;
          at_sum(P, f & F_PHALF, l0, l1);
          fn = __shfl_sync(~0u, kinds, g - 2);
          row_inv(first);
          pv_done();
          sched_fence(q_st);
          at_mask(S, wrow, lane);
          unroll8([&](auto kc) { exp_q(S, kc, std::integral_constant<int, 4>{}); });
          g++; par ^= SLOT / 16; f = fn;
          at_fin<0, 32>(S, P);
          if (first) {
#pragma unroll
            for (int i = 0; i < 8; i++) park(piece(t), i, scaled(i));
            hand_over();
          }
          TC(g - 1, 5);
          if (!TCLK) TL(1, 1 + g, tid == 128);
          mbar_wait_c(B(B_KF + (g & 1)), (g >> 1) & 1);
        }
      }
      const bool wok = mbar_test(B(ffn ? B_WF : B_QP + 1), 0);
      grab(wf, 3 * SLOT, 0, 8);
      mbar_wait_c(B(B_VF + 1), 0);
      bar_sync(1 + w, 256);
      fence_regs<64>(O); fence_regs<32>(P);
      wg_fence();
#pragma unroll
      for (int k = 0; k < 8; k++) mma_n128_rs<1>(O, P + 4 * k, desc_add(dv0, 2 * SLOT + k * 2048), 1);
      wg_commit();
      if (w == 0) bar_arrive(2, 256);
      pin_order(__uint_as_float(wf[28] & wf[24]), pin);
      __syncwarp();
      if (wok) release2(B_WE);
      TL(3, 12 + 16 * w, (tid & 127) == 0);
      sched_fence(q_st);
      at_sum(P, false, l0, l1);
      row_inv(true);
      sched_fence(q_st);
      wg_wait<0>();
      fence_regs<64>(O); fence_regs<32>(P);
      release2(B_VE + 1);
      if (UNLIKELY(!wok || fail != 0)) {
#pragma unroll 1
        for (int tt = 0; tt < 4; tt++) {
          if (!((tt < 3 ? fail >> tt : fail != 0) & 1)) continue;
          slow_tile(O, P, l0, l1, wq, (((tt + 1) & 2) ? ti : 15 - ti) * 128 + wrow, hh + (tt & 2) * 8, lane, q_st);
          row_inv(false);
          if (tt < 3) {
#pragma unroll
            for (int i = 0; i < 8; i++) park(piece(tt + 1), i, scaled(i));
            publish(2 + tt);
          }
        }
        if (!wok) {
          mbar_wait_c(B(ffn ? B_WF : B_QP + 1), 0);
          grab(wf, 3 * SLOT, 0, 8);
          pin_order(__uint_as_float(wf[28] & wf[24]), pin);
          __syncwarp();
          release2(B_WE);
        }
      }
      TL(3, 13 + 16 * w, (tid & 127) == 0);
      issue3(0, 0, 0);
      TL(3, 14 + 16 * w, (tid & 127) == 0);
      TL(1, 36, tid == 128);
    }
    uint32_t hp[32];
    lane = lane_id();
    {
      int st = 1, prev = 0; uint32_t ph = 0;
      __nv_bfloat16* dst = g_qkv + (size_t)((15 - ti) * 128 + cw * 16 + (lane >> 2)) * NQ + (hh + 16) * 128 + (lane & 3) * 8;
      auto kblock = [&](auto between, int lim = 6) {
        issue3(st, ph, 1);
        between();
        wg_wait<1>();
        release2(B_EMPTY3 + prev);
        prev = st;
        if (++st == lim) { st = 0; ph ^= 1; }
      };
      uint4 ob[8];
      kblock([&]() { sched_fence(rbar); ob[0] = scaled(0); ob[1] = scaled(2); ob[2] = scaled(1); ob[3] = scaled(3); sched_fence(rbar); });
      kblock([&]() { sched_fence(rbar); ob[4] = scaled(4); ob[5] = scaled(6); ob[6] = scaled(5); ob[7] = scaled(7); sched_fence(rbar); grab(wf + 32, 5 * SLOT, 0, 8); });
#pragma unroll 1
      for (int kb = 3; kb < 11; kb++) {
        kblock([&]() {
          sched_fence(rbar);
#pragma unroll
          for (int i = 0; i < 8; i++)
            if (kb == 3 + i) *reinterpret_cast<uint4*>(dst + (i & 2) * 4 * NQ + (i & 1) * 32 + (i & 4) * 16) = ob[i];
          TL(3, 14 + kb + 16 * w, (tid & 127) == 0);
          if (kb == 8) TL(2, 2, tid == 128);
        }, kb == 4 ? 5 : 6);
        if (kb == 4) release2(B_EMPTY3 + 5);
      }
      publish(5);
      kblock([&]() { mbar_wait_c(B(ffn ? B_WF2 : B_QP + 2), 0); grab(wf + 32, 5 * SLOT, 8, 16); });
#pragma unroll 1
      for (int kb = 12; kb < G_KB; kb++) {
        kblock([&]() { if ((kb & 7) == 0) TL(2, 1 + (kb >> 3), tid == 128); });
        if (kb == X_KB && lane == 0) mbar_arrive(B(B_XE));
      }
      kblock([&]() {
        mbar_wait_c(B(B_XF), 0);
#pragma unroll
        for (int i = 0; i < 8; i++)
          ldsm4(hp + 4 * i, sb + 6 * SLOT + w * 16384 + ((cw & 3) * 16 + (lane & 15)) * 128 + (i >> 2) * 8192 + ((((i & 3) * 2 + (lane >> 4)) ^ (lane & 7)) << 4));
      });
#pragma unroll 1
      for (int kb = G_KB + 1; kb < 64; kb++) {
        kblock([&]() { if ((kb & 7) == 0) TL(2, 1 + (kb >> 3), tid == 128); });
        if (kb == G_KB + 2 && lane == 0) mbar_arrive(B(B_XE));
      }
    }
    lane = lane_id();
    const int r0 = lane >> 2, q4 = lane & 3, ct = cw * 32 + lane;
    uint32_t tb[16];
    mbar_wait_c(B(B_WR), 0);
#pragma unroll
    for (int i = 0; i < 4; i++) ldsm4(tb + 4 * i, sb + OFF_MISC + 512 + (lane & 1) * 256 + (lane >> 3) * 16 + i * 64);
    mbar_wait_c(B(B_SET2), 0);
    float4* const psd = reinterpret_cast<float4*>(xr + XR_PS + cw * 16 + r0);
    const uint4* const pss = g_xr + (mt * 8 + (ct & 1) * 4) * XR_SIZE + XR_PS + (ct >> 1);
    sched_fence(stg);
    wg_wait<0>();
    fence_regs<64>(acc);
    TL(2, 10, tid == 128);
    {
      float d[2][4] = {}, qa[2][4] = {}, qb[2][4] = {};
#pragma unroll
      for (int j = 0; j < 16; j++) {
        hp[2 * j] = hadd2_bf(hp[2 * j], pack_bf16(acc[4 * j], acc[4 * j + 1]));
        hp[2 * j + 1] = hadd2_bf(hp[2 * j + 1], pack_bf16(acc[4 * j + 2], acc[4 * j + 3]));
        if (j & 1) {
          mma16816(d[(j >> 1) & 1], hp[2 * j - 2], hp[2 * j - 1], hp[2 * j], hp[2 * j + 1], tb[j - 1], tb[j]);
          mma16816(qa[(j >> 1) & 1], hp[2 * j - 2], hp[2 * j - 1], hp[2 * j], hp[2 * j + 1], hp[2 * j - 2], hp[2 * j]);
          mma16816(qb[(j >> 1) & 1], hp[2 * j - 2], hp[2 * j - 1], hp[2 * j], hp[2 * j + 1], hp[2 * j - 1], hp[2 * j + 1]);
        }
      }
      if (q4 == (r0 >> 1)) {
        __stcg(psd, make_float4(d[0][0] + d[1][0], (r0 & 1) ? qa[0][1] + qa[1][1] : qa[0][0] + qa[1][0], d[0][1] + d[1][1], 0.f));
        __stcg(psd + 8, make_float4(d[0][2] + d[1][2], (r0 & 1) ? qb[0][3] + qb[1][3] : qb[0][2] + qb[1][2], d[0][3] + d[1][3], 0.f));
      }
    }
    TL(2, 11, tid == 128);
    mbar_wait_c(B(B_EMPTY3 + 1), 0);
    stage_store_128(stg, lane, hp);
    if (ffn) mbar_wait_c(B(B_WF2), 1);
    grab(wf + 96, 6 * SLOT, 0, 8);
    const float wsum = *reinterpret_cast<const float*>(sp + OFF_MISC + 1024);
    __syncwarp();
    {
      uint4 ps[4];
      poll_chunks(ps, pss, XR_SIZE);
      TL(2, 12, tid == 128);
      auto F = [](uint32_t u) { return __uint_as_float(u); };
      float s1 = (F(ps[0].x) + F(ps[1].x)) + (F(ps[2].x) + F(ps[3].x)), s2 = (F(ps[0].y) + F(ps[1].y)) + (F(ps[2].y) + F(ps[3].y));
      float s3 = (F(ps[0].z) + F(ps[1].z)) + (F(ps[2].z) + F(ps[3].z));
      __syncwarp();
      s1 += __shfl_xor_sync(~0u, s1, 1); s2 += __shfl_xor_sync(~0u, s2, 1); s3 += __shfl_xor_sync(~0u, s3, 1);
      const float mean = s1 * (1.f / DM);
      float mb, inv;
      ln_round(mean, fmaxf(fmaf(s2, 1.f / DM, -mean * mean), 0.f), mb, inv);
      const uint32_t u = pack_bf16(0.f, fmaf(s3 - mb * wsum, inv, 0.f));
      const uint32_t key = (u ^ ((((int)u >> 31) & 0x7FFF0000u) | 0x80000000u)) | (0x7FFFu - (mt * 128 + (ct >> 1)));
      const uint32_t nm2 = pack_bf16(-mb, -mb);
      const uint32_t c1 = __reduce_max_sync(~0u, key);
      const uint32_t c2 = __reduce_max_sync(~0u, key == c1 ? 0u : key);
      if (lane == 0) {
        __stcg(reinterpret_cast<uint2*>(psd) + (XR_KEY - XR_PS) * 2 - cw * 31, make_uint2(c1, c2));
        mbar_arrive(B(B_OUT));
      }
      TL(2, 13, tid == 128);
      const int row = (0x7FFF - (((lane >> 4) ? c2 : c1) & 0x7FFF)) & 15;
      const uint32_t rn = __shfl_sync(~0u, nm2, row * 2);
      const uint2 ri = ln_split(__shfl_sync(~0u, inv, row * 2));
      uint32_t v[4];
#pragma unroll
      for (int i = 0; i < 4; i++)
        asm volatile("ld.shared.u32 %0, [%1];" : "=r"(v[i]) : "r"(stg + ((lane >> 3) & 1) * 8192 + row * 128 + ((((lane & 4) + i) ^ (row & 7)) << 4) + q4 * 4) : "memory");
      __stcg(xr + XR_CAND + cw * 64 + 32 + lane, make_uint4(ln_apply(v[0], rn, ri), ln_apply(v[1], rn, ri), ln_apply(v[2], rn, ri), ln_apply(v[3], rn, ri)));
      __stcg(xr + XR_CAND + cw * 64 + lane, make_uint4(v[0], v[1], v[2], v[3]));
      sched_fence(stg);
      const uint32_t na = __shfl_sync(~0u, nm2, r0 * 2), nb = __shfl_sync(~0u, nm2, r0 * 2 + 16);
      const uint2 ia = ln_split(__shfl_sync(~0u, inv, r0 * 2)), ib = ln_split(__shfl_sync(~0u, inv, r0 * 2 + 16));
#pragma unroll
      for (int i = 0; i < 32; i++) hp[i] = hadd2_bf(hp[i], ln_apply(hp[i], (i & 1) ? nb : na, (i & 1) ? ib : ia));
      __syncwarp();
      stage_store_128(stg, lane, hp);
      publish(B_OUT3 - B_PUB);
    }
    uint32_t wd[16][4];
    sched_fence(stg);
    if (ffn) mbar_wait_c(B(B_FULL3 + 5 * w), 1 - w);
    auto load_wd = [&](int h) {
#pragma unroll
      for (int i = h; i < 16; i += 2)
        asm volatile("ldmatrix.sync.aligned.m8n8.x4.trans.shared.b16 {%0,%1,%2,%3}, [%4];"
                     : "=r"(wd[i][0]), "=r"(wd[i][1]), "=r"(wd[i][2]), "=r"(wd[i][3])
                     : "r"(sb + OFF_R3 + 5 * w * SLOT + (2 * (cw & 3) + (i >> 3)) * 4096 + (h * 16 + (lane & 7) + (lane >> 4) * 8) * 128 +
                           (((2 * ((i >> 1) & 3) + ((lane >> 3) & 1)) ^ (lane & 7)) << 4)) : "memory");
    };
    load_wd(0);
    __syncwarp();
    cluster_arrive();
    const char* xsrc = reinterpret_cast<const char*>(g_xr + (r0 >> 1) * XR_SIZE + XR_CAND + 32 + (cw >> 1) * 4 + q4);
    asm volatile("" : "+l"(xsrc));
    sched_fence(stg);
    TL(2, 22, tid == 128);
    mbar_wait_c(B(B_OUT2), 0);
    TL(2, 14, tid == 128);
    if (ffn) {
      uint4 xb[2];
      const uint4* xp = reinterpret_cast<const uint4*>(xsrc + *reinterpret_cast<const uint32_t*>(sp + OFF_MISC + 8 + (r0 & 1) * 4));
      poll_chunks(xb, xp, 4 * XR_SIZE);
      __syncwarp();
      TL(2, 15, tid == 128);
      float d[8][4] = {};
#pragma unroll
      for (int n = 0; n < 32; n++) {
        if (n == 8) { sched_fence(stg); load_wd(1); }
        const int s = (n >> 4) * 4 + ((n >> 1) & 3), m = ((n >> 3) & 1) * 2 + (n & 1);
        const uint32_t* a = wf + 16 * s + 4 * m;
        mma16816(d[n & 7], a[0], a[1], a[2], a[3], (m & 2) ? xb[s >> 2].z : xb[s >> 2].x, (m & 2) ? xb[s >> 2].w : xb[s >> 2].y);
      }
      float v[8];
#pragma unroll
      for (int i = 0; i < 8; i++) {
        const float lo = (q4 & 1) ? d[2 + (i >> 2)][i & 3] : d[i >> 2][i & 3], hi = (q4 & 1) ? d[6 + (i >> 2)][i & 3] : d[4 + (i >> 2)][i & 3];
        v[i] = (q4 & 2) ? hi : lo;
      }
#pragma unroll
      for (int i = 0; i < 4; i++) v[i] = ((q4 & 2) ? v[i + 4] : v[i]) + __shfl_xor_sync(~0u, (q4 & 2) ? v[i] : v[i + 4], 2);
#pragma unroll
      for (int i = 0; i < 2; i++) v[i] = ((q4 & 1) ? v[i + 2] : v[i]) + __shfl_xor_sync(~0u, (q4 & 1) ? v[i] : v[i + 2], 1);
      float4* red = reinterpret_cast<float4*>(sp + SL_SCR * SLOT);
      reinterpret_cast<float2*>(red + cw * 16 + (q4 >> 1) * 8 + r0)[q4 & 1] = make_float2(v[0], v[1]);
      bar_sync(3, 256);
      TL(2, 16, tid == 128);
      const float4 z0 = red[lane], z1 = red[32 + lane], z2 = red[64 + lane], z3 = red[96 + lane];
      const uint32_t ub = pack_bf16((z0.x + z1.x) + (z2.x + z3.x), (z0.y + z1.y) + (z2.y + z3.y));
      const uint32_t gb = pack_bf16((z0.z + z1.z) + (z2.z + z3.z), (z0.w + z1.w) + (z2.w + z3.w));
      const float g0 = bf_lo(gb), g1 = bf_hi(gb);
      const uint32_t sg = pack_bf16(g0 * sigmoid(g0), g1 * sigmoid(g1));
      const uint32_t act = pack_bf16(bf_lo(sg) * bf_lo(ub), bf_hi(sg) * bf_hi(ub));
      const uint32_t pr = __byte_perm(act, __shfl_xor_sync(~0u, act, 1), (lane & 1) ? 0x3276 : 0x5410);
      const int src = q4 * 2 + (r0 & 1);
      const uint32_t a0 = __shfl_sync(~0u, pr, src), a1 = __shfl_sync(~0u, pr, src + 8), a2 = __shfl_sync(~0u, pr, src + 16), a3 = __shfl_sync(~0u, pr, src + 24);
      TL(2, 17, tid == 128);
      float y[8][4] = {};
#pragma unroll
      for (int i = 0; i < 8; i++) mma16816(y[i], wd[2 * i][0], wd[2 * i][1], wd[2 * i][2], wd[2 * i][3], a0, a1);
#pragma unroll
      for (int i = 0; i < 8; i++) mma16816(y[i], wd[2 * i + 1][0], wd[2 * i + 1][1], wd[2 * i + 1][2], wd[2 * i + 1][3], a2, a3);
      float2* yd = reinterpret_cast<float2*>(g_xr + (cw * 16 + 2 * q4) * XR_SIZE + XR_Y + fid * 4) + r0;
#pragma unroll
      for (int j = 0; j < 2; j++) {
        float v[4];
#pragma unroll
        for (int e = 0; e < 4; e++) {
          const float lo = (q4 & 1) ? y[4 * j + 1][e] : y[4 * j][e], hi = (q4 & 1) ? y[4 * j + 3][e] : y[4 * j + 2][e];
          v[e] = (q4 & 2) ? hi : lo;
        }
        __stcg(yd + j * 16 * XR_SIZE, make_float2(v[0], v[1]));
        __stcg(yd + j * 16 * XR_SIZE + 2 * XR_SIZE, make_float2(v[2], v[3]));
      }
    }
    TL(2, 18, tid == 128);
    cluster_wait();
    if (rid == 127 && ct < C_NUM) g_cnt[ct] = 0;
    if (cw < 2) {
      const int tok = (lane >> 1) & 1, pair = cw * 2 + (lane & 1);
      uint32_t* const dst = reinterpret_cast<uint32_t*>(out + (size_t)(~*reinterpret_cast<const uint32_t*>(sp + OFF_MISC + tok * 4) & 0x7FF) * DM) + rid * 4 + pair;
      idle(ffn ? Y_CLK : Y_CLK + 2000);
      const bool fin = mbar_test(B(B_FIN), 0);
      uint4 op = lds128(sb + OFF_MISC + 128 + (tok * 4 + pair) * 16);
      uint4 z[7];
      poll_chunks(z, xr + XR_Y + (lane >> 1) * 4 + pair, 64);
      __syncwarp();
      TL(2, 19, tid == 128);
      if (!fin) { mbar_wait_c(B(B_FIN), 0); op = lds128(sb + OFF_MISC + 128 + (tok * 4 + pair) * 16); }
      auto F = [](uint32_t u) { return __uint_as_float(u); };
      const float v0 = ((F(z[0].x) + F(z[1].x)) + (F(z[2].x) + F(z[3].x))) + ((F(z[4].x) + F(z[5].x)) + F(z[6].x));
      const float v1 = ((F(z[0].y) + F(z[1].y)) + (F(z[2].y) + F(z[3].y))) + ((F(z[4].y) + F(z[5].y)) + F(z[6].y));
      const float v2 = ((F(z[0].z) + F(z[1].z)) + (F(z[2].z) + F(z[3].z))) + ((F(z[4].z) + F(z[5].z)) + F(z[6].z));
      const float v3 = ((F(z[0].w) + F(z[1].w)) + (F(z[2].w) + F(z[3].w))) + ((F(z[4].w) + F(z[5].w)) + F(z[6].w));
      float ya = (tok ? v1 : v0) + __shfl_xor_sync(~0u, tok ? v0 : v1, 2), yb = (tok ? v3 : v2) + __shfl_xor_sync(~0u, tok ? v2 : v3, 2);
#pragma unroll
      for (int o = 4; o < 32; o <<= 1) { ya += __shfl_xor_sync(~0u, ya, o); yb += __shfl_xor_sync(~0u, yb, o); }
      const uint32_t yp = pack_bf16(ya, yb);
      if (lane < 4) *dst = hadd2_bf(op.x, hadd2_bf(op.y, pack_bf16(bf_lo(yp) * F(op.z), bf_hi(yp) * F(op.z))));
      TL(2, 21, tid == 128);
    }
    TL(2, 20, tid == 128);
    TL_DUMP();
  }
}

typedef CUresult (*EncodeFn)(CUtensorMap*, CUtensorMapDataType, cuuint32_t, void*, const cuuint64_t*, const cuuint64_t*, const cuuint32_t*,
                             const cuuint32_t*, CUtensorMapInterleave, CUtensorMapSwizzle, CUtensorMapL2promotion, CUtensorMapFloatOOBfill);
EncodeFn g_enc = nullptr;

void map2(CUtensorMap* m, const void* ptr, uint64_t rows, uint64_t cols, uint32_t bc, uint32_t br) {
  const CUtensorMapSwizzle sw = bc == 64 ? CU_TENSOR_MAP_SWIZZLE_128B : CU_TENSOR_MAP_SWIZZLE_64B;
  cuuint64_t gd[2] = {cols, rows}, gs[1] = {cols * 2};
  cuuint32_t bd[2] = {bc, br}, es[2] = {1, 1};
  g_enc(m, CU_TENSOR_MAP_DATA_TYPE_BFLOAT16, 2, (void*)ptr, gd, gs, bd, es, CU_TENSOR_MAP_INTERLEAVE_NONE, sw,
        CU_TENSOR_MAP_L2_PROMOTION_L2_128B, CU_TENSOR_MAP_FLOAT_OOB_FILL_NONE);
}
void map3(CUtensorMap* m, const void* ptr, uint64_t rows, uint64_t cols, uint32_t br, uint32_t bch, uint32_t bc = 64) {
  cuuint64_t gd[3] = {bc, rows, cols / bc}, gs[2] = {cols * 2, bc * 2};
  cuuint32_t bd[3] = {bc, br, bch}, es[3] = {1, 1, 1};
  g_enc(m, CU_TENSOR_MAP_DATA_TYPE_BFLOAT16, 3, (void*)ptr, gd, gs, bd, es, CU_TENSOR_MAP_INTERLEAVE_NONE, bc == 64 ? CU_TENSOR_MAP_SWIZZLE_128B : CU_TENSOR_MAP_SWIZZLE_64B,
        CU_TENSOR_MAP_L2_PROMOTION_L2_128B, CU_TENSOR_MAP_FLOAT_OOB_FILL_NONE);
}

}

extern "C" void kernel_launch(void* const* d_in, const int* in_sizes, int n_in, void* d_out, int out_size) {
  const __nv_bfloat16* x = (const __nv_bfloat16*)d_in[0];
  const __nv_bfloat16* ckv = (const __nv_bfloat16*)d_in[1];
  const __nv_bfloat16* wq = (const __nv_bfloat16*)d_in[2];
  const __nv_bfloat16* wk = (const __nv_bfloat16*)d_in[3];
  const __nv_bfloat16* wv = (const __nv_bfloat16*)d_in[4];
  const __nv_bfloat16* wo = (const __nv_bfloat16*)d_in[5];
  const __nv_bfloat16* w_r = (const __nv_bfloat16*)d_in[7];
  const __nv_bfloat16* wgate = (const __nv_bfloat16*)d_in[8];
  const __nv_bfloat16* wup = (const __nv_bfloat16*)d_in[9];
  const __nv_bfloat16* wdown = (const __nv_bfloat16*)d_in[10];
  __nv_bfloat16* out = (__nv_bfloat16*)d_out;

  if (!g_enc) {
    void* fn = nullptr;
    cudaDriverEntryPointQueryResult qr;
    cudaGetDriverEntryPoint("cuTensorMapEncodeTiled", &fn, cudaEnableDefault, &qr);
    g_enc = (EncodeFn)fn;
    cudaFuncSetAttribute(fused_kernel, cudaFuncAttributeMaxDynamicSharedMemorySize, SMEM_BYTES);
  }
  void *xn, *qkv;
  cudaGetSymbolAddress(&xn, g_xn);
  cudaGetSymbolAddress(&qkv, g_qkv);

  Params p;
  map2(&p.xn, xn, SEQ, DM, 64, 128);
  map2(&p.ckv, ckv, SEQ, DC, 64, 128);
  map3(&p.wq, wq, DM, NQ, 64, 2);
  map3(&p.wk, wk, DC, NQ, 64, 2);
  map3(&p.wv, wv, DC, NQ, 64, 2);
  map3(&p.kv, qkv, 3 * SEQ, NQ, 128, 1);
  map2(&p.ctx_ld, qkv, SEQ, NQ, 64, 128);
  map3(&p.ctx_st, qkv, SEQ, NQ, 64, 1, 32);
  map3(&p.wo, wo, NQ, DM, 64, 1);
  map3(&p.x, x, SEQ, DM, 64, 1);
  map3(&p.wd, wdown, FF, DM, 32, 8);
  map2(&p.out, out, SEQ, DM, 64, 64);
  map2(&p.wg, wgate, DM, FF, 32, 128);
  map2(&p.wu, wup, DM, FF, 32, 128);
  fused_kernel<<<128, 384, SMEM_BYTES, cudaStreamPerThread>>>(x, wq, w_r, out, p);
}
```

```cpp
#include <cuda_runtime.h>
#include <cuda_bf16.h>
#include <cuda.h>
#include <stdint.h>
#include <type_traits>

#pragma nv_diag_suppress 549
namespace {

constexpr int SEQ = 2048, DM = 1024, NH = 32, HD = 128, DC = 512, NQ = NH * HD, FF = 3584;

__device__ __align__(1024) __nv_bfloat16 g_xn[SEQ * DM];
__device__ __align__(1024) __nv_bfloat16 g_qkv[2 * SEQ * NQ];
constexpr int XR_PS = 0;
constexpr int XR_KEY = 128;
constexpr int XR_FLAG = 132;
constexpr int XR_CAND = 136;
constexpr int XR_Y = 648;
constexpr int XR_SIZE = 1104;
__device__ __align__(1024) uint4 g_xr[128 * XR_SIZE];
constexpr int C_LN = 0, C_QKV = 16, C_CTX = 32, C_HD = 64, C_NUM = 80;
__device__ unsigned g_cnt[C_NUM];

#define TL(k, i, cond) do {} while (0)
#define TL_BYTES 0
#define TL_INIT() do {} while (0)
#define TL_DUMP() do {} while (0)
#define TC(g, i) do {} while (0)
#define TS(i) do {} while (0)
#undef TCLK
#define TCLK 0

__device__ __forceinline__ uint32_t s2u(const void* p) { return (uint32_t)__cvta_generic_to_shared(p); }
__device__ __forceinline__ void mbar_init(uint32_t b, uint32_t c) { asm volatile("mbarrier.init.shared::cta.b64 [%0], %1;" ::"r"(b), "r"(c) : "memory"); }
__device__ __forceinline__ void mbar_expect(uint32_t b, uint32_t bytes) { asm volatile("mbarrier.arrive.expect_tx.shared::cta.b64 _, [%0], %1;" ::"r"(b), "r"(bytes) : "memory"); }
__device__ __forceinline__ void mbar_arrive(uint32_t b) { asm volatile("mbarrier.arrive.shared::cta.b64 _, [%0];" ::"r"(b) : "memory"); }
__device__ __forceinline__ bool mbar_test(uint32_t b, uint32_t ph) {
  uint32_t ok;
  asm volatile("{\n.reg .pred p;\nmbarrier.test_wait.parity.shared::cta.b64 p, [%1], %2;\nselp.u32 %0, 1, 0, p;\n}" : "=r"(ok) : "r"(b), "r"(ph) : "memory");
  return ok;
}
__device__ __forceinline__ void mbar_wait(uint32_t b, uint32_t ph) {
  asm volatile(
      "{\n.reg .pred p;\n.reg .u32 n;\nmov.u32 n, 0;\n"
      "LW:\nmbarrier.try_wait.parity.shared::cta.b64 p, [%0], %1, 20000;\n@p bra LD;\n"
      "add.u32 n, n, 1;\nsetp.lt.u32 p, n, 0x40000;\n@p bra LW;\ntrap;\nLD:\n}" ::"r"(b), "r"(ph) : "memory");
}
__device__ __forceinline__ void mbar_wait_c(uint32_t b, uint32_t ph) {
  asm volatile(
      "{\n.reg .pred p;\n.reg .u32 n;\nmov.u32 n, 0;\n"
      "LW:\nmbarrier.try_wait.parity.shared::cta.b64 p, [%0], %1;\n@p bra LD;\n"
      "add.u32 n, n, 1;\nsetp.lt.u32 p, n, 0x100000;\n@p bra LW;\ntrap;\nLD:\n}" ::"r"(b), "r"(ph) : "memory");
}
__device__ __forceinline__ bool mbar_try(uint32_t b, uint32_t ph) {
  uint32_t ok;
  asm volatile("{\n.reg .pred p;\nmbarrier.try_wait.parity.shared::cta.b64 p, [%1], %2;\nselp.u32 %0, 1, 0, p;\n}" : "=r"(ok) : "r"(b), "r"(ph) : "memory");
  return ok;
}
#define UNLIKELY(c) __builtin_expect(!!(c), 0)
__device__ __forceinline__ uint32_t pinned(uint32_t v) { uint32_t r; asm volatile("mov.b32 %0, %1;" : "=r"(r) : "r"(v)); return r; }
__device__ __forceinline__ bool elect_one() {
  uint32_t p;
  asm volatile("{\n.reg .pred p;\nelect.sync _|p, 0xFFFFFFFF;\nselp.u32 %0, 1, 0, p;\n}" : "=r"(p));
  return p;
}
__device__ __forceinline__ int lane_id() { int r; asm volatile("mov.u32 %0, %%laneid;" : "=r"(r)); return r; }
template <bool SLEEP = false>
__device__ __forceinline__ void spin_until_ge(const unsigned* p, unsigned target) {
  asm volatile(
      "{\n.reg .pred p, q;\n.reg .u32 n, v;\nmov.u32 n, 0;\nsetp.ne.u32 q, %2, 0;\n"
      "LW:\nld.acquire.gpu.global.u32 v, [%0];\nsetp.ge.u32 p, v, %1;\n@p bra LD;\n@q nanosleep.u32 200;\n"
      "add.u32 n, n, 1;\nsetp.lt.u32 p, n, 0x400000;\n@p bra LW;\ntrap;\nLD:\n}" ::"l"(p), "r"(target), "n"((int)SLEEP) : "memory");
}
template <int N>
__device__ __forceinline__ void poll_chunks(uint4 (&v)[N], const uint4* p, int stride) {
  uint32_t m[N];
#pragma unroll
  for (int i = 0; i < N; i++) { m[i] = ~0u; v[i] = make_uint4(0, 0, 0, 0); }
#pragma unroll 1
  for (int n = 0; n < 0x400000; n++) {
    uint32_t a = 0;
#pragma unroll
    for (int i = 0; i < N; i++)
      asm volatile("{\n.reg .pred p;\nsetp.eq.u32 p, %5, 0xFFFFFFFF;\n@p ld.relaxed.gpu.global.v4.u32 {%0,%1,%2,%3}, [%4];\n}"
                   : "+r"(v[i].x), "+r"(v[i].y), "+r"(v[i].z), "+r"(v[i].w) : "l"(p + i * stride), "r"(m[i]) : "memory");
#pragma unroll
    for (int i = 0; i < N; i++) { m[i] = max(max(v[i].x, v[i].y), max(v[i].z, v[i].w)); a = max(a, m[i]); }
    if (__all_sync(~0u, a != 0xFFFFFFFFu)) break;
  }
}
__device__ __forceinline__ void fence_async_all() { asm volatile("fence.proxy.async;" ::: "memory"); }
__device__ __forceinline__ void bar_sync(int id, int n) { asm volatile("bar.sync %0, %1;" ::"r"(id), "r"(n) : "memory"); }
__device__ __forceinline__ void bar_arrive(int id, int n) { asm volatile("bar.arrive %0, %1;" ::"r"(id), "r"(n) : "memory"); }
__device__ __forceinline__ void cluster_arrive() { asm volatile("barrier.cluster.arrive.relaxed.aligned;" ::: "memory"); }
__device__ __forceinline__ void cluster_wait() { asm volatile("barrier.cluster.wait.acquire.aligned;" ::: "memory"); }
__device__ __forceinline__ void fence_gpu() { asm volatile("fence.acq_rel.gpu;" ::: "memory"); }
__device__ __forceinline__ void red_add(unsigned* p, unsigned v) { asm volatile("red.relaxed.gpu.global.add.u32 [%0], %1;" ::"l"(p), "r"(v) : "memory"); }
__device__ __forceinline__ void prefetch_tm(const CUtensorMap* m) { asm volatile("prefetch.tensormap [%0];" ::"l"(m) : "memory"); }

constexpr uint64_t EV_N = 0x1000000000000000ull, EV_F = 0x12F0000000000000ull;
__device__ __forceinline__ void tma_ld2(uint32_t dst, const CUtensorMap* m, uint32_t bar, int c0, int c1, bool ef = false) {
  asm volatile("cp.async.bulk.tensor.2d.shared::cta.global.mbarrier::complete_tx::bytes.L2::cache_hint [%0], [%1, {%3,%4}], [%2], %5;" ::"r"(dst), "l"(m), "r"(bar), "r"(c0), "r"(c1), "l"(ef ? EV_F : EV_N) : "memory");
}
__device__ __forceinline__ void tma_ld3(uint32_t dst, const CUtensorMap* m, uint32_t bar, int c0, int c1, int c2, bool ef = false) {
  asm volatile("cp.async.bulk.tensor.3d.shared::cta.global.mbarrier::complete_tx::bytes.L2::cache_hint [%0], [%1, {%3,%4,%5}], [%2], %6;" ::"r"(dst), "l"(m), "r"(bar), "r"(c0), "r"(c1), "r"(c2), "l"(ef ? EV_F : EV_N) : "memory");
}
__device__ __forceinline__ void tma_ld3_mc(uint32_t dst, const CUtensorMap* m, uint32_t bar, int c0, int c1, int c2, uint16_t mask, bool ef = false) {
  asm volatile("cp.async.bulk.tensor.3d.shared::cluster.global.mbarrier::complete_tx::bytes.multicast::cluster.L2::cache_hint [%0], [%1, {%3,%4,%5}], [%2], %6, %7;" ::"r"(dst), "l"(m), "r"(bar), "r"(c0), "r"(c1), "r"(c2), "h"(mask), "l"(ef ? EV_F : EV_N) : "memory");
}
__device__ __forceinline__ void tma_pf3(const CUtensorMap* m, int c0, int c1, int c2) {
  asm volatile("cp.async.bulk.prefetch.tensor.3d.L2.global [%0, {%1,%2,%3}];" ::"l"(m), "r"(c0), "r"(c1), "r"(c2) : "memory");
}
__device__ __forceinline__ void l2_prefetch(const void* p, uint32_t bytes) { asm volatile("cp.async.bulk.prefetch.L2.global [%0], %1;" ::"l"(p), "r"(bytes) : "memory"); }

__device__ __forceinline__ void wg_fence() { asm volatile("wgmma.fence.sync.aligned;" ::: "memory"); }
__device__ __forceinline__ void wg_commit() { asm volatile("wgmma.commit_group.sync.aligned;" ::: "memory"); }
template <int N> __device__ __forceinline__ void wg_wait() { asm volatile("wgmma.wait_group.sync.aligned %0;" ::"n"(N) : "memory"); }
template <int N> __device__ __forceinline__ void reg_alloc() { asm volatile("setmaxnreg.inc.sync.aligned.u32 %0;" ::"n"(N)); }
template <int N> __device__ __forceinline__ void reg_dealloc() { asm volatile("setmaxnreg.dec.sync.aligned.u32 %0;" ::"n"(N)); }
template <int N> __device__ __forceinline__ void fence_regs(float* d) {
#pragma unroll
  for (int i = 0; i < N; i++) asm volatile("" : "+f"(d[i])::"memory");
}
template <int N> __device__ __forceinline__ void fence_regs(uint32_t* d) {
#pragma unroll
  for (int i = 0; i < N; i++) asm volatile("" : "+r"(d[i])::"memory");
}

__device__ __forceinline__ uint64_t mk_desc(uint32_t addr, uint32_t lbo, uint32_t sbo, uint32_t swz) {
  uint32_t lo = ((addr & 0x3FFFF) >> 4) | ((lbo >> 4) << 16);
  uint32_t hi = (sbo >> 4) | (swz << 30);
  return ((uint64_t)hi << 32) | lo;
}
__device__ __forceinline__ uint64_t desc_add(uint64_t d, uint32_t bytes) {
  uint32_t lo = (uint32_t)d + (bytes >> 4);
  return (d & 0xFFFFFFFF00000000ull) | lo;
}

#define R8(b) "+f"(d[b + 0]), "+f"(d[b + 1]), "+f"(d[b + 2]), "+f"(d[b + 3]), "+f"(d[b + 4]), "+f"(d[b + 5]), "+f"(d[b + 6]), "+f"(d[b + 7])
#define REGS32 "%0,%1,%2,%3,%4,%5,%6,%7,%8,%9,%10,%11,%12,%13,%14,%15,%16,%17,%18,%19,%20,%21,%22,%23,%24,%25,%26,%27,%28,%29,%30,%31"
#define REGS64 REGS32 ",%32,%33,%34,%35,%36,%37,%38,%39,%40,%41,%42,%43,%44,%45,%46,%47,%48,%49,%50,%51,%52,%53,%54,%55,%56,%57,%58,%59,%60,%61,%62,%63"
#define REGS128 REGS64 ",%64,%65,%66,%67,%68,%69,%70,%71,%72,%73,%74,%75,%76,%77,%78,%79,%80,%81,%82,%83,%84,%85,%86,%87,%88,%89,%90,%91,%92,%93,%94,%95," \
               "%96,%97,%98,%99,%100,%101,%102,%103,%104,%105,%106,%107,%108,%109,%110,%111,%112,%113,%114,%115,%116,%117,%118,%119,%120,%121,%122,%123,%124,%125,%126,%127"

template <int TB>
__device__ __forceinline__ void mma_n256_ss(float (&d)[128], uint64_t a, uint64_t b, int acc) {
  asm volatile("{\n.reg .pred p;\nsetp.ne.b32 p, %130, 0;\n"
               "wgmma.mma_async.sync.aligned.m64n256k16.f32.bf16.bf16 {" REGS128 "}, %128, %129, p, 1, 1, 0, %131;\n}\n"
               : R8(0), R8(8), R8(16), R8(24), R8(32), R8(40), R8(48), R8(56), R8(64), R8(72), R8(80), R8(88), R8(96), R8(104), R8(112), R8(120)
               : "l"(a), "l"(b), "r"(acc), "n"(TB));
}
template <int TB>
__device__ __forceinline__ void mma_n128_ss(float* d, uint64_t a, uint64_t b, int acc) {
  asm volatile("{\n.reg .pred p;\nsetp.ne.b32 p, %66, 0;\n"
               "wgmma.mma_async.sync.aligned.m64n128k16.f32.bf16.bf16 {" REGS64 "}, %64, %65, p, 1, 1, 0, %67;\n}\n"
               : R8(0), R8(8), R8(16), R8(24), R8(32), R8(40), R8(48), R8(56)
               : "l"(a), "l"(b), "r"(acc), "n"(TB));
}
template <int TB>
__device__ __forceinline__ void mma_n128_rs(float* d, const uint32_t* a, uint64_t b, int acc) {
  asm volatile("{\n.reg .pred p;\nsetp.ne.b32 p, %69, 0;\n"
               "wgmma.mma_async.sync.aligned.m64n128k16.f32.bf16.bf16 {" REGS64 "}, {%64,%65,%66,%67}, %68, p, 1, 1, %70;\n}\n"
               : R8(0), R8(8), R8(16), R8(24), R8(32), R8(40), R8(48), R8(56)
               : "r"(a[0]), "r"(a[1]), "r"(a[2]), "r"(a[3]), "l"(b), "r"(acc), "n"(TB));
}
__device__ __forceinline__ void mma_n64_rs(float* d, const uint32_t* a, uint64_t b, int acc) {
  asm volatile("{\n.reg .pred p;\nsetp.ne.b32 p, %37, 0;\n"
               "wgmma.mma_async.sync.aligned.m64n64k16.f32.bf16.bf16 {" REGS32 "}, {%32,%33,%34,%35}, %36, p, 1, 1, 0;\n}\n"
               : R8(0), R8(8), R8(16), R8(24)
               : "r"(a[0]), "r"(a[1]), "r"(a[2]), "r"(a[3]), "l"(b), "r"(acc));
}
#define W8(b) "=f"(d[b + 0]), "=f"(d[b + 1]), "=f"(d[b + 2]), "=f"(d[b + 3]), "=f"(d[b + 4]), "=f"(d[b + 5]), "=f"(d[b + 6]), "=f"(d[b + 7])
__device__ __forceinline__ void mma_n128_rs0(float* d, const uint32_t* a, uint64_t b) {
  asm volatile("wgmma.mma_async.sync.aligned.m64n128k16.f32.bf16.bf16 {" REGS64 "}, {%64,%65,%66,%67}, %68, 0, 1, 1, 0;\n"
               : W8(0), W8(8), W8(16), W8(24), W8(32), W8(40), W8(48), W8(56)
               : "r"(a[0]), "r"(a[1]), "r"(a[2]), "r"(a[3]), "l"(b));
}
__device__ __forceinline__ void mma_n64_rs0(float* d, const uint32_t* a, uint64_t b) {
  asm volatile("wgmma.mma_async.sync.aligned.m64n64k16.f32.bf16.bf16 {" REGS32 "}, {%32,%33,%34,%35}, %36, 0, 1, 1, 0;\n"
               : W8(0), W8(8), W8(16), W8(24)
               : "r"(a[0]), "r"(a[1]), "r"(a[2]), "r"(a[3]), "l"(b));
}
__device__ __forceinline__ uint32_t pack_bf16(float lo, float hi) {
  uint32_t r;
  asm("cvt.rn.bf16x2.f32 %0, %1, %2;" : "=r"(r) : "f"(hi), "f"(lo));
  return r;
}
__device__ __forceinline__ float bf_lo(uint32_t v) { return __uint_as_float(v << 16); }
__device__ __forceinline__ float bf_hi(uint32_t v) { return __uint_as_float(v & 0xFFFF0000u); }
__device__ __forceinline__ float bf_round(float v) { return bf_lo(pack_bf16(v, v)); }
__device__ __forceinline__ void stsm4(uint32_t addr, uint32_t r0, uint32_t r1, uint32_t r2, uint32_t r3) {
  asm volatile("stmatrix.sync.aligned.m8n8.x4.shared.b16 [%0], {%1,%2,%3,%4};" ::"r"(addr), "r"(r0), "r"(r1), "r"(r2), "r"(r3) : "memory");
}
__device__ __forceinline__ uint4 lds128(uint32_t addr) {
  uint4 v;
  asm volatile("ld.shared.v4.u32 {%0,%1,%2,%3}, [%4];" : "=r"(v.x), "=r"(v.y), "=r"(v.z), "=r"(v.w) : "r"(addr));
  return v;
}
__device__ __forceinline__ float ex2(float x) {
  float y;
  asm("ex2.approx.ftz.f32 %0, %1;" : "=f"(y) : "f"(x));
  return y;
}
__device__ __forceinline__ void pin_order(float v, uint32_t dummy) {
  asm volatile("{\n.reg .pred p;\nsetp.eq.b32 p, %0, 0xFFFFFFFF;\n@p st.shared.b32 [%1], %0;\n}" ::"r"(__float_as_uint(v)), "r"(dummy) : "memory");
}
__device__ __forceinline__ float sigmoid(float x) {
  float y;
  asm("rcp.approx.ftz.f32 %0, %1;" : "=f"(y) : "f"(1.f + ex2(x * -1.4426950408889634f)));
  return y;
}
__device__ __forceinline__ void sched_fence(uint32_t dummy) {
  asm volatile("{\n.reg .pred p;\n.reg .u32 c;\nsetp.eq.b32 p, %0, 0xFFFFFFFF;\nmov.u32 c, %%clock;\n@p st.shared.b32 [%0], c;\n}" ::"r"(dummy) : "memory");
}
__device__ __forceinline__ void idle(int n) {
  asm volatile("{\n.reg .pred p;\n.reg .u32 a, b;\nmov.u32 a, %%clock;\nLI:\nmov.u32 b, %%clock;\nsub.u32 b, b, a;\nsetp.lt.u32 p, b, %0;\n@p bra LI;\n}" ::"r"(n) : "memory");
}
__device__ __forceinline__ void stage_store_128(uint32_t base, int lane, const uint32_t* pk) {
  const int row = (lane & 7) + ((lane >> 3) & 1) * 8;
  const uint32_t rb = base + row * 128;
  const int hi = lane >> 4;
#pragma unroll
  for (int j = 0; j < 8; j++) {
    const int chunk = 2 * j + hi;
    const uint32_t a = rb + (j >> 2) * 8192 + (((chunk & 7) ^ (lane & 7)) << 4);
    stsm4(a, pk[4 * j + 0], pk[4 * j + 1], pk[4 * j + 2], pk[4 * j + 3]);
  }
}
__device__ __forceinline__ void ln_round(float mean, float var, float& m_bf, float& inv_s) {
  const uint32_t mv = pack_bf16(mean, var);
  m_bf = bf_lo(mv);
  float sq, rc;
  asm("sqrt.approx.ftz.f32 %0, %1;" : "=f"(sq) : "f"(bf_round(bf_hi(mv) + 1e-5f)));
  asm("rcp.approx.ftz.f32 %0, %1;" : "=f"(rc) : "f"(bf_round(sq)));
  inv_s = rc;
}
__device__ __forceinline__ uint32_t hadd2_bf(uint32_t a, uint32_t b) {
  uint32_t r;
  asm("add.rn.bf16x2 %0, %1, %2;" : "=r"(r) : "r"(a), "r"(b));
  return r;
}
__device__ __forceinline__ uint2 ln_split(float inv_s) {
  const uint32_t hi = pack_bf16(inv_s, inv_s);
  const float lo = inv_s - bf_lo(hi);
  return make_uint2(hi, pack_bf16(lo, lo));
}
__device__ __forceinline__ uint32_t ln_apply(uint32_t h, uint32_t nm2, uint2 inv) {
  uint32_t r;
  asm("{\n.reg .b32 d, t;\nadd.rn.bf16x2 d, %1, %2;\nmul.rn.bf16x2 t, d, %4;\nfma.rn.bf16x2 %0, d, %3, t;\n}" : "=r"(r) : "r"(h), "r"(nm2), "r"(inv.x), "r"(inv.y));
  return r;
}
__device__ __forceinline__ void ldsm4(uint32_t* r, uint32_t addr) {
  asm volatile("ldmatrix.sync.aligned.m8n8.x4.shared.b16 {%0,%1,%2,%3}, [%4];" : "=r"(r[0]), "=r"(r[1]), "=r"(r[2]), "=r"(r[3]) : "r"(addr) : "memory");
}
__device__ __forceinline__ void mma16816(float* d, uint32_t a0, uint32_t a1, uint32_t a2, uint32_t a3, uint32_t b0, uint32_t b1) {
  asm volatile("mma.sync.aligned.m16n8k16.row.col.f32.bf16.bf16.f32 {%0,%1,%2,%3}, {%4,%5,%6,%7}, {%8,%9}, {%0,%1,%2,%3};"
               : "+f"(d[0]), "+f"(d[1]), "+f"(d[2]), "+f"(d[3]) : "r"(a0), "r"(a1), "r"(a2), "r"(a3), "r"(b0), "r"(b1));
}

template <class F>
__device__ __forceinline__ void unroll8(F f) {
  f(std::integral_constant<int, 0>{}); f(std::integral_constant<int, 1>{}); f(std::integral_constant<int, 2>{}); f(std::integral_constant<int, 3>{});
  f(std::integral_constant<int, 4>{}); f(std::integral_constant<int, 5>{}); f(std::integral_constant<int, 6>{}); f(std::integral_constant<int, 7>{});
}

constexpr float AT_C = 0.08838834764831845f * 1.4426950408889634f;
constexpr float AT_LO = 0x1p-40f, AT_HI = 0x1p40f;
constexpr int AT_R1 = 48;
template <int I0, int I1>
__device__ __forceinline__ void at_exp(float* S) {
#pragma unroll
  for (int i = I0; i < I1; i++) asm volatile("ex2.approx.ftz.f32 %0, %0;" : "+f"(S[i]));
}
template <int I0, int I1>
__device__ __forceinline__ void at_fin(const float* S, uint32_t* P) {
#pragma unroll
  for (int i = I0; i < I1; i += 4) {
    P[i / 2] = pack_bf16(S[i], S[i + 1]); P[i / 2 + 1] = pack_bf16(S[i + 2], S[i + 3]);
  }
}
__device__ __forceinline__ void at_sum(const uint32_t* P, bool half, float& l0, float& l1) {
  uint32_t u[4];
#pragma unroll
  for (int r = 0; r < 4; r++) {
    const uint32_t* q = P + (r >> 1) * 16 + (r & 1);
    u[r] = hadd2_bf(hadd2_bf(hadd2_bf(q[0], q[2]), hadd2_bf(q[4], q[6])), hadd2_bf(hadd2_bf(q[8], q[10]), hadd2_bf(q[12], q[14])));
  }
  u[0] = hadd2_bf(u[0], half ? 0u : u[2]);
  u[1] = hadd2_bf(u[1], half ? 0u : u[3]);
  l0 += bf_lo(u[0]) + bf_hi(u[0]);
  l1 += bf_lo(u[1]) + bf_hi(u[1]);
}
template <int j>
__device__ __forceinline__ void at_mask1(float* S, int d) {
  float dummy0 = 0.f, dummy1 = 0.f;
  float& lo0 = j < 7 ? S[4 * (j < 7 ? j + 1 : j) + 2] : dummy0;
  float& lo1 = j < 7 ? S[4 * (j < 7 ? j + 1 : j) + 3] : dummy1;
  asm("{\n.reg .pred p, q;\nsetp.lt.s32 p, %4, %5;\nsetp.le.s32 q, %4, %5;\n"
      "@p add.f32 %0, %0, 0fFF800000;\n@q add.f32 %1, %1, 0fFF800000;\n@p add.f32 %2, %2, 0fFF800000;\n@q add.f32 %3, %3, 0fFF800000;\n}"
      : "+f"(S[4 * j]), "+f"(S[4 * j + 1]), "+f"(lo0), "+f"(lo1) : "r"(d), "r"(8 * j));
}
__device__ __forceinline__ void at_mask(float* S, int r, int lane) {
  unroll8([&](auto jc) { at_mask1<decltype(jc)::value>(S, r + (lane >> 2) - (lane & 3) * 2); });
}
__device__ __forceinline__ uint32_t ldg32(const __nv_bfloat16* p) { return __ldcg(reinterpret_cast<const uint32_t*>(p)); }
__device__ __forceinline__ uint32_t ldg16x2(const __nv_bfloat16* p, int stride) {
  return (uint32_t)__ldcg(reinterpret_cast<const unsigned short*>(p)) | ((uint32_t)__ldcg(reinterpret_cast<const unsigned short*>(p + stride)) << 16);
}
__device__ __forceinline__ void slow_tile(float* O, uint32_t* Q, float& l0, float& l1, const __nv_bfloat16* wq, int row0, int head, int lane, uint32_t dummy) {
  const int r = lane >> 2, q = lane & 3;
#pragma unroll
  for (int i = 0; i < 64; i++) O[i] = 0.f;
  {
    const __nv_bfloat16* xa = g_xn + (size_t)(row0 + r) * DM + 2 * q;
    const __nv_bfloat16* wb = wq + (size_t)(2 * q) * NQ + head * HD + (r >> 1) * 8 + (r & 1);
#pragma unroll 1
    for (int k = 0; k < DM; k += 16) {
      const uint32_t a0 = ldg32(xa + k), a1 = ldg32(xa + k + 8 * DM), a2 = ldg32(xa + k + 8), a3 = ldg32(xa + k + 8 * DM + 8);
#pragma unroll
      for (int j = 0; j < 16; j++) {
        const __nv_bfloat16* wp = wb + (size_t)k * NQ + (j >> 2) * 32 + (j & 3) * 2;
        mma16816(O + 4 * j, a0, a1, a2, a3, ldg16x2(wp, NQ), ldg16x2(wp + 8 * NQ, NQ));
        if (j == 7) sched_fence(dummy);
      }
    }
  }
#pragma unroll
  for (int i = 0; i < 32; i++) Q[i] = pack_bf16(O[2 * i], O[2 * i + 1]);
#pragma unroll
  for (int i = 0; i < 64; i++) O[i] = 0.f;
  float m0 = -INFINITY, m1 = -INFINITY;
  l0 = l1 = 0.f;
#pragma unroll 1
  for (int kv = 0; kv <= row0; kv += 16) {
    float s[8] = {0.f, 0.f, 0.f, 0.f, 0.f, 0.f, 0.f, 0.f};
    const __nv_bfloat16* kp = g_qkv + (size_t)(kv + r) * NQ + head * HD + 2 * q;
#pragma unroll
    for (int k = 0; k < 8; k++) {
      mma16816(s, Q[4 * k], Q[4 * k + 1], Q[4 * k + 2], Q[4 * k + 3], ldg32(kp + 16 * k), ldg32(kp + 16 * k + 8));
      mma16816(s + 4, Q[4 * k], Q[4 * k + 1], Q[4 * k + 2], Q[4 * k + 3], ldg32(kp + 8 * NQ + 16 * k), ldg32(kp + 8 * NQ + 16 * k + 8));
    }
#pragma unroll
    for (int i = 0; i < 8; i++)
      if (kv + (i >> 2) * 8 + 2 * q + (i & 1) > row0 + r + (i & 2) * 4) s[i] = -INFINITY;
    float a = fmaxf(fmaxf(fmaxf(s[0], s[1]), fmaxf(s[4], s[5])), m0), b = fmaxf(fmaxf(fmaxf(s[2], s[3]), fmaxf(s[6], s[7])), m1);
    a = fmaxf(a, __shfl_xor_sync(~0u, a, 1)); b = fmaxf(b, __shfl_xor_sync(~0u, b, 1));
    a = fmaxf(a, __shfl_xor_sync(~0u, a, 2)); b = fmaxf(b, __shfl_xor_sync(~0u, b, 2));
    const float c0 = ex2(m0 - a), c1 = ex2(m1 - b);
    m0 = a; m1 = b;
#pragma unroll
    for (int i = 0; i < 8; i++) s[i] = ex2(s[i] - ((i & 2) ? b : a));
    l0 = l0 * c0 + (s[0] + s[1]) + (s[4] + s[5]);
    l1 = l1 * c1 + (s[2] + s[3]) + (s[6] + s[7]);
    sched_fence(dummy);
    const uint32_t p0 = pack_bf16(s[0], s[1]), p1 = pack_bf16(s[2], s[3]), p2 = pack_bf16(s[4], s[5]), p3 = pack_bf16(s[6], s[7]);
    const __nv_bfloat16* vp = g_qkv + (size_t)(SEQ + kv + 2 * q) * NQ + head * HD + r;
#pragma unroll
    for (int j = 0; j < 16; j++) {
      O[4 * j] *= c0; O[4 * j + 1] *= c0; O[4 * j + 2] *= c1; O[4 * j + 3] *= c1;
      mma16816(O + 4 * j, p0, p1, p2, p3, ldg16x2(vp + 8 * j, NQ), ldg16x2(vp + 8 * NQ + 8 * j, NQ));
      if (j == 7) sched_fence(dummy);
    }
  }
}

constexpr int P1_STAGE = 49152;
constexpr int SLOT = 32768;
constexpr int OFF_R3 = 0;
constexpr int OFF_BAR = 229376;
constexpr int OFF_MISC = OFF_BAR + 8 * 58;
constexpr int SMEM_BYTES = OFF_MISC + 2080 + TL_BYTES;
enum : int {
  B_FULL1 = 0, B_KF = 4, B_VF = 6, B_FULL3 = 8, B_XF = 14, B_LN = 15, B_DEP = 16, B_OUT2 = 22, B_FIN = 23, B_SET2 = 25, B_QP = 26, B_WF2 = 29,
  B_WF = 30, B_WR = 31,
  B_XE = 33, B_PUB = 34, B_OUT = 40, B_OUT3 = 41,
  B_EMPTY1 = 42, B_KE = 46, B_VE = 48, B_EMPTY3 = 50, B_WE = 56, B_NUM = 57
};
constexpr int OFF_STG = SLOT, SL_SCR = 2;
constexpr int PRE = 3;
constexpr int LN_PF = 5, LN_PFN = 2, LN_LD = 4;
constexpr int WQ_0 = 18, WQ_D = 2;
constexpr int KV_PF = 11, W_G0 = 28;
constexpr int X_KB = 17, G_KB = 32;
constexpr int SL_NS = 600, SET_NS = 50;
constexpr int OUT_CLK = 500, Y_CLK = 400;
struct Params {
  CUtensorMap xn, ckv, wq, wk, wv, kv, ctx_ld, ctx_st, wo, x, wd, wg, wu, out;
};

__global__ void __cluster_dims__(2, 1, 1) __launch_bounds__(384, 1)
fused_kernel(const __nv_bfloat16* __restrict__ x, const __nv_bfloat16* __restrict__ wq, const __nv_bfloat16* __restrict__ w_r,
             __nv_bfloat16* __restrict__ out, const __grid_constant__ Params p) {
  extern __shared__ __align__(1024) uint8_t sp[];
  const uint32_t sb = s2u(sp);
  const uint32_t bar = sb + OFF_BAR;
  auto B = [&](int i) { return bar + 8 * i; };
  const int tid = threadIdx.x, warp = __shfl_sync(~0u, tid >> 5, 0), wg = warp >> 2, lane = tid & 31;
  const int cta = blockIdx.x, rank = cta & 1, cl = cta >> 1;
  const int mp = cl < 4 ? 1 : (cl < 36 ? (cl & 7) : (0x3207654 >> (4 * ((cl - 36) % 7))) & 7);
  const int gq = cl < 4 ? 4 + cl : (cl < 36 ? (cl - 4) >> 3 : 4 + (cl - 36) / 7);
  const int mt = 2 * mp + rank;
  const int ti = (gq & 3) * 2 + rank, hh = mp * 2 + (gq >> 2);
  const int rid = mt * 8 + gq;
  const int fid = mt * 7 + gq - 1;
  const bool ffn = gq > 0;
  uint4* const xr = g_xr + rid * XR_SIZE;
  TL_INIT();
  TL(0, 0, tid == 128);
  if (warp == 0) {
    if (elect_one()) {
#pragma unroll
      for (int kb = 0; kb < PRE; kb++) mbar_init(B(B_FULL1 + kb), 1);
      asm volatile("fence.mbarrier_init.release.cluster;" ::: "memory");
    }
    __syncwarp();
    cluster_arrive();
    if (elect_one()) {
#pragma unroll
      for (int kb = 0; kb < PRE; kb++) {
        mbar_expect(B(B_FULL1 + kb), P1_STAGE);
        tma_ld2(sb + kb * P1_STAGE, &p.ckv, B(B_FULL1 + kb), kb * 64, mt * 128);
        tma_ld3(sb + kb * P1_STAGE + 16384 + rank * 16384, &p.wk, B(B_FULL1 + kb), 0, kb * 64, (gq + 8) * 4 + rank * 2);
        tma_ld3(sb + kb * P1_STAGE + 32768 - rank * 16384, &p.wk, B(B_FULL1 + kb), 0, kb * 64, (gq + 8) * 4 + 2 - rank * 2);
      }
    }
  } else if (elect_one()) {
#pragma unroll 1
    for (int i = PRE + warp - 1; i < B_NUM; i += 11)
      mbar_init(B(i), i >= B_EMPTY1 ? 16 : (i >= B_XE ? 8 : (i >= B_WF ? 2 : 1)));
    asm volatile("fence.mbarrier_init.release.cluster;" ::: "memory");
  }
  __syncwarp();
  if (warp) cluster_arrive();
  if (wg == 0) {
    reg_dealloc<40>();
    if (warp == 1 && elect_one()) {
      if (mt >= 2 * PRE) tma_pf3(&p.wk, 0, mp * 64, (gq + 8) * 4 + rank * 2);
      if (gq >= PRE) asm volatile("cp.async.bulk.prefetch.tensor.2d.L2.global [%0, {%1,%2}];" ::"l"(&p.ckv), "r"(gq * 64), "r"(mt * 128) : "memory");
    } else if (warp == 2 && elect_one()) {
      prefetch_tm(&p.wv); prefetch_tm(&p.wq); prefetch_tm(&p.xn);
    }
    __syncwarp();
    cluster_wait();
    if (warp == 0) {
      int st = PRE; uint32_t ph = 1;
#pragma unroll 1
      for (int t = 0; t < 6; t++) {
        const CUtensorMap* ma = t >= 4 ? &p.xn : &p.ckv;
        const CUtensorMap* mb = t >= 4 ? &p.wq : ((t & 1) ? &p.wv : &p.wk);
        const int nk = t >= 4 ? 16 : 8;
        const int row = (t < 4 ? mt : (t == 4 ? 15 - ti : ti)) * 128;
        const int col = t < 4 ? (gq + ((t >> 1) ^ 1) * 8) * 4 + rank * 2 : (hh + rank * 16) * 2;
        if (t >= 4) mbar_wait(B(B_DEP + t - 4), 0);
#pragma unroll 1
        for (int kb = t ? 0 : PRE; kb < nk; kb++) {
          const uint32_t d = sb + st * P1_STAGE, fb = B(B_FULL1 + st);
          const int n = t * 8 + kb;
          const bool la = t == 0 || t >= 4 || (kb & 5) == 5, lb = t < 5 || kb >= 4;
          const int k0 = (t == 5 ? (kb + 12) & 15 : kb ^ ((t & kb & 1) * 4)) * 64;
          mbar_wait_c(B(B_EMPTY1 + st), ph);
          if (elect_one()) {
            mbar_expect(fb, la * 16384 + lb * 32768);
            if (la) tma_ld2(t == 0 && (kb & 5) == 4 ? sb + 6 * SLOT + (kb & 2) * 8192 : d, ma, fb, k0, row);
            if (lb) tma_ld3_mc(d + 16384 + rank * 16384, mb, fb, 0, k0, col, 3);
          }
          if (t < 5 && elect_one()) {
            if (n >= LN_PF && n < LN_PF + LN_PFN) l2_prefetch(x + (size_t)cta * 16 * DM + (n - LN_PF) * (16 * DM / LN_PFN), 32768 / LN_PFN);
            if (n == LN_LD) mbar_arrive(B(B_LN));
            if (t < 3 && kb == (t ? 0 : 4)) tma_pf3((t & 1) ? &p.wk : &p.wv, 0, mp * 64, (gq + (((t + 1) >> 1) ^ 1) * 8) * 4 + rank * 2);
            if (n >= WQ_0 && n < WQ_0 + 4 * WQ_D && (n - WQ_0) % WQ_D == 0) tma_pf3(&p.wq, 0, ((n - WQ_0) / WQ_D * 4 + (gq & 3)) * 64, (hh + rank * 16) * 2);
          }
          if (++st == 4) { st = 0; ph ^= 1; }
        }
      }
      if (elect_one()) { prefetch_tm(&p.kv); prefetch_tm(&p.ctx_ld); prefetch_tm(&p.wo); prefetch_tm(&p.wg); prefetch_tm(&p.wu); }
      int seq0, seq1;
      {
        const int G = ti & 6, own = rank ? G + 33 : 31 - G, j = 18 - lane;
        seq0 = lane < 13 - G ? (lane < G ? lane : lane + 2) : (lane <= 14 - G ? 14 - lane : (lane == 15 - G ? own : (lane == 16 - G ? G + 32 : 16 - lane)));
        seq1 = lane <= G + 1 ? lane : (lane == G + 2 ? G + 32 : (lane == G + 3 ? own : (j > G + 1 ? j : j - 2)));
      }
      auto load_kv = [&](int g, int isv) {
        const int h2 = g >= 17, sx = g - 17 * h2, b = __shfl_sync(~0u, h2 ? seq1 : seq0, sx);
        const int row = isv * SEQ + (b & 15) * 128, col = (hh + 16 * h2) * 2;
        const uint32_t d = sb + (isv ? 2 + 2 * (g & 1) : (g & 1)) * SLOT, fb = B(B_KF + 2 * isv + (g & 1));
        const bool ef = ((b & 8) || sx >= 11) && (h2 || !isv);
        const int n3 = g - KV_PF;
        const int pb = ti >= 6 && n3 >= 0 && n3 < 16 ? (n3 < 4 ? n3 : (n3 >= 12 ? 23 - n3 : ((n3 & 1) ? (n3 + 3) >> 1 : 17 - (n3 >> 1)))) : -1;
        mbar_wait_c(g < 2 ? B(B_EMPTY1 + (isv ? 1 + 2 * g : g)) : B(B_KE + 2 * isv + (g & 1)), g < 2 ? 1 : ((g >> 1) & 1) ^ 1);
        if (elect_one()) {
          mbar_expect(fb, b < 32 ? SLOT : 0);
          if (b < 16) {
            tma_ld3_mc(d + rank * 16384, &p.kv, fb, 0, row, col + rank, 3, ef);
          } else if (b < 32) {
            tma_ld3(d, &p.kv, fb, 0, row, col, ef);
            tma_ld3(d + 16384, &p.kv, fb, 0, row, col + 1, ef);
          }
          if (pb >= 0) tma_pf3(&p.kv, 0, isv * SEQ + pb * 128, (hh + 16) * 2 + rank);
        }
      };
      int nw = ffn ? 0 : 12;
      auto load_w = [&]() {
        const int c = nw < 8 ? (nw >> 2) + (nw & 2) : nw >> 1;
        if (elect_one()) {
          if (!(nw & 3)) mbar_expect(B(B_WF - (nw >> 3)), 32768);
          tma_ld2(sb + (c < 2 ? 3 : 4) * SLOT + c * 16384 + (nw & 1) * 8192, (nw & 1) ? &p.wg : &p.wu, B(B_WF - (nw >> 3)), fid * 32, c * 128, true);
        }
        nw++;
      };
#pragma unroll 1
      for (int g = 0; g < 34; g++) {
        if (g == 0 || g == KV_PF) mbar_wait(B(B_DEP + 2 + (g > 0)), 0);
        auto try_w = [&]() { if (g >= W_G0 && nw < 12 && __all_sync(~0u, mbar_test(B(B_QP + (nw >> 2)), 0))) load_w(); };
        load_kv(g, 0);
        try_w();
        if (g > 0) load_kv(g - 1, 1);
        try_w();
      }
      load_kv(33, 1);
#pragma unroll 1
      while (nw < 12) { mbar_wait(B(B_QP + (nw >> 2)), 0); load_w(); }
      if (elect_one()) { prefetch_tm(&p.wd); prefetch_tm(&p.x); prefetch_tm(&p.out); }
      auto load3 = [&](int kb, int sl) {
        if (elect_one()) {
          mbar_expect(B(B_FULL3 + sl), SLOT);
          tma_ld2(sb + OFF_R3 + sl * SLOT, &p.ctx_ld, B(B_FULL3 + sl), (kb & 31) * 64, (kb < 32 ? SEQ : 0) + mt * 128, true);
          tma_ld3_mc(sb + OFF_R3 + sl * SLOT + 16384 + rank * 8192, &p.wo, B(B_FULL3 + sl), 0, kb * 64, gq * 2 + rank, 3);
        }
      };
      mbar_wait(B(B_DEP + 4), 0);
#pragma unroll
      for (int kb = 0; kb < 5; kb++) {
        mbar_wait_c(B(kb == 3 ? B_WE : (kb == 4 ? B_VE + 1 : B_KE + kb)), 0);
        load3(kb, kb);
      }
      if (elect_one()) mbar_arrive(B(B_FULL3 + 5));
#pragma unroll 1
      for (int r = 1; r < 11; r++) {
#pragma unroll
        for (int j = 0; j < 6; j++) {
          if (j == 5 && r == 10) break;
          if (j == 3 && r == 5) mbar_wait(B(B_DEP + 5), 0);
          mbar_wait_c(B(B_EMPTY3 + j), ~r & 1);
          load3(r * 6 + j - 1, j);
          if (j == 5 && r == 9 && elect_one()) l2_prefetch(xr, XR_CAND * 16);
        }
      }
      if (ffn) {
#pragma unroll
        for (int j = 1; j >= 0; j--) {
          mbar_wait(B(B_EMPTY3 + 5 * j), j);
          if (elect_one()) {
            mbar_expect(B(B_FULL3 + 5 * j), SLOT);
            tma_ld3(sb + OFF_R3 + 5 * j * SLOT, &p.wd, B(B_FULL3 + 5 * j), 0, fid * 32, 8 * j, true);
          }
        }
      }
    } else {
      if (warp >= 2) {
#pragma unroll 1
        for (int i = tid - 64; i < XR_CAND; i += 64) xr[i] = make_uint4(~0u, ~0u, ~0u, ~0u);
        if (warp == 2) { __syncwarp(); if (lane == 0) mbar_arrive(B(B_WR)); }
      }
      if (warp == 3) {
        float ws = 0.f;
#pragma unroll
        for (int j = 0; j < 4; j++) {
          const uint4 q = __ldg(reinterpret_cast<const uint4*>(w_r) + j * 32 + lane);
          ws += bf_lo(q.x) + bf_hi(q.x) + bf_lo(q.y) + bf_hi(q.y) + bf_lo(q.z) + bf_hi(q.z) + bf_lo(q.w) + bf_hi(q.w);
        }
#pragma unroll
        for (int o = 16; o; o >>= 1) ws += __shfl_xor_sync(~0u, ws, o);
        uint2* tab = reinterpret_cast<uint2*>(sp + OFF_MISC + 512);
        tab[lane] = make_uint2(0x3F803F80u, 0x3F803F80u);
        tab[32 + lane] = __ldg(reinterpret_cast<const uint2*>(w_r + gq * 128) + lane);
        if (lane == 0) *reinterpret_cast<float*>(sp + OFF_MISC + 1024) = ws;
        __syncwarp();
        if (lane == 0) mbar_arrive(B(B_WR));
      }
      if (tid == 32) TS(0);
      mbar_wait(B(B_LN), 0);
      const uint4* src = reinterpret_cast<const uint4*>(x + (size_t)(cta * 16 + warp - 1) * DM) + lane;
      uint4* dst = reinterpret_cast<uint4*>(g_xn + (size_t)(cta * 16 + warp - 1) * DM) + lane;
      uint4 v[4];
#pragma unroll
      for (int j = 0; j < 4; j++) v[j] = __ldcs(src + j * 32);
#pragma unroll 1
      for (int r = warp - 1; r < 16; r += 3) {
        float a0 = 0.f, a1 = 0.f, b0 = 0.f, b1 = 0.f;
#pragma unroll
        for (int j = 0; j < 4; j++) {
          const uint32_t u[4] = {v[j].x, v[j].y, v[j].z, v[j].w};
#pragma unroll
          for (int i = 0; i < 4; i++) { const float a = bf_lo(u[i]), b = bf_hi(u[i]); a0 += a; a1 += b; b0 = fmaf(a, a, b0); b1 = fmaf(b, b, b1); }
        }
        a0 += a1; b0 += b1;
#pragma unroll
        for (int o = 16; o; o >>= 1) { a0 += __shfl_xor_sync(~0u, a0, o); b0 += __shfl_xor_sync(~0u, b0, o); }
        const float mean = a0 * (1.f / DM);
        float mb, inv;
        ln_round(mean, fmaxf(fmaf(b0, 1.f / DM, -mean * mean), 0.f), mb, inv);
        const uint2 iv = ln_split(inv * AT_C);
        const uint32_t nm2 = pack_bf16(-mb, -mb);
        src += 384;
#pragma unroll
        for (int j = 0; j < 4; j++) {
          dst[j * 32] = make_uint4(ln_apply(v[j].x, nm2, iv), ln_apply(v[j].y, nm2, iv), ln_apply(v[j].z, nm2, iv), ln_apply(v[j].w, nm2, iv));
          sched_fence(sb + lane);
          if (r < 13) v[j] = __ldcs(src + j * 32);
        }
        dst += 384;
      }
      __syncwarp();
      if (lane == 0) {
        fence_gpu();
        red_add(&g_cnt[C_LN + (cta >> 3)], 1);
      }
      TL(3, warp, lane == 0);
      __syncwarp();
      if (warp == 3) {
        if (lane == 0) {
#pragma unroll 1
          for (int i = 0; i < 6; i++) {
            const int c = i < 2 ? C_LN + (i ? ti : 15 - ti) : (i < 4 ? C_QKV + (i - 2) * 8 + mp : C_CTX + (i - 4) * 16 + mt);
            spin_until_ge<true>(&g_cnt[c], i < 2 ? 24 : 16);
            fence_async_all();
            mbar_arrive(B(B_DEP + i));
            TL(3, 4 + i, true);
          }
        }
      } else if (warp == 1 && elect_one()) {
        mbar_wait(B(B_WR), 0);
#pragma unroll 1
        for (int i = 0; i < 6; i++) {
          const int c = i < 2 ? C_QKV + gq + (i ^ 1) * 8 : C_CTX + (i >> 2) * 16 + ((i == 3 || i == 4) ? ti : 15 - ti);
          mbar_wait(B(B_PUB + i), 0);
          if (i == 2) {
            mbar_wait(B(B_PUB + 3), 0);
            fence_gpu();
            red_add(&g_cnt[C_HD + hh], 1);
            spin_until_ge<true>(&g_cnt[C_HD + hh], 8);
          }
          if (i >= 2 && i < 5) {
            asm volatile("fence.proxy.async.shared::cta;" ::: "memory");
#pragma unroll 1
            for (int n = 0; n < 8; n++) {
              const int h = n >> 2, a = n & 3;
              asm volatile("cp.async.bulk.tensor.3d.global.shared::cta.bulk_group [%0, {%2,%3,%4}], [%1];" ::"l"(&p.ctx_st),
                           "r"(sb + (i == 4 ? 6 * SLOT + h * 16384 : (3 + 2 * h) * SLOT + (i - 2) * 16384) + a * 4096),
                           "r"(0), "r"((i < 4 ? SEQ : 0) + (i == 2 ? 15 - ti : ti) * 128 + h * 64), "r"(hh * 4 + a) : "memory");
              asm volatile("cp.async.bulk.commit_group;\ncp.async.bulk.wait_group.read 0;" ::: "memory");
            }
            mbar_arrive(B(B_QP + i - 2));
            asm volatile("cp.async.bulk.wait_group 0;" ::: "memory");
          }
          fence_gpu();
          red_add(&g_cnt[c], 1);
          TS(1 + i);
        }
      }
      if (warp == 2) {
#pragma unroll 1
        for (int n = 0; n < 8; n++) {
          if (!(n & 3)) mbar_wait(B(B_XE), n >> 2);
          if ((n < 4 || ffn) && elect_one()) {
            const uint32_t fb = B(n < 4 ? B_XF : B_WF2), d = sb + 6 * SLOT + (n & 3) * 8192;
            if (!(n & 3)) mbar_expect(fb, 32768);
            if (n < 4) tma_ld3(d, &p.x, fb, 0, mt * 128 + (n >> 1) * 64, gq * 2 + (n & 1), true);
            else tma_ld2(d, (n & 1) ? &p.wg : &p.wu, fb, fid * 32, (4 + (n >> 1)) * 128, true);
          }
          __nanosleep(SL_NS);
        }
#pragma unroll 1
        for (int i = XR_CAND + lane; i < XR_SIZE; i += 32) { xr[i] = make_uint4(~0u, ~0u, ~0u, ~0u); __nanosleep(SET_NS); }
        __syncwarp();
        if (lane == 0) { fence_gpu(); mbar_arrive(B(B_SET2)); }
        TL(2, 26, lane == 0);
        __syncwarp();
      }
      __syncwarp();
      cluster_arrive();
      if (warp == 3) {
        mbar_wait(B(B_OUT), 0);
        uint4 kv[2];
        poll_chunks(kv, g_xr + ((lane >> 1) * 8 + gq) * XR_SIZE + XR_KEY + (lane & 1) * 2, 1);
        const uint32_t a1 = max(kv[0].x, kv[0].z), a2 = max(min(kv[0].x, kv[0].z), max(kv[0].y, kv[0].w));
        const uint32_t b1 = max(kv[1].x, kv[1].z), b2 = max(min(kv[1].x, kv[1].z), max(kv[1].y, kv[1].w));
        const uint32_t k1 = max(a1, b1), k2 = max(min(a1, b1), max(a2, b2));
        const uint32_t m1 = __reduce_max_sync(~0u, k1);
        const uint32_t m2 = __reduce_max_sync(~0u, k1 == m1 ? k2 : k1);
        auto cand = [&](uint32_t k) { return (((~k >> 7) & 15) * (8 * XR_SIZE) + ((~k >> 4) & 7) * 64) * 16; };
        const uint32_t o1 = cand(m1), o2 = cand(m2) + (((m1 ^ m2) & 0x7FF0) ? 0 : 256);
        if (lane == 0) {
          *reinterpret_cast<uint4*>(sp + OFF_MISC) = make_uint4(m1, m2, o1, o2);
          mbar_arrive(B(B_OUT2));
        }
        const uint32_t key = (lane & 4) ? m2 : m1;
        const uint4* src = g_xr + (((~key >> 7) & 15) * 8 + (rid >> 4)) * XR_SIZE;
        poll_chunks(kv, g_xr + (((lane & 4) ? o2 : o1) >> 4) + (rid >> 4) * XR_SIZE + XR_CAND + (rid & 12) + (lane & 3), 32);
        uint32_t u = key >> 16;
        u = (u & 0x8000u) ? (u & 0x7FFFu) : (~u & 0xFFFFu);
        const float rs = bf_round(sigmoid(__uint_as_float(u << 16)));
        if (lane < 8)
          *reinterpret_cast<uint4*>(sp + OFF_MISC + 128 + lane * 16) = make_uint4((rid & 2) ? ((rid & 1) ? kv[0].w : kv[0].z) : ((rid & 1) ? kv[0].y : kv[0].x),
              (rid & 2) ? ((rid & 1) ? kv[1].w : kv[1].z) : ((rid & 1) ? kv[1].y : kv[1].x), __float_as_uint(rs), 0);
#pragma unroll 1
        for (int n = 0; n < 0x400000; n++) {
          uint32_t v;
          asm volatile("ld.acquire.gpu.global.u32 %0, [%1];" : "=r"(v) : "l"(src + XR_FLAG) : "memory");
          if (__all_sync(~0u, v == 0)) break;
        }
        __syncwarp();
        if (lane == 0) mbar_arrive(B(B_FIN));
      }
      if (warp == 1 && elect_one()) {
        mbar_wait(B(B_OUT3), 0);
        asm volatile("fence.proxy.async.shared::cta;" ::: "memory");
        auto owner = [&]() {
          uint2 top;
          asm volatile("ld.shared.v2.u32 {%0,%1}, [%2];" : "=r"(top.x), "=r"(top.y) : "r"(sb + OFF_MISC) : "memory");
          return (0x7FFF - (top.x & 0x7FFF)) >> 7 == mt || (0x7FFF - (top.y & 0x7FFF)) >> 7 == mt;
        };
#pragma unroll 1
        for (int n = 0; n < 4; n++) {
          if (n && !(mbar_test(B(B_OUT2), 0) && owner())) idle(OUT_CLK);
          asm volatile("cp.async.bulk.tensor.2d.global.shared::cta.bulk_group [%0, {%2,%3}], [%1];" ::"l"(&p.out), "r"(sb + OFF_STG + n * 8192),
                       "r"(gq * 128 + (n & 1) * 64), "r"(mt * 128 + (n >> 1) * 64) : "memory");
        }
        asm volatile("cp.async.bulk.commit_group;" ::: "memory");
        mbar_wait(B(B_OUT2), 0);
        if (owner()) {
          asm volatile("cp.async.bulk.wait_group 0;" ::: "memory");
          asm volatile("st.release.gpu.global.u32 [%0], 0;" ::"l"(xr + XR_FLAG) : "memory");
        } else {
          asm volatile("cp.async.bulk.wait_group.read 0;" ::: "memory");
        }
        TL(2, 25, true);
      }
    }
    __syncwarp();
    if (warp == 0) cluster_arrive();
    cluster_wait();
    TL_DUMP();
    if (tid == 32) TS(8);
  } else {
    reg_alloc<232>();
    cluster_wait();
    const int w = wg - 1, cw = warp - 4;
    int lane = lane_id();
    const uint32_t stg = sb + OFF_STG + w * 16384 + (cw & 3) * 2048;
    auto publish = [&](int i) { __syncwarp(); if (lane == 0) mbar_arrive(B(B_PUB + i)); };
    uint32_t rbar;
    asm("mapa.shared::cluster.u32 %0, %1, %2;" : "=r"(rbar) : "r"(bar), "r"(lane & 1));
    auto release2 = [&](int i) { if (lane < 2) asm volatile("mbarrier.arrive.shared::cluster.b64 _, [%0];" ::"r"(rbar + 8 * i) : "memory"); };
    float R[128];
    float O[64], acc[64];
    uint32_t pk[64];
    uint32_t* const Q = pk;
    uint32_t P[32];
    auto packed = [&](int i) {
      const float* v = R + 16 * (i >> 1) + 2 * (i & 1);
      return make_uint4(pack_bf16(v[0], v[1]), pack_bf16(v[4], v[5]), pack_bf16(v[8], v[9]), pack_bf16(v[12], v[13]));
    };
    const uint32_t q_st = sb + (cw & 3) * 1024 + (lane >> 2) * 64 + (((lane & 3) ^ (lane >> 3)) << 4);
    const uint32_t q_ld = sb + (cw & 3) * 1024 + (lane & 15) * 64 + (((lane >> 4) ^ ((lane >> 1) & 3)) << 4);
    auto park = [&](uint32_t off, int i, uint4 v) {
      asm volatile("st.shared.v4.u32 [%0], {%1,%2,%3,%4};" ::"r"(q_st + off + (i >> 1) * 4096 + (i & 1) * 512), "r"(v.x), "r"(v.y), "r"(v.z), "r"(v.w) : "memory");
    };
    auto load_q = [&](uint32_t off, int k) { ldsm4(Q + 4 * k, ((q_ld + off) ^ ((k & 1) << 5)) + (k >> 1) * 4096); };
    {
      TL(0, 1, tid == 128);
      __nv_bfloat16* pdst = g_qkv;
      auto put2 = [&](int j) {
#pragma unroll
        for (int i = (j >> 1) * 4 + (j & 1); i < (j >> 1) * 4 + 4; i += 2)
          __stcs(reinterpret_cast<uint4*>(pdst + (i & 1) * 8 * NQ + (i >> 1) * 32), make_uint4(pk[4 * i], pk[4 * i + 1], pk[4 * i + 2], pk[4 * i + 3]));
      };
      const uint64_t da0 = mk_desc(sb + w * 8192, 16, 1024, 1);
      const uint64_t db0 = mk_desc(sb + 16384, 8192, 1024, 1);
      int st = 0; uint32_t ph = 0;
      auto issue = [&](int accum, auto between, bool res = false) {
        mbar_wait_c(B(B_FULL1 + st), ph);
        const uint64_t da = desc_add(da0, res ? 6 * SLOT + st * 8192 : st * P1_STAGE), db = desc_add(db0, st * P1_STAGE);
        between();
        wg_fence();
#pragma unroll
        for (int k = 0; k < 4; k++) mma_n256_ss<1>(R, desc_add(da, k * 32), desc_add(db, k * 2048), k == 0 ? accum : 1);
        wg_commit();
      };
      issue(0, []() {});
#pragma unroll 1
      for (int t = 0;; t++) {
        const int nk = t >= 4 ? 16 : 8;
        const bool tr = t > 0 && t < 5;
        TL(0, 2 + 2 * t + 16 * w, (tid & 127) == 0);
        int prev = st;
        if (++st == 4) { st = 0; ph ^= 1; }
#pragma unroll 1
        for (int kb = 1; kb < nk; kb++) {
          if (kb == nk - 1 && w == 1) bar_sync(5, 256);
          issue(1, []() {}, t < 4 && (kb & 5) == 4);
          if (kb == nk - 1 && w == 0) bar_arrive(5, 256);
          if (tr) {
#pragma unroll
            for (int i = 1; i < 8; i++) if (kb == (i << (t >> 2))) put2(i);
            if (kb == (7 << (t >> 2)) && !(t & 1)) publish((t >> 1) - 1);
          } else if (t == 5) {
            if (kb == 2) {
#pragma unroll
              for (int i = 0; i < 8; i++) park(6 * SLOT + w * 16384, i, make_uint4(pk[4 * i], pk[4 * i + 1], pk[4 * i + 2], pk[4 * i + 3]));
              __syncwarp();
            }
            if (kb == 4) {
#pragma unroll
              for (int k = 0; k < 8; k++) load_q(6 * SLOT + w * 16384, k);
              __syncwarp();
            }
            if (kb == 6) {
#pragma unroll
              for (int i = 0; i < 8; i++) park(6 * SLOT + w * 16384, i, make_uint4(pk[32 + 4 * i], pk[33 + 4 * i], pk[34 + 4 * i], pk[35 + 4 * i]));
            }
          }
          wg_wait<1>();
          release2(B_EMPTY1 + prev);
          prev = st;
          if (++st == 4) { st = 0; ph ^= 1; }
        }
        if (t == 5) break;
        issue(0, [&]() {
          sched_fence(q_st);
          wg_wait<0>();
          fence_regs<128>(R);
          TL(0, 3 + 2 * t + 16 * w, (tid & 127) == 0);
#pragma unroll
          for (int i = 0; i < 16; i++) { const uint4 v = packed(i); pk[4 * i] = v.x; pk[4 * i + 1] = v.y; pk[4 * i + 2] = v.z; pk[4 * i + 3] = v.w; }
          release2(B_EMPTY1 + prev);
          fence_regs<128>(R);
        });
        if (w == 1) bar_arrive(4, 256);
        sched_fence(q_st);
        pdst = g_qkv + (size_t)((t & 1) * SEQ + mt * 128 + cw * 16 + (lane >> 2)) * NQ + (gq + ((t >> 1) ^ 1) * 8) * 256 + (lane & 3) * 8;
        if (t < 4) put2(0);
        if (w == 0) bar_sync(4, 256);
      }
      if (w == 1) bar_arrive(6, 256);
      mbar_wait_c(B(B_KF), 0);
      sched_fence(q_st);
      wg_wait<0>();
      fence_regs<128>(R);
      release2(B_EMPTY1 + 3);
      TL(0, 13 + 16 * w, (tid & 127) == 0);
    }
    auto issue3 = [&](int st, uint32_t ph, int accum) {
      mbar_wait_c(B(B_FULL3 + st), ph);
      const uint64_t da = mk_desc(sb + OFF_R3 + w * 8192 + st * SLOT, 16, 1024, 1), db = mk_desc(sb + OFF_R3 + 16384 + st * SLOT, 8192, 1024, 1);
      wg_fence();
#pragma unroll
      for (int k = 0; k < 4; k++) mma_n128_ss<1>(acc, desc_add(da, k * 32), desc_add(db, k * 2048), k == 0 ? accum : 1);
      wg_commit();
    };
    uint32_t wf[128];
    auto w_addr = [&](uint32_t off, int m) {
      const uint32_t w_ld = sb + ((lane >> 3) & 1) * 8192 + ((cw >> 1) * 32 + (lane & 7) + (lane >> 4) * 8) * 64 + ((((cw & 1) * 2) ^ ((lane >> 1) & 3)) << 4);
      return ((w_ld + off) ^ ((m & 1) << 4)) + (m >> 2) * 16384 + ((m >> 1) & 1) * 1024;
    };
    auto grab = [&](uint32_t* d, uint32_t off, int m0, int m1) {
#pragma unroll
      for (int m = m0; m < m1; m++)
        asm volatile("ldmatrix.sync.aligned.m8n8.x4.trans.shared.b16 {%0,%1,%2,%3}, [%4];"
                     : "=r"(d[4 * m]), "=r"(d[4 * m + 1]), "=r"(d[4 * m + 2]), "=r"(d[4 * m + 3]) : "r"(w_addr(off, m)) : "memory");
    };
    float inv[2] = {0.f, 0.f};
    auto scaled = [&](int i) {
      const float* o = O + 16 * (i >> 1) + 2 * (i & 1);
      const float c = inv[i & 1];
      return make_uint4(pack_bf16(o[0] * c, o[1] * c), pack_bf16(o[4] * c, o[5] * c), pack_bf16(o[8] * c, o[9] * c), pack_bf16(o[12] * c, o[13] * c));
    };
    {
      const int wrow = cw * 16;
      const uint64_t dk0 = mk_desc(sb, 16, 1024, 1);
      const uint64_t dv0 = mk_desc(sb + 2 * SLOT, 16384, 1024, 1);
      const uint32_t pin = sb + OFF_MISC + 1028;
      float l0 = 0.f, l1 = 0.f;
      int g = 0, t = 0;
      uint32_t fail = 0;
      auto piece = [&](int tt) { return (uint32_t)(tt == 3 ? 6 * SLOT + w * 16384 : (3 + 2 * w) * SLOT + (tt - 1) * 16384); };
      uint32_t par = 0;
      auto issue_s = [&](float* S) {
        const uint64_t dk = desc_add(dk0, par * 16);
        mma_n128_rs0(S, Q, dk);
#pragma unroll
        for (int k = 1; k < 8; k++) mma_n128_rs<0>(S, Q + 4 * k, desc_add(dk, (k >> 2) * 16384 + (k & 3) * 32), 1);
        wg_commit();
      };
      auto issue_pv = [&](bool half, int accum) {
        const uint64_t dv = desc_add(dv0, ((g - 1) & 1) * 2 * SLOT);
        wg_fence();
#pragma unroll
        for (int k = 0; k < 4; k++) mma_n128_rs<1>(O, P + 4 * k, desc_add(dv, k * 2048), k == 0 ? accum : 1);
        wg_commit();
        if (UNLIKELY(half)) {
          wg_fence();
          wg_commit();
        } else {
          wg_fence();
#pragma unroll
          for (int k = 4; k < 8; k++) mma_n128_rs<1>(O, P + 4 * k, desc_add(dv, k * 2048), 1);
          wg_commit();
        }
        bar_arrive(2 - w, 256);
        wg_wait<2>();
        fence_regs<32>(Q);
      };
      auto release_k = [&]() { release2(B_KE); rbar ^= 8; };
      auto pv_done = [&]() {
        TC(g, 3);
        sched_fence(q_st);
        wg_wait<0>();
        fence_regs<64>(O); fence_regs<32>(P);
        TC(g, 4);
        release2(B_VE);
      };
      auto row_inv = [&](bool go) {
        float a = l0 + __shfl_xor_sync(~0u, l0, 1), b = l1 + __shfl_xor_sync(~0u, l1, 1);
        a += __shfl_xor_sync(~0u, a, 2); b += __shfl_xor_sync(~0u, b, 2);
        const bool ok = __all_sync(~0u, a >= AT_LO && a <= AT_HI && b >= AT_LO && b <= AT_HI) != 0;
        asm("rcp.approx.ftz.f32 %0, %1;" : "=f"(inv[0]) : "f"(a));
        asm("rcp.approx.ftz.f32 %0, %1;" : "=f"(inv[1]) : "f"(b));
        fail |= (uint32_t)(go && !ok) << t;
        l0 = go ? 0.f : l0; l1 = go ? 0.f : l1;
        t += go;
      };
      const uint64_t m_first = 1ull | (1ull << (16 - ti)) | (1ull << 17) | (1ull << (18 + ti));
      const uint64_t m_diag = (1ull << (15 - ti - 2 * rank)) | (1ull << (16 - ti)) | (9ull << (17 + ti));
      enum { F_FIRST = 1, F_DIAG = 2, F_LAST = 4, F_PFIRST = 8, F_PHALF = 16, F_STOP = 32 };
      auto kind = [&](int gn) {
        const uint32_t a = (uint32_t)((m_first << 1) >> gn), d = (uint32_t)((m_diag << 1) >> gn);
        return ((a >> 1) & 1) * F_FIRST | ((d >> 1) & 1) * F_DIAG | ((a >> 2) & 1) * F_LAST | (a & 1) * F_PFIRST |
               (w == 0 ? (d & 1) * F_PHALF | ((d >> 1) & 1) * F_STOP : 0) | (gn == 34 ? F_STOP : 0);
      };
      uint32_t kinds;
      {
        uint32_t qt[64];
#pragma unroll
        for (int i = 0; i < 16; i++) { const uint4 v = packed(i); qt[4 * i] = v.x; qt[4 * i + 1] = v.y; qt[4 * i + 2] = v.z; qt[4 * i + 3] = v.w; }
        fence_regs<64>(qt);
        sched_fence(q_st);
        float S[64];
        wg_fence();
        issue_s(S);
        bar_arrive(w ? 1 : 7, 256);
        bar_sync(6 + w, 256);
        sched_fence(q_st);
        TL(1, 0, tid == 128);
#pragma unroll
        for (int i = 0; i < 16; i++) park(piece(1), i, make_uint4(qt[4 * i], qt[4 * i + 1], qt[4 * i + 2], qt[4 * i + 3]));
        kinds = pinned(kind(lane + 3));
        sched_fence(q_st);
        wg_wait<0>();
        fence_regs<64>(S);
        release_k();
        TL(1, 1, tid == 128);
        const bool kok = mbar_try(B(B_KF + 1), 0);
        at_exp<0, 32>(S);
        sched_fence(q_st);
        at_exp<32, 64>(S); at_fin<0, 64>(S, P);
        if (UNLIKELY(!kok)) mbar_wait_c(B(B_KF + 1), 0);
        TL(1, 2, tid == 128);
      }
      uint32_t f = F_PFIRST, fn;
      auto shadow = [&]() {
        const bool vok = mbar_try(B(B_VF + ((g - 1) & 1)), ((g - 1) >> 1) & 1);
        at_sum(P, f & F_PHALF, l0, l1);
        fn = __shfl_sync(~0u, kinds, max(g - 2, 0));
        if (UNLIKELY(!vok)) mbar_wait_c(B(B_VF + ((g - 1) & 1)), ((g - 1) >> 1) & 1);
      };
      auto hand_over = [&]() { __syncwarp(); if (lane == 0 && !((fail >> (t - 1)) & 1)) mbar_arrive(B(B_PUB + 1 + t)); };
      auto exp_q = [&](float* S, auto kc, auto nc) {
        constexpr int k = decltype(kc)::value, n = decltype(nc)::value;
        asm volatile("{\n.reg .pred p;\nsetp.ne.b32 p, %5, 0;\n@p ldmatrix.sync.aligned.m8n8.x4.shared.b16 {%0,%1,%2,%3}, [%4];\n}"
                     : "+r"(Q[4 * k]), "+r"(Q[4 * k + 1]), "+r"(Q[4 * k + 2]), "+r"(Q[4 * k + 3])
                     : "r"(((q_ld + piece(t + 1)) ^ ((k & 1) << 5)) + (k >> 1) * 4096), "r"(f & F_LAST) : "memory");
        at_exp<n * k, n * k + n>(S);
      };
      g = 1; par = SLOT / 16;
#pragma unroll 1
      for (;;) {
        {
          TC(g, 0);
          bar_sync(1 + w, 256);
          fence_regs<32>(Q);
          float S[64];
          wg_fence();
          issue_s(S);
          sched_fence(q_st);
          TC(g, 1);
          shadow();
          fence_regs<64>(O); fence_regs<32>(P);
          issue_pv(f & F_PHALF, ~f & F_PFIRST);
          fence_regs<64>(S);
          TC(g, 2);
          release_k();
          at_exp<0, 8>(S);
          const bool first = f & F_FIRST;
          if (UNLIKELY(f & (F_FIRST | F_LAST | F_DIAG))) {
            row_inv(first);
            at_mask(S + 32, (f & F_DIAG) ? wrow - 64 : 64, lane);
            unroll8([&](auto kc) { exp_q(S + 8, kc, std::integral_constant<int, AT_R1 / 8 - 1>{}); });
          } else {
            at_exp<8, AT_R1>(S);
          }
          pv_done();
          g = pinned(g + 1); par = pinned(par ^ (SLOT / 16)); f = fn;
          const bool kok = mbar_try(B(B_KF + (g & 1)), g < 34 ? (g >> 1) & 1 : 0);
          if (UNLIKELY(first)) {
            unroll8([&](auto ic) {
              constexpr int i = decltype(ic)::value, n = (64 - AT_R1) / 8;
              at_exp<AT_R1 + n * i, AT_R1 + n * i + n>(S);
              park(piece(t), i, scaled(i));
            });
            at_fin<0, 64>(S, P);
            hand_over();
          } else {
            at_exp<AT_R1, 64>(S); at_fin<0, 64>(S, P);
          }
          TC(g - 1, 5);
          if (!TCLK) TL(1, 1 + g, tid == 128);
          if (kok && !(f & F_STOP)) continue;
          if (UNLIKELY(!kok)) mbar_wait_c(B(B_KF + (g & 1)), (g >> 1) & 1);
          if (g == 34) break;
        }
#pragma unroll 1
        while (f & F_STOP) {
          TC(g, 0);
          bar_sync(1, 256);
          fence_regs<64>(O); fence_regs<32>(Q); fence_regs<32>(P);
          float S[32];
          const uint64_t dk = desc_add(dk0, par * 16);
          wg_fence();
          mma_n64_rs0(S, Q, dk);
#pragma unroll
          for (int k = 1; k < 8; k++) mma_n64_rs(S, Q + 4 * k, desc_add(dk, (k >> 2) * 16384 + (k & 3) * 32), 1);
          wg_commit();
          TC(g, 1);
          mbar_wait_c(B(B_VF + ((g - 1) & 1)), ((g - 1) >> 1) & 1);
          issue_pv(f & F_PHALF, ~f & F_PFIRST);
          fence_regs<32>(S);
          TC(g, 2);
          release_k();
          const bool first = f & F_FIRST;
          at_sum(P, f & F_PHALF, l0, l1);
          fn = __shfl_sync(~0u, kinds, g - 2);
          row_inv(first);
          pv_done();
          sched_fence(q_st);
          at_mask(S, wrow, lane);
          unroll8([&](auto kc) { exp_q(S, kc, std::integral_constant<int, 4>{}); });
          g++; par ^= SLOT / 16; f = fn;
          at_fin<0, 32>(S, P);
          if (first) {
#pragma unroll
            for (int i = 0; i < 8; i++) park(piece(t), i, scaled(i));
            hand_over();
          }
          TC(g - 1, 5);
          if (!TCLK) TL(1, 1 + g, tid == 128);
          mbar_wait_c(B(B_KF + (g & 1)), (g >> 1) & 1);
        }
      }
      const bool wok = mbar_test(B(ffn ? B_WF : B_QP + 1), 0);
      grab(wf, 3 * SLOT, 0, 8);
      mbar_wait_c(B(B_VF + 1), 0);
      bar_sync(1 + w, 256);
      fence_regs<64>(O); fence_regs<32>(P);
      wg_fence();
#pragma unroll
      for (int k = 0; k < 8; k++) mma_n128_rs<1>(O, P + 4 * k, desc_add(dv0, 2 * SLOT + k * 2048), 1);
      wg_commit();
      if (w == 0) bar_arrive(2, 256);
      pin_order(__uint_as_float(wf[28] & wf[24]), pin);
      __syncwarp();
      if (wok) release2(B_WE);
      TL(3, 12 + 16 * w, (tid & 127) == 0);
      sched_fence(q_st);
      at_sum(P, false, l0, l1);
      row_inv(true);
      sched_fence(q_st);
      wg_wait<0>();
      fence_regs<64>(O); fence_regs<32>(P);
      release2(B_VE + 1);
      if (UNLIKELY(!wok || fail != 0)) {
#pragma unroll 1
        for (int tt = 0; tt < 4; tt++) {
          if (!((tt < 3 ? fail >> tt : fail != 0) & 1)) continue;
          slow_tile(O, P, l0, l1, wq, (((tt + 1) & 2) ? ti : 15 - ti) * 128 + wrow, hh + (tt & 2) * 8, lane, q_st);
          row_inv(false);
          if (tt < 3) {
#pragma unroll
            for (int i = 0; i < 8; i++) park(piece(tt + 1), i, scaled(i));
            publish(2 + tt);
          }
        }
        if (!wok) {
          mbar_wait_c(B(ffn ? B_WF : B_QP + 1), 0);
          grab(wf, 3 * SLOT, 0, 8);
          pin_order(__uint_as_float(wf[28] & wf[24]), pin);
          __syncwarp();
          release2(B_WE);
        }
      }
      TL(3, 13 + 16 * w, (tid & 127) == 0);
      issue3(0, 0, 0);
      TL(3, 14 + 16 * w, (tid & 127) == 0);
      TL(1, 36, tid == 128);
    }
    uint32_t hp[32];
    lane = lane_id();
    {
      int st = 1, prev = 0; uint32_t ph = 0;
      __nv_bfloat16* dst = g_qkv + (size_t)((15 - ti) * 128 + cw * 16 + (lane >> 2)) * NQ + hh * 128 + (lane & 3) * 8;
      auto kblock = [&](auto between, int lim = 6) {
        issue3(st, ph, 1);
        between();
        wg_wait<1>();
        release2(B_EMPTY3 + prev);
        prev = st;
        if (++st == lim) { st = 0; ph ^= 1; }
      };
      uint4 ob[8];
      kblock([&]() { sched_fence(rbar); ob[0] = scaled(0); ob[1] = scaled(2); ob[2] = scaled(1); ob[3] = scaled(3); sched_fence(rbar); });
      kblock([&]() { sched_fence(rbar); ob[4] = scaled(4); ob[5] = scaled(6); ob[6] = scaled(5); ob[7] = scaled(7); sched_fence(rbar); grab(wf + 32, 5 * SLOT, 0, 8); });
#pragma unroll 1
      for (int kb = 3; kb < 11; kb++) {
        kblock([&]() {
          sched_fence(rbar);
#pragma unroll
          for (int i = 0; i < 8; i++)
            if (kb == 3 + i) *reinterpret_cast<uint4*>(dst + (i & 2) * 4 * NQ + (i & 1) * 32 + (i & 4) * 16) = ob[i];
          TL(3, 14 + kb + 16 * w, (tid & 127) == 0);
          if (kb == 8) TL(2, 2, tid == 128);
        }, kb == 4 ? 5 : 6);
        if (kb == 4) release2(B_EMPTY3 + 5);
      }
      publish(5);
      kblock([&]() { mbar_wait_c(B(ffn ? B_WF2 : B_QP + 2), 0); grab(wf + 32, 5 * SLOT, 8, 16); });
#pragma unroll 1
      for (int kb = 12; kb < G_KB; kb++) {
        kblock([&]() { if ((kb & 7) == 0) TL(2, 1 + (kb >> 3), tid == 128); });
        if (kb == X_KB && lane == 0) mbar_arrive(B(B_XE));
      }
      kblock([&]() {
        mbar_wait_c(B(B_XF), 0);
#pragma unroll
        for (int i = 0; i < 8; i++)
          ldsm4(hp + 4 * i, sb + 6 * SLOT + w * 16384 + ((cw & 3) * 16 + (lane & 15)) * 128 + (i >> 2) * 8192 + ((((i & 3) * 2 + (lane >> 4)) ^ (lane & 7)) << 4));
      });
#pragma unroll 1
      for (int kb = G_KB + 1; kb < 64; kb++) {
        kblock([&]() { if ((kb & 7) == 0) TL(2, 1 + (kb >> 3), tid == 128); });
        if (kb == G_KB + 2 && lane == 0) mbar_arrive(B(B_XE));
      }
    }
    lane = lane_id();
    const int r0 = lane >> 2, q4 = lane & 3, ct = cw * 32 + lane;
    uint32_t tb[16];
    mbar_wait_c(B(B_WR), 0);
#pragma unroll
    for (int i = 0; i < 4; i++) ldsm4(tb + 4 * i, sb + OFF_MISC + 512 + (lane & 1) * 256 + (lane >> 3) * 16 + i * 64);
    mbar_wait_c(B(B_SET2), 0);
    float4* const psd = reinterpret_cast<float4*>(xr + XR_PS + cw * 16 + r0);
    const uint4* const pss = g_xr + (mt * 8 + (ct & 1) * 4) * XR_SIZE + XR_PS + (ct >> 1);
    sched_fence(stg);
    wg_wait<0>();
    fence_regs<64>(acc);
    TL(2, 10, tid == 128);
    {
      float d[2][4] = {}, qa[2][4] = {}, qb[2][4] = {};
#pragma unroll
      for (int j = 0; j < 16; j++) {
        hp[2 * j] = hadd2_bf(hp[2 * j], pack_bf16(acc[4 * j], acc[4 * j + 1]));
        hp[2 * j + 1] = hadd2_bf(hp[2 * j + 1], pack_bf16(acc[4 * j + 2], acc[4 * j + 3]));
        if (j & 1) {
          mma16816(d[(j >> 1) & 1], hp[2 * j - 2], hp[2 * j - 1], hp[2 * j], hp[2 * j + 1], tb[j - 1], tb[j]);
          mma16816(qa[(j >> 1) & 1], hp[2 * j - 2], hp[2 * j - 1], hp[2 * j], hp[2 * j + 1], hp[2 * j - 2], hp[2 * j]);
          mma16816(qb[(j >> 1) & 1], hp[2 * j - 2], hp[2 * j - 1], hp[2 * j], hp[2 * j + 1], hp[2 * j - 1], hp[2 * j + 1]);
        }
      }
      if (q4 == (r0 >> 1)) {
        __stcg(psd, make_float4(d[0][0] + d[1][0], (r0 & 1) ? qa[0][1] + qa[1][1] : qa[0][0] + qa[1][0], d[0][1] + d[1][1], 0.f));
        __stcg(psd + 8, make_float4(d[0][2] + d[1][2], (r0 & 1) ? qb[0][3] + qb[1][3] : qb[0][2] + qb[1][2], d[0][3] + d[1][3], 0.f));
      }
    }
    TL(2, 11, tid == 128);
    mbar_wait_c(B(B_EMPTY3 + 1), 0);
    stage_store_128(stg, lane, hp);
    if (ffn) mbar_wait_c(B(B_WF2), 1);
    grab(wf + 96, 6 * SLOT, 0, 8);
    const float wsum = *reinterpret_cast<const float*>(sp + OFF_MISC + 1024);
    __syncwarp();
    {
      uint4 ps[4];
      poll_chunks(ps, pss, XR_SIZE);
      TL(2, 12, tid == 128);
      auto F = [](uint32_t u) { return __uint_as_float(u); };
      float s1 = (F(ps[0].x) + F(ps[1].x)) + (F(ps[2].x) + F(ps[3].x)), s2 = (F(ps[0].y) + F(ps[1].y)) + (F(ps[2].y) + F(ps[3].y));
      float s3 = (F(ps[0].z) + F(ps[1].z)) + (F(ps[2].z) + F(ps[3].z));
      __syncwarp();
      s1 += __shfl_xor_sync(~0u, s1, 1); s2 += __shfl_xor_sync(~0u, s2, 1); s3 += __shfl_xor_sync(~0u, s3, 1);
      const float mean = s1 * (1.f / DM);
      float mb, inv;
      ln_round(mean, fmaxf(fmaf(s2, 1.f / DM, -mean * mean), 0.f), mb, inv);
      const uint32_t u = pack_bf16(0.f, fmaf(s3 - mb * wsum, inv, 0.f));
      const uint32_t key = (u ^ ((((int)u >> 31) & 0x7FFF0000u) | 0x80000000u)) | (0x7FFFu - (mt * 128 + (ct >> 1)));
      const uint32_t nm2 = pack_bf16(-mb, -mb);
      const uint32_t c1 = __reduce_max_sync(~0u, key);
      const uint32_t c2 = __reduce_max_sync(~0u, key == c1 ? 0u : key);
      if (lane == 0) {
        __stcg(reinterpret_cast<uint2*>(psd) + (XR_KEY - XR_PS) * 2 - cw * 31, make_uint2(c1, c2));
        mbar_arrive(B(B_OUT));
      }
      TL(2, 13, tid == 128);
      const int row = (0x7FFF - (((lane >> 4) ? c2 : c1) & 0x7FFF)) & 15;
      const uint32_t rn = __shfl_sync(~0u, nm2, row * 2);
      const uint2 ri = ln_split(__shfl_sync(~0u, inv, row * 2));
      uint32_t v[4];
#pragma unroll
      for (int i = 0; i < 4; i++)
        asm volatile("ld.shared.u32 %0, [%1];" : "=r"(v[i]) : "r"(stg + ((lane >> 3) & 1) * 8192 + row * 128 + ((((lane & 4) + i) ^ (row & 7)) << 4) + q4 * 4) : "memory");
      __stcg(xr + XR_CAND + cw * 64 + 32 + lane, make_uint4(ln_apply(v[0], rn, ri), ln_apply(v[1], rn, ri), ln_apply(v[2], rn, ri), ln_apply(v[3], rn, ri)));
      __stcg(xr + XR_CAND + cw * 64 + lane, make_uint4(v[0], v[1], v[2], v[3]));
      sched_fence(stg);
      const uint32_t na = __shfl_sync(~0u, nm2, r0 * 2), nb = __shfl_sync(~0u, nm2, r0 * 2 + 16);
      const uint2 ia = ln_split(__shfl_sync(~0u, inv, r0 * 2)), ib = ln_split(__shfl_sync(~0u, inv, r0 * 2 + 16));
#pragma unroll
      for (int i = 0; i < 32; i++) hp[i] = hadd2_bf(hp[i], ln_apply(hp[i], (i & 1) ? nb : na, (i & 1) ? ib : ia));
      __syncwarp();
      stage_store_128(stg, lane, hp);
      publish(B_OUT3 - B_PUB);
    }
    uint32_t wd[16][4];
    sched_fence(stg);
    if (ffn) mbar_wait_c(B(B_FULL3 + 5 * w), 1 - w);
    auto load_wd = [&](int h) {
#pragma unroll
      for (int i = h; i < 16; i += 2)
        asm volatile("ldmatrix.sync.aligned.m8n8.x4.trans.shared.b16 {%0,%1,%2,%3}, [%4];"
                     : "=r"(wd[i][0]), "=r"(wd[i][1]), "=r"(wd[i][2]), "=r"(wd[i][3])
                     : "r"(sb + OFF_R3 + 5 * w * SLOT + (2 * (cw & 3) + (i >> 3)) * 4096 + (h * 16 + (lane & 7) + (lane >> 4) * 8) * 128 +
                           (((2 * ((i >> 1) & 3) + ((lane >> 3) & 1)) ^ (lane & 7)) << 4)) : "memory");
    };
    load_wd(0);
    __syncwarp();
    cluster_arrive();
    const char* xsrc = reinterpret_cast<const char*>(g_xr + (r0 >> 1) * XR_SIZE + XR_CAND + 32 + (cw >> 1) * 4 + q4);
    asm volatile("" : "+l"(xsrc));
    sched_fence(stg);
    TL(2, 22, tid == 128);
    mbar_wait_c(B(B_OUT2), 0);
    TL(2, 14, tid == 128);
    if (ffn) {
      uint4 xb[2];
      const uint4* xp = reinterpret_cast<const uint4*>(xsrc + *reinterpret_cast<const uint32_t*>(sp + OFF_MISC + 8 + (r0 & 1) * 4));
      poll_chunks(xb, xp, 4 * XR_SIZE);
      __syncwarp();
      TL(2, 15, tid == 128);
      float d[8][4] = {};
#pragma unroll
      for (int n = 0; n < 32; n++) {
        if (n == 8) { sched_fence(stg); load_wd(1); }
        const int s = (n >> 4) * 4 + ((n >> 1) & 3), m = ((n >> 3) & 1) * 2 + (n & 1);
        const uint32_t* a = wf + 16 * s + 4 * m;
        mma16816(d[n & 7], a[0], a[1], a[2], a[3], (m & 2) ? xb[s >> 2].z : xb[s >> 2].x, (m & 2) ? xb[s >> 2].w : xb[s >> 2].y);
      }
      float v[8];
#pragma unroll
      for (int i = 0; i < 8; i++) {
        const float lo = (q4 & 1) ? d[2 + (i >> 2)][i & 3] : d[i >> 2][i & 3], hi = (q4 & 1) ? d[6 + (i >> 2)][i & 3] : d[4 + (i >> 2)][i & 3];
        v[i] = (q4 & 2) ? hi : lo;
      }
#pragma unroll
      for (int i = 0; i < 4; i++) v[i] = ((q4 & 2) ? v[i + 4] : v[i]) + __shfl_xor_sync(~0u, (q4 & 2) ? v[i] : v[i + 4], 2);
#pragma unroll
      for (int i = 0; i < 2; i++) v[i] = ((q4 & 1) ? v[i + 2] : v[i]) + __shfl_xor_sync(~0u, (q4 & 1) ? v[i] : v[i + 2], 1);
      float4* red = reinterpret_cast<float4*>(sp + SL_SCR * SLOT);
      reinterpret_cast<float2*>(red + cw * 16 + (q4 >> 1) * 8 + r0)[q4 & 1] = make_float2(v[0], v[1]);
      bar_sync(3, 256);
      TL(2, 16, tid == 128);
      const float4 z0 = red[lane], z1 = red[32 + lane], z2 = red[64 + lane], z3 = red[96 + lane];
      const uint32_t ub = pack_bf16((z0.x + z1.x) + (z2.x + z3.x), (z0.y + z1.y) + (z2.y + z3.y));
      const uint32_t gb = pack_bf16((z0.z + z1.z) + (z2.z + z3.z), (z0.w + z1.w) + (z2.w + z3.w));
      const float g0 = bf_lo(gb), g1 = bf_hi(gb);
      const uint32_t sg = pack_bf16(g0 * sigmoid(g0), g1 * sigmoid(g1));
      const uint32_t act = pack_bf16(bf_lo(sg) * bf_lo(ub), bf_hi(sg) * bf_hi(ub));
      const uint32_t pr = __byte_perm(act, __shfl_xor_sync(~0u, act, 1), (lane & 1) ? 0x3276 : 0x5410);
      const int src = q4 * 2 + (r0 & 1);
      const uint32_t a0 = __shfl_sync(~0u, pr, src), a1 = __shfl_sync(~0u, pr, src + 8), a2 = __shfl_sync(~0u, pr, src + 16), a3 = __shfl_sync(~0u, pr, src + 24);
      TL(2, 17, tid == 128);
      float y[8][4] = {};
#pragma unroll
      for (int i = 0; i < 8; i++) mma16816(y[i], wd[2 * i][0], wd[2 * i][1], wd[2 * i][2], wd[2 * i][3], a0, a1);
#pragma unroll
      for (int i = 0; i < 8; i++) mma16816(y[i], wd[2 * i + 1][0], wd[2 * i + 1][1], wd[2 * i + 1][2], wd[2 * i + 1][3], a2, a3);
      float2* yd = reinterpret_cast<float2*>(g_xr + (cw * 16 + 2 * q4) * XR_SIZE + XR_Y + fid * 4) + r0;
#pragma unroll
      for (int j = 0; j < 2; j++) {
        float v[4];
#pragma unroll
        for (int e = 0; e < 4; e++) {
          const float lo = (q4 & 1) ? y[4 * j + 1][e] : y[4 * j][e], hi = (q4 & 1) ? y[4 * j + 3][e] : y[4 * j + 2][e];
          v[e] = (q4 & 2) ? hi : lo;
        }
        __stcg(yd + j * 16 * XR_SIZE, make_float2(v[0], v[1]));
        __stcg(yd + j * 16 * XR_SIZE + 2 * XR_SIZE, make_float2(v[2], v[3]));
      }
    }
    TL(2, 18, tid == 128);
    cluster_wait();
    if (rid == 127 && ct < C_NUM) g_cnt[ct] = 0;
    if (cw < 2) {
      const int tok = (lane >> 1) & 1, pair = cw * 2 + (lane & 1);
      uint32_t* const dst = reinterpret_cast<uint32_t*>(out + (size_t)(~*reinterpret_cast<const uint32_t*>(sp + OFF_MISC + tok * 4) & 0x7FF) * DM) + rid * 4 + pair;
      idle(ffn ? Y_CLK : Y_CLK + 2000);
      const bool fin = mbar_test(B(B_FIN), 0);
      uint4 op = lds128(sb + OFF_MISC + 128 + (tok * 4 + pair) * 16);
      uint4 z[7];
      poll_chunks(z, xr + XR_Y + (lane >> 1) * 4 + pair, 64);
      __syncwarp();
      TL(2, 19, tid == 128);
      if (!fin) { mbar_wait_c(B(B_FIN), 0); op = lds128(sb + OFF_MISC + 128 + (tok * 4 + pair) * 16); }
      auto F = [](uint32_t u) { return __uint_as_float(u); };
      const float v0 = ((F(z[0].x) + F(z[1].x)) + (F(z[2].x) + F(z[3].x))) + ((F(z[4].x) + F(z[5].x)) + F(z[6].x));
      const float v1 = ((F(z[0].y) + F(z[1].y)) + (F(z[2].y) + F(z[3].y))) + ((F(z[4].y) + F(z[5].y)) + F(z[6].y));
      const float v2 = ((F(z[0].z) + F(z[1].z)) + (F(z[2].z) + F(z[3].z))) + ((F(z[4].z) + F(z[5].z)) + F(z[6].z));
      const float v3 = ((F(z[0].w) + F(z[1].w)) + (F(z[2].w) + F(z[3].w))) + ((F(z[4].w) + F(z[5].w)) + F(z[6].w));
      float ya = (tok ? v1 : v0) + __shfl_xor_sync(~0u, tok ? v0 : v1, 2), yb = (tok ? v3 : v2) + __shfl_xor_sync(~0u, tok ? v2 : v3, 2);
#pragma unroll
      for (int o = 4; o < 32; o <<= 1) { ya += __shfl_xor_sync(~0u, ya, o); yb += __shfl_xor_sync(~0u, yb, o); }
      const uint32_t yp = pack_bf16(ya, yb);
      if (lane < 4) *dst = hadd2_bf(op.x, hadd2_bf(op.y, pack_bf16(bf_lo(yp) * F(op.z), bf_hi(yp) * F(op.z))));
      TL(2, 21, tid == 128);
    }
    TL(2, 20, tid == 128);
    TL_DUMP();
  }
}

typedef CUresult (*EncodeFn)(CUtensorMap*, CUtensorMapDataType, cuuint32_t, void*, const cuuint64_t*, const cuuint64_t*, const cuuint32_t*,
                             const cuuint32_t*, CUtensorMapInterleave, CUtensorMapSwizzle, CUtensorMapL2promotion, CUtensorMapFloatOOBfill);
EncodeFn g_enc = nullptr;

void map2(CUtensorMap* m, const void* ptr, uint64_t rows, uint64_t cols, uint32_t bc, uint32_t br) {
  const CUtensorMapSwizzle sw = bc == 64 ? CU_TENSOR_MAP_SWIZZLE_128B : CU_TENSOR_MAP_SWIZZLE_64B;
  cuuint64_t gd[2] = {cols, rows}, gs[1] = {cols * 2};
  cuuint32_t bd[2] = {bc, br}, es[2] = {1, 1};
  g_enc(m, CU_TENSOR_MAP_DATA_TYPE_BFLOAT16, 2, (void*)ptr, gd, gs, bd, es, CU_TENSOR_MAP_INTERLEAVE_NONE, sw,
        CU_TENSOR_MAP_L2_PROMOTION_L2_128B, CU_TENSOR_MAP_FLOAT_OOB_FILL_NONE);
}
void map3(CUtensorMap* m, const void* ptr, uint64_t rows, uint64_t cols, uint32_t br, uint32_t bch, uint32_t bc = 64) {
  cuuint64_t gd[3] = {bc, rows, cols / bc}, gs[2] = {cols * 2, bc * 2};
  cuuint32_t bd[3] = {bc, br, bch}, es[3] = {1, 1, 1};
  g_enc(m, CU_TENSOR_MAP_DATA_TYPE_BFLOAT16, 3, (void*)ptr, gd, gs, bd, es, CU_TENSOR_MAP_INTERLEAVE_NONE, bc == 64 ? CU_TENSOR_MAP_SWIZZLE_128B : CU_TENSOR_MAP_SWIZZLE_64B,
        CU_TENSOR_MAP_L2_PROMOTION_L2_128B, CU_TENSOR_MAP_FLOAT_OOB_FILL_NONE);
}

}

extern "C" void kernel_launch(void* const* d_in, const int* in_sizes, int n_in, void* d_out, int out_size) {
  const __nv_bfloat16* x = (const __nv_bfloat16*)d_in[0];
  const __nv_bfloat16* ckv = (const __nv_bfloat16*)d_in[1];
  const __nv_bfloat16* wq = (const __nv_bfloat16*)d_in[2];
  const __nv_bfloat16* wk = (const __nv_bfloat16*)d_in[3];
  const __nv_bfloat16* wv = (const __nv_bfloat16*)d_in[4];
  const __nv_bfloat16* wo = (const __nv_bfloat16*)d_in[5];
  const __nv_bfloat16* w_r = (const __nv_bfloat16*)d_in[7];
  const __nv_bfloat16* wgate = (const __nv_bfloat16*)d_in[8];
  const __nv_bfloat16* wup = (const __nv_bfloat16*)d_in[9];
  const __nv_bfloat16* wdown = (const __nv_bfloat16*)d_in[10];
  __nv_bfloat16* out = (__nv_bfloat16*)d_out;

  if (!g_enc) {
    void* fn = nullptr;
    cudaDriverEntryPointQueryResult qr;
    cudaGetDriverEntryPoint("cuTensorMapEncodeTiled", &fn, cudaEnableDefault, &qr);
    g_enc = (EncodeFn)fn;
    cudaFuncSetAttribute(fused_kernel, cudaFuncAttributeMaxDynamicSharedMemorySize, SMEM_BYTES);
  }
  void *xn, *qkv;
  cudaGetSymbolAddress(&xn, g_xn);
  cudaGetSymbolAddress(&qkv, g_qkv);

  Params p;
  map2(&p.xn, xn, SEQ, DM, 64, 128);
  map2(&p.ckv, ckv, SEQ, DC, 64, 128);
  map3(&p.wq, wq, DM, NQ, 64, 2);
  map3(&p.wk, wk, DC, NQ, 64, 2);
  map3(&p.wv, wv, DC, NQ, 64, 2);
  map3(&p.kv, qkv, 2 * SEQ, NQ, 128, 1);
  map2(&p.ctx_ld, qkv, 2 * SEQ, NQ, 64, 128);
  map3(&p.ctx_st, qkv, 2 * SEQ, NQ, 64, 1, 32);
  map3(&p.wo, wo, NQ, DM, 64, 1);
  map3(&p.x, x, SEQ, DM, 64, 1);
  map3(&p.wd, wdown, FF, DM, 32, 8);
  map2(&p.out, out, SEQ, DM, 64, 64);
  map2(&p.wg, wgate, DM, FF, 32, 128);
  map2(&p.wu, wup, DM, FF, 32, 128);
  fused_kernel<<<128, 384, SMEM_BYTES, cudaStreamPerThread>>>(x, wq, w_r, out, p);
}
```
